```python
import torch

def _softmax(x, axis=-1):
    return torch.softmax(x, dim=axis)

def _gelu(x):
    return torch.nn.functional.gelu(x, approximate='tanh')

def _silu(x):
    return torch.nn.functional.silu(x)

def _sigmoid(x):
    return torch.sigmoid(x)

def _layernorm(x, axis=-1, eps=1e-05):
    m = x.mean(dim=axis, keepdim=True)
    v = x.var(dim=axis, keepdim=True, unbiased=False)
    return (x - m) / torch.sqrt(v + eps)

def _scatter_add(tgt, idx, src, axis=0):
    return tgt.clone().index_add_(axis, idx, src)

def _segment_sum(src, seg, n):
    out = torch.zeros((n,) + src.shape[1:], dtype=src.dtype)
    return out.index_add_(0, seg, src)

def _pad(x, pw):
    flat = tuple((v for pair in reversed(pw) for v in pair))
    return torch.nn.functional.pad(x, flat)
kernel_name = 'adaLN_cond__gqa_block_cached__moe_arch_mod__prompt'

def setup_inputs():

    _w = lambda a: (lambda t: t.to(torch.bfloat16) if t.is_floating_point() else t)(torch.as_tensor(a))

    def _A_setup():
        B, Sq, D = (1, 2048, 576)
        Hq, Hkv, Sk, Dh = (32, 16, 2048, 128)
        assert Hq % Hkv == 0, (Hq, Hkv)
        return {'x': _w((lambda *s: torch.randn(*s, dtype=torch.bfloat16) * 0.1)(B, Sq, D)), 'k_cache': _w((lambda *s: torch.randn(*s, dtype=torch.bfloat16) * 0.8)(B, Hkv, Sk, Dh)), 'v_cache': _w((lambda *s: torch.randn(*s, dtype=torch.bfloat16) * 0.8)(B, Hkv, Sk, Dh)), 'wq': _w((lambda *s: torch.randn(*s, dtype=torch.bfloat16) * 0.8)(D, Hq * Dh) * D ** (-0.5)), 'wo': _w((lambda *s: torch.randn(*s, dtype=torch.bfloat16) * 0.8)(Hq * Dh, D) * (Hq * Dh) ** (-0.5))}
    _A_in = _A_setup()

    def _B_setup():
        B, S, D, F, C = (1, 2048, 576, 4608, 2)
        return {'x': _w((lambda *s: torch.randn(*s, dtype=torch.bfloat16) * 0.1)(B, S, D)), 'w_r': _w((lambda *s: torch.randn(*s, dtype=torch.bfloat16) * 3.2)(D)), 'w_gate': _w((lambda *s: torch.randn(*s, dtype=torch.bfloat16) * 0.2)(D, F)), 'w_up': _w((lambda *s: torch.randn(*s, dtype=torch.bfloat16) * 0.2)(D, F)), 'w_down': _w((lambda *s: torch.randn(*s, dtype=torch.bfloat16) * 0.2)(F, D))}
    _B_in = _B_setup()
    return {'A_x': _A_in['x'], 'A_k_cache': _A_in['k_cache'], 'A_v_cache': _A_in['v_cache'], 'A_wq': _A_in['wq'], 'A_wo': _A_in['wo'], 'B_x': _B_in['x'], 'B_w_r': _B_in['w_r'], 'B_w_gate': _B_in['w_gate'], 'B_w_up': _B_in['w_up'], 'B_w_down': _B_in['w_down'], 'c': _w((lambda *s: torch.randn(*s, dtype=torch.bfloat16) * 0.4)(1, 576) * 8.0), 'w_mod': _w((lambda *s: torch.randn(*s, dtype=torch.bfloat16) * 0.4)(576, 6 * 576) * 576 ** (-0.5) * 8.0)}

def reference(A_x, A_k_cache, A_v_cache, A_wq, A_wo, B_x, B_w_r, B_w_gate, B_w_up, B_w_down, c, w_mod):

    def _A_ref(x, k_cache, v_cache, wq, wo):
        B, Sq, D = x.shape
        Hq, Dh = (32, 128)
        Hkv = k_cache.shape[1]
        rep = Hq // Hkv
        q = (lambda x, *d: x.permute(*d))((x @ wq).reshape(B, Sq, Hq, Dh), 0, 2, 1, 3)
        k = (lambda x, n, axis: torch.repeat_interleave(x, n, dim=axis))(k_cache, rep, axis=1)
        v = (lambda x, n, axis: torch.repeat_interleave(x, n, dim=axis))(v_cache, rep, axis=1)
        scores = torch.einsum('bhqd,bhkd->bhqk', q, k) * Dh ** (-0.5)
        p = _softmax(scores, axis=-1)
        o = torch.einsum('bhqk,bhkd->bhqd', p, v)
        return (lambda x, *d: x.permute(*d))(o, 0, 2, 1, 3).reshape(B, Sq, Hq * Dh) @ wo

    def _B_ref(x, w_r, w_gate, w_up, w_down):
        B, S, D = x.shape
        C = 2
        r = x @ w_r
        idx = torch.argsort(-r, axis=-1)[:, :C]
        idx_e = (lambda x, n, axis: torch.repeat_interleave(x, n, dim=axis))(idx.reshape(B, C, 1), D, axis=2)
        x_sel = (lambda x, i, axis: torch.take_along_dim(x, i, dim=axis))(x, idx_e, axis=1)
        g = _silu(x_sel @ w_gate)
        u = x_sel @ w_up
        y = g * u @ w_down
        r_sel = _sigmoid((lambda x, i, axis: torch.take_along_dim(x, i, dim=axis))(r, idx, axis=1))
        y = y * r_sel.reshape(B, C, 1)
        b_off = (torch.arange(B) * S).reshape(B, 1)
        flat_idx = (idx + b_off).reshape(B * C)
        zero = (x * 0.0).reshape(B * S, D)
        upd = _scatter_add(zero, flat_idx, y.reshape(B * C, D), axis=0)
        return x + upd.reshape(B, S, D)
    x = A_x
    mod = (_silu(c) @ w_mod).reshape(c.shape[0], 6, 1, -1)
    sa, ca, ga, sb, cb, gb = (mod[:, 0].clone(), mod[:, 1].clone(), mod[:, 2].clone(), mod[:, 3].clone(), mod[:, 4].clone(), mod[:, 5].clone())
    h = _layernorm(x, axis=-1) * (1 + ca) + sa
    x = x + ga * _A_ref(h, A_k_cache, A_v_cache, A_wq, A_wo)
    h = _layernorm(x, axis=-1) * (1 + cb) + sb
    x = x + gb * _B_ref(h, B_w_r, B_w_gate, B_w_up, B_w_down)
    return x
```

```cpp
#include <cuda_runtime.h>
#include <cuda_bf16.h>
#include <cuda.h>
#include <stdint.h>

typedef __nv_bfloat16 bf16;

constexpr int SQ = 2048, DM = 576, HQ = 32, HKV = 16, SK = 2048, DH = 128, FF = 4608;

#define MC 1

#define LAZY_LIMIT 1.0995116e12f
__device__ uint4 g_mod1[144];
__device__ uint4 g_mod2[288];
__device__ uint4 g_q[128 * 4 * 8 * 256];
__device__ float4 g_acc[16 * 2 * 72 * 4 * 32];
__device__ __align__(16) float g_y[2 * DM];
__device__ uint4 g_key[512];
__device__ uint32_t g_h2[SQ * DM / 2], g_x2[SQ * DM / 2];
__device__ unsigned int g_cnt[32 * 32];
__device__ unsigned int g_err;
#define HAS_ERR
enum { C_SIDE = 1, C_Y = 3, C_Q = 8 };

#define STAMP(i)
#define GSTAMP(i)
#define SETERR(v)

__device__ __forceinline__ uint32_t smem_u32(const void* p) { return (uint32_t)__cvta_generic_to_shared(p); }
__device__ __forceinline__ void mbar_init(uint32_t a, uint32_t cnt) { asm volatile("mbarrier.init.shared::cta.b64 [%0], %1;" ::"r"(a), "r"(cnt)); }
__device__ __forceinline__ void mbar_expect_tx(uint32_t a, uint32_t bytes) { asm volatile("mbarrier.arrive.expect_tx.shared::cta.b64 _, [%0], %1;" ::"r"(a), "r"(bytes) : "memory"); }
__device__ __forceinline__ void mbar_arrive_cl(uint32_t a_cluster) { asm volatile("mbarrier.arrive.shared::cluster.b64 _, [%0];" ::"r"(a_cluster) : "memory"); }
__device__ __forceinline__ void mbar_wait(uint32_t a, uint32_t parity) {
  asm volatile(
      "{\n.reg .pred p;\n.reg .u32 n;\nmov.u32 n, 0;\n"
      "WAIT_LOOP:\n"
      "mbarrier.try_wait.parity.shared::cta.b64 p, [%0], %1;\n"
      "@p bra WAIT_DONE;\n"
      "add.u32 n, n, 1;\n"
      "setp.lt.u32 p, n, 65536;\n"
      "@p bra WAIT_LOOP;\n"
      "WAIT_DONE:\n}\n" ::"r"(a), "r"(parity), "l"(&g_err) : "memory");
}
__device__ __forceinline__ unsigned ld_acquire(const unsigned* p) {
  unsigned v;
  asm volatile("ld.acquire.gpu.global.u32 %0, [%1];" : "=r"(v) : "l"(p) : "memory");
  return v;
}
__device__ __forceinline__ void cnt_wait(int idx, unsigned target) {
  uint32_t n = 0;
  while (ld_acquire(&g_cnt[idx * 32]) < target) {
    if (++n > (1u << 15)) { SETERR(2); break; }
  }
}
__device__ __forceinline__ unsigned cnt_arrive(int idx) {
  unsigned old;
  asm volatile("atom.add.acq_rel.gpu.global.u32 %0, [%1], 1;" : "=r"(old) : "l"(&g_cnt[idx * 32]) : "memory");
  return old;
}
__device__ __forceinline__ uint4 poll4(const uint4* p) {
  uint4 v;
  uint32_t n = 0;
  while (true) {
    asm volatile("ld.relaxed.gpu.global.v4.u32 {%0,%1,%2,%3}, [%4];" : "=r"(v.x), "=r"(v.y), "=r"(v.z), "=r"(v.w) : "l"(p) : "memory");
    if (v.x && v.y && v.z && v.w) break;
    if (++n > (1u << 15)) { SETERR(4); break; }
  }
  return v;
}
__device__ __forceinline__ uint32_t hmul2(uint32_t a, uint32_t b) { uint32_t r; asm("mul.rn.bf16x2 %0, %1, %2;" : "=r"(r) : "r"(a), "r"(b)); return r; }
__device__ __forceinline__ uint32_t hadd2(uint32_t a, uint32_t b) { uint32_t r; asm("add.rn.bf16x2 %0, %1, %2;" : "=r"(r) : "r"(a), "r"(b)); return r; }
__device__ __forceinline__ uint32_t hfma2(uint32_t a, uint32_t b, uint32_t c) { uint32_t r; asm("fma.rn.bf16x2 %0, %1, %2, %3;" : "=r"(r) : "r"(a), "r"(b), "r"(c)); return r; }
__device__ __forceinline__ void mma16816(float (&c)[4], uint32_t a0, uint32_t a1, uint32_t a2, uint32_t a3, uint32_t b0, uint32_t b1) {
  asm volatile("mma.sync.aligned.m16n8k16.row.col.f32.bf16.bf16.f32 {%0,%1,%2,%3}, {%4,%5,%6,%7}, {%8,%9}, {%0,%1,%2,%3};"
               : "+f"(c[0]), "+f"(c[1]), "+f"(c[2]), "+f"(c[3]) : "r"(a0), "r"(a1), "r"(a2), "r"(a3), "r"(b0), "r"(b1));
}
__device__ __forceinline__ void ldsm4t(uint32_t (&r)[4], uint32_t a) {
  asm volatile("ldmatrix.sync.aligned.m8n8.x4.trans.shared.b16 {%0,%1,%2,%3}, [%4];" : "=r"(r[0]), "=r"(r[1]), "=r"(r[2]), "=r"(r[3]) : "r"(a) : "memory");
}
__device__ __forceinline__ void ldsm2t(uint32_t (&r)[2], uint32_t a) {
  asm volatile("ldmatrix.sync.aligned.m8n8.x2.trans.shared.b16 {%0,%1}, [%2];" : "=r"(r[0]), "=r"(r[1]) : "r"(a) : "memory");
}
__device__ __forceinline__ float warp_sum(float v) {
#pragma unroll
  for (int o = 16; o; o >>= 1) v += __shfl_xor_sync(~0u, v, o);
  return v;
}
__device__ __forceinline__ void tma_load_2d(uint32_t dst, const CUtensorMap* map, uint32_t mbar, int c0, int c1) {
  asm volatile("cp.async.bulk.tensor.2d.shared::cluster.global.mbarrier::complete_tx::bytes [%0], [%1, {%3, %4}], [%2];"
               ::"r"(dst), "l"(map), "r"(mbar), "r"(c0), "r"(c1) : "memory");
}
__device__ __forceinline__ void tma_load_2d_mc(uint32_t dst, const CUtensorMap* map, uint32_t mbar, int c0, int c1) {
  asm volatile("cp.async.bulk.tensor.2d.shared::cluster.global.mbarrier::complete_tx::bytes.multicast::cluster [%0], [%1, {%3, %4}], [%2], %5;"
               ::"r"(dst), "l"(map), "r"(mbar), "r"(c0), "r"(c1), "h"((uint16_t)3) : "memory");
}
__device__ __forceinline__ void tma_prefetch_2d(const CUtensorMap* map, int c0, int c1) {
  asm volatile("cp.async.bulk.prefetch.tensor.2d.L2.global.tile [%0, {%1, %2}];" ::"l"(map), "r"(c0), "r"(c1) : "memory");
}
__device__ __forceinline__ void bulk_prefetch(const void* p, uint32_t bytes) {
  asm volatile("cp.async.bulk.prefetch.L2.global [%0], %1;" ::"l"(p), "r"(bytes) : "memory");
}
__device__ __forceinline__ void bulk_load(uint32_t dst, const void* src, uint32_t bytes, uint32_t mbar) {
  asm volatile("cp.async.bulk.shared::cluster.global.mbarrier::complete_tx::bytes [%0], [%1], %2, [%3];"
               ::"r"(dst), "l"(src), "r"(bytes), "r"(mbar) : "memory");
}
__device__ __forceinline__ void wgmma_fence() { asm volatile("wgmma.fence.sync.aligned;" ::: "memory"); }
__device__ __forceinline__ void wgmma_commit() { asm volatile("wgmma.commit_group.sync.aligned;" ::: "memory"); }
template <int N> __device__ __forceinline__ void wgmma_wait() { asm volatile("wgmma.wait_group.sync.aligned %0;" ::"n"(N) : "memory"); }
__device__ __forceinline__ void fence_async() { asm volatile("fence.proxy.async.shared::cta;" ::: "memory"); }
__device__ __forceinline__ void bar_sync(int id, int n) { asm volatile("bar.sync %0, %1;" ::"r"(id), "r"(n) : "memory"); }
__device__ __forceinline__ void bar_arrive(int id, int n) { asm volatile("bar.arrive %0, %1;" ::"r"(id), "r"(n) : "memory"); }

__device__ __forceinline__ uint64_t mk_desc(uint32_t addr, uint32_t lbo_bytes, uint32_t sbo_bytes) {
  return (uint64_t)((addr & 0x3FFFF) >> 4) | ((uint64_t)((lbo_bytes >> 4) & 0x3FFF) << 16) |
         ((uint64_t)((sbo_bytes >> 4) & 0x3FFF) << 32) | ((uint64_t)1 << 62);
}

#define R32(d) \
  "+f"(d[0]), "+f"(d[1]), "+f"(d[2]), "+f"(d[3]), "+f"(d[4]), "+f"(d[5]), "+f"(d[6]), "+f"(d[7]), \
  "+f"(d[8]), "+f"(d[9]), "+f"(d[10]), "+f"(d[11]), "+f"(d[12]), "+f"(d[13]), "+f"(d[14]), "+f"(d[15]), \
  "+f"(d[16]), "+f"(d[17]), "+f"(d[18]), "+f"(d[19]), "+f"(d[20]), "+f"(d[21]), "+f"(d[22]), "+f"(d[23]), \
  "+f"(d[24]), "+f"(d[25]), "+f"(d[26]), "+f"(d[27]), "+f"(d[28]), "+f"(d[29]), "+f"(d[30]), "+f"(d[31])
#define R64(d) R32(d), \
  "+f"(d[32]), "+f"(d[33]), "+f"(d[34]), "+f"(d[35]), "+f"(d[36]), "+f"(d[37]), "+f"(d[38]), "+f"(d[39]), \
  "+f"(d[40]), "+f"(d[41]), "+f"(d[42]), "+f"(d[43]), "+f"(d[44]), "+f"(d[45]), "+f"(d[46]), "+f"(d[47]), \
  "+f"(d[48]), "+f"(d[49]), "+f"(d[50]), "+f"(d[51]), "+f"(d[52]), "+f"(d[53]), "+f"(d[54]), "+f"(d[55]), \
  "+f"(d[56]), "+f"(d[57]), "+f"(d[58]), "+f"(d[59]), "+f"(d[60]), "+f"(d[61]), "+f"(d[62]), "+f"(d[63])
#define S32 \
  "{%0,%1,%2,%3,%4,%5,%6,%7,%8,%9,%10,%11,%12,%13,%14,%15,%16,%17,%18,%19,%20,%21,%22,%23,%24,%25,%26,%27,%28,%29,%30,%31}"
#define S64 \
  "{%0,%1,%2,%3,%4,%5,%6,%7,%8,%9,%10,%11,%12,%13,%14,%15,%16,%17,%18,%19,%20,%21,%22,%23,%24,%25,%26,%27,%28,%29,%30,%31," \
  "%32,%33,%34,%35,%36,%37,%38,%39,%40,%41,%42,%43,%44,%45,%46,%47,%48,%49,%50,%51,%52,%53,%54,%55,%56,%57,%58,%59,%60,%61,%62,%63}"

template <int TB>
__device__ __forceinline__ void wgmma128_ss(float (&d)[64], uint64_t da, uint64_t db, int scale_d) {
  asm volatile("{\n.reg .pred p;\nsetp.ne.b32 p, %66, 0;\n"
               "wgmma.mma_async.sync.aligned.m64n128k16.f32.bf16.bf16 " S64 ", %64, %65, p, 1, 1, 0, %67;\n}\n"
               : R64(d) : "l"(da), "l"(db), "r"(scale_d), "n"(TB));
}
template <int TB>
__device__ __forceinline__ void wgmma64_ss(float (&d)[64], uint64_t da, uint64_t db, int scale_d) {
  asm volatile("{\n.reg .pred p;\nsetp.ne.b32 p, %34, 0;\n"
               "wgmma.mma_async.sync.aligned.m64n64k16.f32.bf16.bf16 " S32 ", %32, %33, p, 1, 1, 0, %35;\n}\n"
               : R32(d) : "l"(da), "l"(db), "r"(scale_d), "n"(TB));
}
template <int TB>
__device__ __forceinline__ void wgmma128_rs(float (&d)[64], uint32_t a0, uint32_t a1, uint32_t a2, uint32_t a3, uint64_t db, int scale_d) {
  asm volatile("{\n.reg .pred p;\nsetp.ne.b32 p, %69, 0;\n"
               "wgmma.mma_async.sync.aligned.m64n128k16.f32.bf16.bf16 " S64 ", {%64,%65,%66,%67}, %68, p, 1, 1, %70;\n}\n"
               : R64(d) : "r"(a0), "r"(a1), "r"(a2), "r"(a3), "l"(db), "r"(scale_d), "n"(TB));
}
__device__ __forceinline__ uint32_t pack_bf16(float a, float b) {
  uint32_t r;
  asm("cvt.rn.bf16x2.f32 %0, %1, %2;" : "=r"(r) : "f"(b), "f"(a));
  return r;
}
__device__ __forceinline__ float ex2(float x) { float y; asm("ex2.approx.ftz.f32 %0, %1;" : "=f"(y) : "f"(x)); return y; }
__device__ __forceinline__ float bfr(float x) { return __bfloat162float(__float2bfloat16(x)); }
__device__ __forceinline__ float bf_lo(uint32_t u) { return __uint_as_float(u << 16); }
__device__ __forceinline__ float bf_hi(uint32_t u) { return __uint_as_float(u & 0xffff0000u); }
__device__ __forceinline__ uint4 lds128(uint32_t a) {
  uint4 v;
  asm volatile("ld.shared.v4.b32 {%0,%1,%2,%3}, [%4];" : "=r"(v.x), "=r"(v.y), "=r"(v.z), "=r"(v.w) : "r"(a) : "memory");
  return v;
}
__device__ __forceinline__ void sts128(uint32_t a, uint4 v) {
  asm volatile("st.shared.v4.b32 [%0], {%1,%2,%3,%4};" ::"r"(a), "r"(v.x), "r"(v.y), "r"(v.z), "r"(v.w) : "memory");
}
__device__ __forceinline__ void red_add_v4(float4* p, float a, float b, float c, float d) {
  asm volatile("red.global.add.v4.f32 [%0], {%1,%2,%3,%4};" ::"l"(p), "f"(a), "f"(b), "f"(c), "f"(d) : "memory");
}
__device__ __forceinline__ float rcp(float x) { float y; asm("rcp.approx.ftz.f32 %0, %1;" : "=f"(y) : "f"(x)); return y; }
__device__ __forceinline__ float sqrt_a(float x) { float y; asm("sqrt.approx.ftz.f32 %0, %1;" : "=f"(y) : "f"(x)); return y; }
__device__ __forceinline__ float silu_bf(float v) { return bfr(v * rcp(1.f + __expf(-v))); }

constexpr int SM_STASH = 131072;
constexpr int SM_H = 81920;
constexpr int SM_MISC = 229376;
constexpr int SM_TOTAL = 232448;
constexpr int B_FULLQ = 0, B_EMPTYQ = 40, B_FULLA = 80, B_EMPTYA = 112, B_FULLO = 144, B_EMPTYO = 192, B_X = 240, B_FFN = 248;
constexpr int SM_MOD = SM_MISC + 256;
constexpr int SM_RED = SM_MISC + 2560;
constexpr int SM_WG = 0, SM_WU = 46080, SM_WD = 92160;
constexpr int SM_T = 147456;

struct Params {
  const bf16 *x, *k, *c, *w_mod, *w_r, *wo, *v;
  bf16* out;
};

__global__ void __launch_bounds__(384, 1)
k_mega(const __grid_constant__ CUtensorMap mX, const __grid_constant__ CUtensorMap mWq,
       const __grid_constant__ CUtensorMap mK, const __grid_constant__ CUtensorMap mV,
       const __grid_constant__ CUtensorMap mWo, const __grid_constant__ CUtensorMap mWg,
       const __grid_constant__ CUtensorMap mWu, const __grid_constant__ CUtensorMap mWd, const Params prm) {
  extern __shared__ __align__(1024) uint8_t smem_raw[];
  const uint32_t sb = smem_u32(smem_raw);
  const uint32_t sBar = sb + SM_MISC;
  const int tid = threadIdx.x, lane = tid & 31;
  const int warp = __shfl_sync(~0u, tid >> 5, 0);
  const int b = blockIdx.x, qt = b & 15, hg = b >> 4;
  const int rank = MC ? (b & 1) : 0;
  constexpr int NREL = MC ? 16 : 8;
  if (warp == 0) {
    const bool empty = (lane >= 5 && lane < 10) || (lane >= 14 && lane < 18) || (lane >= 24 && lane < 30);
    mbar_init(sBar + lane * 8, empty ? NREL : 1);
    asm volatile("fence.mbarrier_init.release.cluster;" ::: "memory");
    __syncwarp();
    if (lane == 0) mbar_expect_tx(sBar + B_X, 9 * 16384);
    __syncwarp();
    if (lane < 9) tma_load_2d(sb + SM_H + lane * 16384, &mX, sBar + B_X, lane * 64, qt * 128);
  }
  asm volatile("barrier.cluster.arrive.release.aligned;\nbarrier.cluster.wait.acquire.aligned;" ::: "memory");
  if (warp < 4) {
    asm volatile("setmaxnreg.dec.sync.aligned.u32 40;");
    if (tid == 0) {
      auto load_pair = [&](uint32_t dst, uint32_t half, const CUtensorMap* m, uint32_t bar, int c0, int c1, int d0, int d1) {
        tma_load_2d_mc(dst + rank * half, m, bar, c0 + rank * d0, c1 + rank * d1);
      };
      uint32_t ph = 0x1f;
      {
        int g5 = 0, c = 0, hs = 1;
#pragma unroll 1
        for (int i = 0; i < 36; i++) {
          const int g = i == 35 ? 2 : g5;
          g5 = g5 == 4 ? 0 : g5 + 1;
          mbar_wait(sBar + B_EMPTYQ + g * 8, (ph >> g) & 1);
          ph ^= 1u << g;
          mbar_expect_tx(sBar + B_FULLQ + g * 8, 16384);
          load_pair(sb + g * 16384, 8192, &mWq, sBar + B_FULLQ + g * 8, (hg * 4 + (hs & 3)) * DH, c * 64, 64, 0);
          if (++c == 9) { c = 0; hs++; }
          if (i == 4) {
            bulk_prefetch(prm.k + ((size_t)(hg * 2) * SK + qt * 128) * DH, 32768);
            bulk_prefetch(prm.v + ((size_t)(hg * 2) * SK + qt * 128) * DH, 32768);
          }
        }
      }
#pragma unroll 1
      for (int t = 0; t < 128; t++) {
        const int s = t & 3, it = t >> 1;
        if (t < 2) {
#pragma unroll 1
          for (int g = t * 2; g < t * 3 + 2; g++) mbar_wait(sBar + B_EMPTYQ + g * 8, (ph >> g) & 1);
        } else if (t >= 4) {
          mbar_wait(sBar + B_EMPTYA + s * 8, ((t >> 2) & 1) ^ 1);
        }
        mbar_expect_tx(sBar + B_FULLA + s * 8, 32768);
        const int row = (hg * 2 + (it >> 5)) * SK + (it & 15) * 128;
        load_pair(sb + s * 32768, 16384, (t & 1) ? &mV : &mK, sBar + B_FULLA + s * 8, 0, row, 64, 0);
        if (t == 32) {
          bulk_prefetch(prm.k + ((size_t)(hg * 2 + 1) * SK + qt * 128) * DH, 32768);
          bulk_prefetch(prm.v + ((size_t)(hg * 2 + 1) * SK + qt * 128) * DH, 32768);
        }
        if (t == 80) {
          bulk_prefetch(prm.wo + ((size_t)hg * 512 + qt * 32) * DM, 32 * DM * 2);
#pragma unroll 1
          for (int i = 0; i < 3; i++) { tma_prefetch_2d(&mWg, (b * 36) & ~7, i * 192); tma_prefetch_2d(&mWu, (b * 36) & ~7, i * 192); }
#pragma unroll 1
          for (int i = 0; i < 9; i++) tma_prefetch_2d(&mWd, i * 64, b * 36);
          cnt_wait(C_SIDE, 128 * 3);
        }
      }
      {
        int g6 = 0, par = 1;
#pragma unroll 1
        for (int i = 0; i < 36; i++) {
          const int g = g6 < 4 ? g6 : g6 + 2;
          if (i < 6) mbar_wait(sBar + B_EMPTYA + (g >> 1) * 8, 1);
          else mbar_wait(sBar + B_EMPTYO + g6 * 8, par);
          mbar_expect_tx(sBar + B_FULLO + g6 * 8, 16384);
          const bool sm = i < 4;
          const int ch = (i - 4) >> 3, kc = (i - 4) & 7;
          load_pair(sb + g * 16384, 8192, &mWo, sBar + B_FULLO + g6 * 8, sm ? 512 : ch * 128, hg * 512 + (sm ? i * 128 : kc * 64), sm ? 0 : 64, sm ? 64 : 0);
          if (++g6 == 6) { g6 = 0; par ^= 1; }
        }
      }
#pragma unroll 1
      for (int g6 = 0; g6 < 6; g6++) mbar_wait(sBar + B_EMPTYO + g6 * 8, 1);
      mbar_expect_tx(sBar + B_FFN, 2 * 46080 + 9 * 6144);
#pragma unroll 1
      for (int i = 0; i < 3; i++) {
        tma_load_2d(sb + SM_WG + i * 15360, &mWg, sBar + B_FFN, (b * 36) & ~7, i * 192);
        tma_load_2d(sb + SM_WU + i * 15360, &mWu, sBar + B_FFN, (b * 36) & ~7, i * 192);
      }
#pragma unroll 1
      for (int i = 0; i < 9; i++) tma_load_2d(sb + SM_WD + i * 6144, &mWd, sBar + B_FFN, i * 64, b * 36);
    } else if (warp > 0) {
      const int st = tid - 32;
      float4* z = g_acc + (size_t)b * 2304;
#pragma unroll 4
      for (int i = st; i < 2304; i += 96) z[i] = make_float4(0.f, 0.f, 0.f, 0.f);
      if (b == 127) {
#pragma unroll 1
        for (int i = st; i < 2 * DM; i += 96) g_y[i] = 0.f;
      }
      if (b < 96) {
        const int grp = b * 3 + warp - 1;
        float a[8];
#pragma unroll
        for (int i = 0; i < 8; i++) a[i] = 0.f;
#pragma unroll 2
        for (int r = lane; r < DM; r += 32) {
          uint4 v = __ldg(reinterpret_cast<const uint4*>(prm.w_mod + (size_t)r * (6 * DM) + 2 * DM + grp * 8));
          float s = silu_bf(__bfloat162float(prm.c[r]));
          a[0] += s * bf_lo(v.x); a[1] += s * bf_hi(v.x); a[2] += s * bf_lo(v.y); a[3] += s * bf_hi(v.y);
          a[4] += s * bf_lo(v.z); a[5] += s * bf_hi(v.z); a[6] += s * bf_lo(v.w); a[7] += s * bf_hi(v.w);
        }
#pragma unroll
        for (int i = 0; i < 8; i++) a[i] = warp_sum(a[i]);
        if (lane == 0) {
          const int kind = grp / 72, cp = (grp - kind * 72) * 4;
#pragma unroll
          for (int i = 0; i < 4; i++) {
            uint32_t w = pack_bf16(a[2 * i], a[2 * i + 1]);
            if (kind == 2) w = hadd2(w, 0x3f803f80u);
            reinterpret_cast<uint32_t*>(g_mod2)[(cp + i) * 4 + kind] = w;
          }
        }
      }
      __syncwarp();
      if (lane == 0) cnt_arrive(C_SIDE);
    }
  } else {
    asm volatile("setmaxnreg.inc.sync.aligned.u32 232;");
    const int cw = (warp >> 2) - 1;
    const int w8 = warp - 4;
    const int ct = tid - 128;
    const int g = lane >> 2, t4 = lane & 3;
    uint32_t relBar;
    asm volatile("mapa.shared::cluster.u32 %0, %1, %2;" : "=r"(relBar) : "r"(sBar), "r"(MC ? (rank ^ (lane & 1)) : 0));
    auto release = [&](int off) {
      if (lane < (MC ? 2 : 1)) mbar_arrive_cl(relBar + off);
    };
    STAMP(0); GSTAMP(90);
    if (b < 72) {
      const int half = ct & 1, r0 = ct >> 1;
      uint4 v[5]; float s[5];
#pragma unroll
      for (int i = 0; i < 5; i++) {
        const int r = min(r0 + 128 * i, DM - 1);
        v[i] = __ldg(reinterpret_cast<const uint4*>(prm.w_mod + (size_t)r * (6 * DM) + b * 16 + half * 8));
        s[i] = __bfloat162float(prm.c[r]);
      }
      float a[8];
#pragma unroll
      for (int i = 0; i < 8; i++) a[i] = 0.f;
#pragma unroll
      for (int i = 0; i < 5; i++) {
        float sv = silu_bf(s[i]);
        if (i == 4 && r0 >= 64) { sv = 0.f; v[i] = make_uint4(0, 0, 0, 0); }
        a[0] += sv * bf_lo(v[i].x); a[1] += sv * bf_hi(v[i].x); a[2] += sv * bf_lo(v[i].y); a[3] += sv * bf_hi(v[i].y);
        a[4] += sv * bf_lo(v[i].z); a[5] += sv * bf_hi(v[i].z); a[6] += sv * bf_lo(v[i].w); a[7] += sv * bf_hi(v[i].w);
      }
      const bool u2 = lane & 2, u4 = lane & 4, u8 = lane & 8;
#pragma unroll
      for (int i = 0; i < 4; i++) { float snd = u2 ? a[i] : a[i + 4]; float kp = u2 ? a[i + 4] : a[i]; a[i] = kp + __shfl_xor_sync(~0u, snd, 2); }
#pragma unroll
      for (int i = 0; i < 2; i++) { float snd = u4 ? a[i] : a[i + 2]; float kp = u4 ? a[i + 2] : a[i]; a[i] = kp + __shfl_xor_sync(~0u, snd, 4); }
      { float snd = u8 ? a[0] : a[1]; float kp = u8 ? a[1] : a[0]; a[0] = kp + __shfl_xor_sync(~0u, snd, 8); }
      a[0] += __shfl_xor_sync(~0u, a[0], 16);
      float* const red = reinterpret_cast<float*>(smem_raw + SM_RED);
      if (lane < 16) red[w8 * 16 + half * 8 + (u2 ? 4 : 0) + (u4 ? 2 : 0) + (u8 ? 1 : 0)] = a[0];
      bar_sync(5, 256);
      if (ct < 8) {
        float s0 = 0.f, s1 = 0.f;
#pragma unroll
        for (int i = 0; i < 8; i++) { float2 x = *reinterpret_cast<float2*>(red + i * 16 + ct * 2); s0 += x.x; s1 += x.y; }
        uint32_t w = pack_bf16(s0, s1);
        if (b >= 36) w = hadd2(w, 0x3f803f80u);
        asm volatile("st.relaxed.gpu.global.u32 [%0], %1;" ::"l"(reinterpret_cast<uint32_t*>(g_mod1) + b * 8 + ct), "r"(~w) : "memory");
      }
    }
    STAMP(1);
    const uint32_t lnA = sb + SM_H + (w8 * 16 + (lane >> 3)) * 128 + (((lane & 7) ^ (lane >> 3)) << 4);
    mbar_wait(sBar + B_X, 0);
#pragma unroll 1
    for (int i = 0; i < 4; i++) {
      const uint32_t a = (lnA ^ ((i & 1) << 6)) + i * 512;
      float f[72];
      float s = 0.f, q = 0.f;
#pragma unroll
      for (int bx = 0; bx < 9; bx++) {
        const uint4 u = lds128(a + bx * 16384);
        const uint32_t w[4] = {u.x, u.y, u.z, u.w};
#pragma unroll
        for (int e = 0; e < 4; e++) { f[bx * 8 + 2 * e] = bf_lo(w[e]); f[bx * 8 + 2 * e + 1] = bf_hi(w[e]); s += f[bx * 8 + 2 * e]; q += f[bx * 8 + 2 * e + 1]; }
      }
      s += q;
      s += __shfl_xor_sync(~0u, s, 1); s += __shfl_xor_sync(~0u, s, 2); s += __shfl_xor_sync(~0u, s, 4);
      const float m = s * (1.f / DM);
      q = 0.f; s = 0.f;
#pragma unroll
      for (int e = 0; e < 72; e += 2) { f[e] -= m; f[e + 1] -= m; q += f[e] * f[e]; s += f[e + 1] * f[e + 1]; }
      q += s;
      q += __shfl_xor_sync(~0u, q, 1); q += __shfl_xor_sync(~0u, q, 2); q += __shfl_xor_sync(~0u, q, 4);
      const float ri = rsqrtf(q * (1.f / DM) + 1e-5f);
#pragma unroll
      for (int bx = 0; bx < 9; bx++)
        sts128(a + bx * 16384, make_uint4(pack_bf16(f[bx * 8] * ri, f[bx * 8 + 1] * ri), pack_bf16(f[bx * 8 + 2] * ri, f[bx * 8 + 3] * ri),
                                          pack_bf16(f[bx * 8 + 4] * ri, f[bx * 8 + 5] * ri), pack_bf16(f[bx * 8 + 6] * ri, f[bx * 8 + 7] * ri)));
    }
    STAMP(2);
    if (ct < 144) {
      const uint4 v = poll4(g_mod1 + ct);
      sts128(sb + SM_MOD + ct * 16, make_uint4(~v.x, ~v.y, ~v.z, ~v.w));
    }
    bar_sync(5, 256);
    STAMP(3);
    auto modulate = [&](int bx) {
      const uint4 sa = lds128(sb + SM_MOD + bx * 128 + (lane & 7) * 16), ca = lds128(sb + SM_MOD + 1152 + bx * 128 + (lane & 7) * 16);
#pragma unroll
      for (int i = 0; i < 4; i++) {
        const uint32_t a = (lnA ^ ((i & 1) << 6)) + i * 512 + bx * 16384;
        const uint4 u = lds128(a);
        sts128(a, make_uint4(hfma2(u.x, ca.x, sa.x), hfma2(u.y, ca.y, sa.y), hfma2(u.z, ca.z, sa.z), hfma2(u.w, ca.w, sa.w)));
      }
      fence_async();
      bar_sync(3 + cw, 128);
    };
    STAMP(4);
    float S[64], O[64];
    uint32_t P[32], Qf[32];
    const uint64_t dA_k = mk_desc(sb + cw * 8192, 16, 1024);
    const uint64_t dB_k = mk_desc(sb, 16, 1024);
    const uint64_t dB_n8 = mk_desc(sb, 8192, 1024);
    const uint64_t dB_n16 = mk_desc(sb, 16384, 1024);
    uint4* const qpark = g_q + (size_t)b * (4 * 8 * 256) + ct;
    {
      uint32_t ph = 0;
      int g5 = 0, prevg = 0;
#pragma unroll 1
      for (int hs = 1; hs <= 4; hs++) {
#pragma unroll 1
        for (int c = 0; c < 9; c++) {
          const int gr = (hs == 4 && c == 8) ? 2 : g5;
          g5 = g5 == 4 ? 0 : g5 + 1;
          if (hs == 1) modulate(c);
          mbar_wait(sBar + B_FULLQ + gr * 8, (ph >> gr) & 1);
          ph ^= 1u << gr;
          wgmma_fence();
          const uint64_t da = dA_k + ((SM_H + c * 16384) >> 4), db = dB_n8 + ((gr * 16384) >> 4);
#pragma unroll
          for (int kk = 0; kk < 4; kk++) wgmma128_ss<1>(S, da + kk * 2, db + kk * 128, (c | kk) != 0);
          wgmma_commit();
          wgmma_wait<1>();
          if (c > 0) release(B_EMPTYQ + prevg * 8);
          prevg = gr;
        }
        wgmma_wait<0>();
        release(B_EMPTYQ + prevg * 8);
#pragma unroll
        for (int i = 0; i < 32; i++) Qf[i] = pack_bf16(S[2 * i], S[2 * i + 1]);
#pragma unroll
        for (int i = 0; i < 8; i++) qpark[((hs & 3) * 8 + i) * 256] = make_uint4(Qf[4 * i], Qf[4 * i + 1], Qf[4 * i + 2], Qf[4 * i + 3]);
      }
    }
    STAMP(5);
    const float sc = 0.08838834764831845f * 1.4426950408889634f;
    float mb0 = 0.f, mb1 = 0.f, l0 = 0.f, l1 = 0.f;
    auto store_o = [&](uint32_t base) {
      float a0 = l0, a1 = l1;
      a0 += __shfl_xor_sync(~0u, a0, 1); a0 += __shfl_xor_sync(~0u, a0, 2);
      a1 += __shfl_xor_sync(~0u, a1, 1); a1 += __shfl_xor_sync(~0u, a1, 2);
      const float i0 = rcp(a0), i1 = rcp(a1);
      const uint32_t ra = base + (w8 * 16 + (lane & 15)) * 128 + (((lane >> 4) ^ (lane & 7)) << 4);
#pragma unroll
      for (int j = 0; j < 16; j += 2) {
        const uint32_t a = (ra ^ ((j & 7) << 4)) + (j >> 3) * 16384;
        asm volatile("stmatrix.sync.aligned.m8n8.x4.shared.b16 [%0], {%1,%2,%3,%4};" ::"r"(a),
                     "r"(pack_bf16(O[j * 4] * i0, O[j * 4 + 1] * i0)), "r"(pack_bf16(O[j * 4 + 2] * i1, O[j * 4 + 3] * i1)),
                     "r"(pack_bf16(O[j * 4 + 4] * i0, O[j * 4 + 5] * i0)), "r"(pack_bf16(O[j * 4 + 6] * i1, O[j * 4 + 7] * i1)) : "memory");
      }
    };
    auto row_max = [&](float& x0, float& x1) {
      float y0 = fmaxf(S[0], S[1]), y1 = fmaxf(S[2], S[3]), z0 = fmaxf(S[4], S[5]), z1 = fmaxf(S[6], S[7]);
#pragma unroll
      for (int j = 2; j < 16; j += 2) {
        y0 = fmaxf(y0, fmaxf(S[j * 4], S[j * 4 + 1])); y1 = fmaxf(y1, fmaxf(S[j * 4 + 2], S[j * 4 + 3]));
        z0 = fmaxf(z0, fmaxf(S[j * 4 + 4], S[j * 4 + 5])); z1 = fmaxf(z1, fmaxf(S[j * 4 + 6], S[j * 4 + 7]));
      }
      x0 = fmaxf(y0, z0); x1 = fmaxf(y1, z1);
      x0 = fmaxf(x0, __shfl_xor_sync(~0u, x0, 1)); x1 = fmaxf(x1, __shfl_xor_sync(~0u, x1, 1));
      x0 = fmaxf(x0, __shfl_xor_sync(~0u, x0, 2)); x1 = fmaxf(x1, __shfl_xor_sync(~0u, x1, 2));
    };
    float s0, s1;
    auto exps = [&](int j0, int j1) {
#pragma unroll
      for (int j = j0; j < j1; j++) {
        S[j * 4] = ex2(fmaf(S[j * 4], sc, -mb0)); S[j * 4 + 1] = ex2(fmaf(S[j * 4 + 1], sc, -mb0));
        S[j * 4 + 2] = ex2(fmaf(S[j * 4 + 2], sc, -mb1)); S[j * 4 + 3] = ex2(fmaf(S[j * 4 + 3], sc, -mb1));
        s0 += S[j * 4] + S[j * 4 + 1]; s1 += S[j * 4 + 2] + S[j * 4 + 3];
      }
    };
    auto cvtP = [&]() {
#pragma unroll
      for (int i = 0; i < 32; i++) P[i] = pack_bf16(S[2 * i], S[2 * i + 1]);
    };
    auto issue_qk = [&](int ks) {
      const uint64_t db = dB_k + ((ks * 32768) >> 4);
#pragma unroll
      for (int kk = 0; kk < 8; kk++)
        wgmma128_rs<0>(S, Qf[kk * 4], Qf[kk * 4 + 1], Qf[kk * 4 + 2], Qf[kk * 4 + 3], db + (kk >> 2) * 1024 + (kk & 3) * 2, kk != 0);
    };
    auto issue_pv = [&](int vs, int first) {
      const uint64_t db = dB_n16 + ((vs * 32768) >> 4);
#pragma unroll
      for (int kk = 0; kk < 8; kk++)
        wgmma128_rs<1>(O, P[kk * 4], P[kk * 4 + 1], P[kk * 4 + 2], P[kk * 4 + 3], db + kk * 128, kk ? 1 : !first);
    };
    auto sched_fence = [&]() {
      asm volatile("st.shared.f32 [%0], %1;" ::"r"(sb + SM_RED + lane * 4), "f"(S[31]) : "memory");
    };
    if (cw == 0) bar_arrive(1, 256);
#pragma unroll 1
    for (int h = 0; h < 4; h++) {
      {
        STAMP(6 + h * 16);
        mbar_wait(sBar + B_FULLA, 0);
        if (h > 0) mbar_wait(sBar + B_FULLA + 24, 1);
        bar_sync(1 + cw, 256);
        wgmma_fence();
        issue_qk(0);
        wgmma_commit();
        if (h > 0) { issue_pv(3, 0); wgmma_commit(); }
        else asm volatile("wgmma.commit_group.sync.aligned; // empty" ::: "memory");
        bar_arrive(2 - cw, 256);
        wgmma_wait<1>();
        release(B_EMPTYA);
        s0 = 0.f; s1 = 0.f;
        float x0, x1;
        row_max(x0, x1);
        mb0 = x0 * sc; mb1 = x1 * sc;
        exps(0, 8);
        sched_fence();
        wgmma_wait<0>();
        if (h > 0) {
          release(B_EMPTYA + 24);
          store_o(sb + SM_STASH + (h - 1) * 32768);
        }
        exps(8, 16);
        cvtP();
        l0 = s0; l1 = s1;
      }
#pragma unroll 1
      for (int j = 1; j < 16; j++) {
        const int ks = (j & 1) * 2, vs = 3 - ks;
        STAMP(6 + h * 16 + j);
        mbar_wait(sBar + B_FULLA + ks * 8, (j >> 1) & 1);
        mbar_wait(sBar + B_FULLA + vs * 8, ((j - 1) >> 1) & 1);
        bar_sync(1 + cw, 256);
        wgmma_fence();
        issue_qk(ks);
        wgmma_commit();
        issue_pv(vs, j == 1);
        wgmma_commit();
        bar_arrive(2 - cw, 256);
        wgmma_wait<1>();
        release(B_EMPTYA + ks * 8);
        if (j == 15 && h < 3) {
          const uint4* qp = qpark + (h + 1) * (8 * 256);
#pragma unroll
          for (int i = 0; i < 8; i++) {
            uint4 v = __ldcg(qp + i * 256);
            Qf[4 * i] = v.x; Qf[4 * i + 1] = v.y; Qf[4 * i + 2] = v.z; Qf[4 * i + 3] = v.w;
          }
        }
        s0 = 0.f; s1 = 0.f;
        exps(0, 8);
        sched_fence();
        wgmma_wait<0>();
        release(B_EMPTYA + vs * 8);
        bool bad = __any_sync(~0u, !(s0 <= LAZY_LIMIT && s1 <= LAZY_LIMIT));
        if (__builtin_expect(!bad, 1)) {
          exps(8, 16);
          cvtP();
          bad = __any_sync(~0u, !(s0 <= LAZY_LIMIT && s1 <= LAZY_LIMIT));
        }
        if (__builtin_expect(bad, 0)) {
          const uint32_t* kp = reinterpret_cast<const uint32_t*>(prm.k + ((size_t)(hg * 2 + (h >> 1)) * SK + j * 128 + g) * DH) + t4;
          const uint4* qp = qpark + h * (8 * 256);
          float4 tmp[16];
#pragma unroll 1
          for (int jn = 0; jn < 16; jn++) {
            float c[4] = {0.f, 0.f, 0.f, 0.f};
#pragma unroll 1
            for (int kk = 0; kk < 8; kk++) {
              const uint4 a = __ldcg(qp + kk * 256);
              mma16816(c, a.x, a.y, a.z, a.w, __ldg(kp + jn * 512 + kk * 8), __ldg(kp + jn * 512 + kk * 8 + 4));
            }
            tmp[jn] = make_float4(c[0], c[1], c[2], c[3]);
          }
#pragma unroll
          for (int jn = 0; jn < 16; jn++) { const float4 c = tmp[jn]; S[jn * 4] = c.x; S[jn * 4 + 1] = c.y; S[jn * 4 + 2] = c.z; S[jn * 4 + 3] = c.w; }
          float x0, x1;
          row_max(x0, x1);
          const float n0 = fmaxf(mb0, x0 * sc), n1 = fmaxf(mb1, x1 * sc);
          const float f0 = ex2(mb0 - n0), f1 = ex2(mb1 - n1);
          mb0 = n0; mb1 = n1;
          l0 *= f0; l1 *= f1;
#pragma unroll
          for (int i = 0; i < 16; i++) { O[i * 4] *= f0; O[i * 4 + 1] *= f0; O[i * 4 + 2] *= f1; O[i * 4 + 3] *= f1; }
          s0 = 0.f; s1 = 0.f;
          exps(0, 16);
          cvtP();
        }
        l0 += s0; l1 += s1;
      }
    }
    STAMP(70);
    mbar_wait(sBar + B_FULLA + 24, 1);
    if (cw == 0) bar_sync(1, 256);
    wgmma_fence();
    issue_pv(3, 0);
    wgmma_commit();
    wgmma_wait<0>();
    release(B_EMPTYA + 24);
    mbar_wait(sBar + B_EMPTYA + 16, 1);
    store_o(sb + 2 * 32768);
    fence_async();
    bar_sync(3 + cw, 128);
    STAMP(71);
    {
      float4* const accp = g_acc + ((size_t)(qt * 2 + cw) * 72 * 4 + (w8 & 3)) * 32 + lane;
      int g6 = 0, par = 0;
#pragma unroll 1
      for (int i = 0; i < 4; i++) {
        mbar_wait(sBar + B_FULLO + i * 8, 0);
        wgmma_fence();
        const uint64_t da = dA_k + ((i < 3 ? SM_STASH + i * 32768 : 65536) >> 4), db = dB_n8 + ((i * 16384) >> 4);
#pragma unroll
        for (int kk = 0; kk < 8; kk++) wgmma64_ss<1>(S, da + (kk >> 2) * 1024 + (kk & 3) * 2, db + kk * 128, (i | kk) != 0);
        wgmma_commit();
        wgmma_wait<1>();
        if (i > 0) release(B_EMPTYO + (i - 1) * 8);
      }
      wgmma_wait<0>();
      release(B_EMPTYO + 24);
      int prevg = 3;
      g6 = 4;
      auto chunk = [&](float (&acc)[64], float (&prev)[64], float4* pp, bool prev_full) {
#pragma unroll
        for (int kc = 0; kc < 8; kc++) {
          mbar_wait(sBar + B_FULLO + g6 * 8, par);
          wgmma_fence();
          const uint64_t da = dA_k + (((kc < 6 ? SM_STASH + (kc >> 1) * 32768 : 65536) + (kc & 1) * 16384) >> 4);
          const uint64_t db = dB_n8 + (uint32_t)((g6 + (g6 >> 2) * 2) * 1024);
#pragma unroll
          for (int kk = 0; kk < 4; kk++) wgmma128_ss<1>(acc, da + kk * 2, db + kk * 128, (kc | kk) != 0);
          wgmma_commit();
          if (kc < 4 || prev_full) {
            red_add_v4(pp + (2 * kc) * 128, prev[kc * 8], prev[kc * 8 + 1], prev[kc * 8 + 2], prev[kc * 8 + 3]);
            red_add_v4(pp + (2 * kc + 1) * 128, prev[kc * 8 + 4], prev[kc * 8 + 5], prev[kc * 8 + 6], prev[kc * 8 + 7]);
          }
          if (kc > 0) {
            wgmma_wait<1>();
            release(B_EMPTYO + prevg * 8);
          }
          prevg = g6;
          if (++g6 == 6) { g6 = 0; par ^= 1; }
        }
        wgmma_wait<0>();
        release(B_EMPTYO + prevg * 8);
      };
#pragma unroll 1
      for (int cp = 0; cp < 2; cp++) {
        chunk(O, S, accp + (cp ? 16 : 64) * 128, cp != 0);
        chunk(S, O, accp + cp * 32 * 128, true);
      }
      STAMP(72);
#pragma unroll
      for (int jb = 0; jb < 16; jb++) red_add_v4(accp + (48 + jb) * 128, S[jb * 4], S[jb * 4 + 1], S[jb * 4 + 2], S[jb * 4 + 3]);
    }
    bar_sync(5, 256);
    if (ct == 0) cnt_arrive(C_Q + qt);
    STAMP(73);
    {
      const int rowA = qt * 128 + hg * 16 + w8;
      const size_t oA = (size_t)rowA * (DM / 2) + lane, oB = oA + 8 * (DM / 2);
      uint32_t xa[9], xb[9], wr[9];
      uint4 md[9];
#pragma unroll
      for (int i = 0; i < 9; i++) {
        xa[i] = __ldg(reinterpret_cast<const uint32_t*>(prm.x) + oA + i * 32);
        xb[i] = __ldg(reinterpret_cast<const uint32_t*>(prm.x) + oB + i * 32);
        wr[i] = __ldg(reinterpret_cast<const uint32_t*>(prm.w_r) + lane + i * 32);
        md[i] = __ldcg(g_mod2 + lane + i * 32);
      }
      cnt_wait(C_Q + qt, 8);
      __syncwarp();
      STAMP(74);
      const float4* ap = g_acc + ((size_t)(qt * 2 + (hg >> 2)) * 72 * 4 + (hg & 3)) * 32 + g * 128 + w8 * 4 + t4;
      float4 av[9];
#pragma unroll
      for (int i = 0; i < 9; i++) av[i] = __ldcg(ap + i * 1024);
      float sA = 0.f, sB = 0.f;
#pragma unroll
      for (int i = 0; i < 9; i++) {
        xa[i] = hadd2(xa[i], hmul2(md[i].x, pack_bf16(av[i].x, av[i].y)));
        xb[i] = hadd2(xb[i], hmul2(md[i].x, pack_bf16(av[i].z, av[i].w)));
        g_x2[oA + i * 32] = xa[i]; g_x2[oB + i * 32] = xb[i];
        sA += bf_lo(xa[i]) + bf_hi(xa[i]); sB += bf_lo(xb[i]) + bf_hi(xb[i]);
      }
      const float mA = warp_sum(sA) * (1.f / DM), mB = warp_sum(sB) * (1.f / DM);
      sA = 0.f; sB = 0.f;
#pragma unroll
      for (int i = 0; i < 9; i++) {
        const float d0 = bf_lo(xa[i]) - mA, d1 = bf_hi(xa[i]) - mA, d2 = bf_lo(xb[i]) - mB, d3 = bf_hi(xb[i]) - mB;
        sA += d0 * d0 + d1 * d1; sB += d2 * d2 + d3 * d3;
      }
      const float rA = rcp(bfr(sqrt_a(bfr(bfr(warp_sum(sA) * (1.f / DM)) + 1e-5f))));
      const float rB = rcp(bfr(sqrt_a(bfr(bfr(warp_sum(sB) * (1.f / DM)) + 1e-5f))));
      const uint32_t nmA = pack_bf16(-mA, -mA), nmB = pack_bf16(-mB, -mB);
      sA = 0.f; sB = 0.f;
      uint32_t ha[9], hb[9];
#pragma unroll
      for (int i = 0; i < 9; i++) {
        const uint32_t da = hadd2(xa[i], nmA), db = hadd2(xb[i], nmB);
        ha[i] = hadd2(hmul2(pack_bf16(bf_lo(da) * rA, bf_hi(da) * rA), md[i].z), md[i].y);
        hb[i] = hadd2(hmul2(pack_bf16(bf_lo(db) * rB, bf_hi(db) * rB), md[i].z), md[i].y);
        g_h2[oA + i * 32] = ha[i]; g_h2[oB + i * 32] = hb[i];
        const float w0 = bf_lo(wr[i]), w1 = bf_hi(wr[i]);
        sA += bf_lo(ha[i]) * w0 + bf_hi(ha[i]) * w1; sB += bf_lo(hb[i]) * w0 + bf_hi(hb[i]) * w1;
      }
      const uint32_t rr = pack_bf16(warp_sum(sA), warp_sum(sB));
      uint32_t u = ((lane & 1) ? rr : rr << 16) & 0xffff0000u;
      u = ((u & 0x7fff0000u) > 0x7f800000u) ? 0u : (u ^ ((u >> 31) ? 0xffff0000u : 0x80000000u));
      u |= 0xffffu - (rowA + (lane & 1) * 8);
      __syncwarp();
      if (lane < 2) asm volatile("st.release.gpu.global.u32 [%0], %1;" ::"l"(reinterpret_cast<uint32_t*>(g_key) + b * 16 + w8 * 2 + lane), "r"(u) : "memory");
#pragma unroll
      for (int i = 0; i < 9; i++) {
        reinterpret_cast<uint32_t*>(prm.out)[oA + i * 32] = hadd2(xa[i], hmul2(md[i].w, ha[i]));
        reinterpret_cast<uint32_t*>(prm.out)[oB + i * 32] = hadd2(xb[i], hmul2(md[i].w, hb[i]));
      }
    }
    STAMP(75);
    uint32_t* const tsu = reinterpret_cast<uint32_t*>(smem_raw + SM_T);
    float* const tsf = reinterpret_cast<float*>(smem_raw + SM_T);
    uint32_t k1, k2;
    {
      const uint4 a = poll4(g_key + ct), c = poll4(g_key + 256 + ct);
      asm volatile("fence.acq_rel.gpu;" ::: "memory");
      auto merge = [](uint32_t& m1, uint32_t& m2, uint32_t n1, uint32_t n2) { m2 = max(min(m1, n1), max(m2, n2)); m1 = max(m1, n1); };
      k1 = max(a.x, a.y); k2 = min(a.x, a.y);
      merge(k1, k2, max(a.z, a.w), min(a.z, a.w));
      merge(k1, k2, max(c.x, c.y), min(c.x, c.y));
      merge(k1, k2, max(c.z, c.w), min(c.z, c.w));
      uint32_t m1 = __reduce_max_sync(~0u, k1);
      uint32_t m2 = __reduce_max_sync(~0u, k1 == m1 ? k2 : k1);
      if (lane == 0) { tsu[w8 * 2] = m1; tsu[w8 * 2 + 1] = m2; }
      bar_sync(5, 256);
      const uint32_t v = tsu[lane & 15];
      k1 = __reduce_max_sync(~0u, v);
      k2 = __reduce_max_sync(~0u, v == k1 ? 0u : v);
    }
    STAMP(76);
    const int row1 = (0xffff - (k1 & 0xffff)) & (SQ - 1), row2 = (0xffff - (k2 & 0xffff)) & (SQ - 1);
    {
      const int kq = w8 >> 1;
      uint32_t af[18];
      const uint32_t* hp = g_h2 + (size_t)(g ? row2 : row1) * (DM / 2) + kq * 72 + t4;
#pragma unroll
      for (int i = 0; i < 18; i++) af[i] = g < 2 ? __ldcg(hp + i * 4) : 0u;
      float c[5][4];
#pragma unroll
      for (int i = 0; i < 5; i++) c[i][0] = c[i][1] = c[i][2] = c[i][3] = 0.f;
      mbar_wait(sBar + B_FFN, 0);
      STAMP(77);
      const uint32_t wa = sb + ((w8 & 1) ? SM_WU : SM_WG) + (kq * 144 + (lane & 15)) * 80 + (lane >> 4) * 16;
#pragma unroll
      for (int ks = 0; ks < 9; ks++) {
        uint32_t b0[4], b1[4], b2[2];
        ldsm4t(b0, wa + ks * 1280); ldsm4t(b1, wa + ks * 1280 + 32); ldsm2t(b2, wa + ks * 1280 + 64 - (lane >> 4) * 16);
        mma16816(c[0], af[2 * ks], 0u, af[2 * ks + 1], 0u, b0[0], b0[1]);
        mma16816(c[1], af[2 * ks], 0u, af[2 * ks + 1], 0u, b0[2], b0[3]);
        mma16816(c[2], af[2 * ks], 0u, af[2 * ks + 1], 0u, b1[0], b1[1]);
        mma16816(c[3], af[2 * ks], 0u, af[2 * ks + 1], 0u, b1[2], b1[3]);
        mma16816(c[4], af[2 * ks], 0u, af[2 * ks + 1], 0u, b2[0], b2[1]);
      }
      float* const part = tsf + 64;
      if (g < 2) {
#pragma unroll
        for (int i = 0; i < 5; i++) *reinterpret_cast<float2*>(part + w8 * 80 + g * 40 + i * 8 + t4 * 2) = make_float2(c[i][0], c[i][1]);
      }
      bar_sync(5, 256);
      bf16* const act = reinterpret_cast<bf16*>(tsf + 768);
      if (ct < 96) {
        const int tok = ct >= 48, f = ct - tok * 48;
        float v = 0.f;
        if (f < 36) {
          const float* pp = part + tok * 40 + f + (b & 1) * 4;
          const float gs = (pp[0] + pp[160]) + (pp[320] + pp[480]), us = (pp[80] + pp[240]) + (pp[400] + pp[560]);
          v = silu_bf(bfr(gs)) * bfr(us);
        }
        act[ct] = __float2bfloat16(v);
      }
      bar_sync(5, 256);
      uint32_t a6[6];
#pragma unroll
      for (int i = 0; i < 6; i++) a6[i] = g < 2 ? reinterpret_cast<const uint32_t*>(act)[g * 24 + i * 4 + t4] : 0u;
#pragma unroll 3
      for (int i = 0; i < 9; i++) {
        const int nt = w8 * 9 + i;
        const uint32_t a = sb + SM_WD + (nt >> 3) * 6144 + lane * 128 + (((nt ^ lane) & 7) << 4);
        uint32_t b0[4], b2[2];
        ldsm4t(b0, a); ldsm2t(b2, a + 4096 - (lane >> 4) * 2048);
        float y[4] = {0.f, 0.f, 0.f, 0.f};
        mma16816(y, a6[0], 0u, a6[1], 0u, b0[0], b0[1]);
        mma16816(y, a6[2], 0u, a6[3], 0u, b0[2], b0[3]);
        mma16816(y, a6[4], 0u, a6[5], 0u, b2[0], b2[1]);
        if (g < 2) asm volatile("red.global.add.v2.f32 [%0], {%1,%2};" ::"l"(g_y + g * DM + nt * 8 + t4 * 2), "f"(y[0]), "f"(y[1]) : "memory");
      }
    }
    bar_sync(5, 256);
    STAMP(78);
    if (ct == 0) tsu[32] = cnt_arrive(C_Y);
    bar_sync(5, 256);
    if (tsu[32] == 127) {
#pragma unroll 1
      for (int i = ct; i < DM; i += 256) {
        const int tok = i >= DM / 2, cp = i - tok * (DM / 2);
        const uint32_t key = tok ? k2 : k1;
        const float r = __uint_as_float((key & 0xffff0000u) ^ ((key >> 31) ? 0x80000000u : 0xffff0000u));
        const float sg = rcp(1.f + __expf(-r));
        const size_t o = (size_t)(tok ? row2 : row1) * (DM / 2) + cp;
        const float2 ys = __ldcg(reinterpret_cast<const float2*>(g_y) + i);
        const uint32_t hb = hadd2(__ldcg(g_h2 + o), hmul2(pack_bf16(ys.x, ys.y), pack_bf16(sg, sg)));
        reinterpret_cast<uint32_t*>(prm.out)[o] = hadd2(__ldcg(g_x2 + o), hmul2(__ldcg(g_mod2 + cp).w, hb));
      }
      const uint4 z = make_uint4(0, 0, 0, 0);
      g_key[ct] = z; g_key[256 + ct] = z;
      if (ct < 144) g_mod1[ct] = z;
      if (ct < 24) g_cnt[ct * 32] = 0;
    }
    STAMP(79); GSTAMP(91);
  }
}

typedef CUresult (*PFN_enc)(CUtensorMap*, CUtensorMapDataType, cuuint32_t, void*, const cuuint64_t*, const cuuint64_t*,
                            const cuuint32_t*, const cuuint32_t*, CUtensorMapInterleave, CUtensorMapSwizzle,
                            CUtensorMapL2promotion, CUtensorMapFloatOOBfill);
static PFN_enc g_enc = nullptr;
static CUtensorMap mk_map(const void* p, uint64_t cols, uint64_t rows, uint32_t bc, uint32_t br, bool swz = true) {
  CUtensorMap m;
  cuuint64_t dims[2] = {cols, rows};
  cuuint64_t strides[1] = {cols * 2};
  cuuint32_t box[2] = {bc, br}, es[2] = {1, 1};
  g_enc(&m, CU_TENSOR_MAP_DATA_TYPE_BFLOAT16, 2, const_cast<void*>(p), dims, strides, box, es, CU_TENSOR_MAP_INTERLEAVE_NONE,
        swz ? CU_TENSOR_MAP_SWIZZLE_128B : CU_TENSOR_MAP_SWIZZLE_NONE, swz ? CU_TENSOR_MAP_L2_PROMOTION_L2_128B : CU_TENSOR_MAP_L2_PROMOTION_NONE,
        CU_TENSOR_MAP_FLOAT_OOB_FILL_NONE);
  return m;
}

extern "C" void kernel_launch(void* const* d_in, const int* in_sizes, int n_in, void* d_out, int out_size) {
  if (!g_enc) {
    cudaDriverEntryPointQueryResult st;
    cudaGetDriverEntryPoint("cuTensorMapEncodeTiled", (void**)&g_enc, cudaEnableDefault, &st);
    cudaFuncSetAttribute(k_mega, cudaFuncAttributeMaxDynamicSharedMemorySize, SM_TOTAL);
  }
  CUtensorMap mX = mk_map(d_in[0], DM, SQ, 64, 128);
  CUtensorMap mWq = mk_map(d_in[3], HQ * DH, DM, 64, 64);
  CUtensorMap mK = mk_map(d_in[1], DH, HKV * SK, 64, 128);
  CUtensorMap mV = mk_map(d_in[2], DH, HKV * SK, 64, 128);
  CUtensorMap mWo = mk_map(d_in[4], DM, HQ * DH, 64, 64);
  CUtensorMap mWg = mk_map(d_in[7], FF, DM, 40, 192, false);
  CUtensorMap mWu = mk_map(d_in[8], FF, DM, 40, 192, false);
  CUtensorMap mWd = mk_map(d_in[9], DM, FF, 64, 48);
  Params prm;
  prm.x = (const bf16*)d_in[0]; prm.k = (const bf16*)d_in[1]; prm.v = (const bf16*)d_in[2]; prm.wo = (const bf16*)d_in[4];
  prm.w_r = (const bf16*)d_in[6]; prm.c = (const bf16*)d_in[10]; prm.w_mod = (const bf16*)d_in[11];
  prm.out = (bf16*)d_out;
  cudaLaunchConfig_t cfg = {};
  cfg.gridDim = dim3(128); cfg.blockDim = dim3(384); cfg.dynamicSmemBytes = SM_TOTAL; cfg.stream = cudaStreamPerThread;
  cudaLaunchAttribute at[1];
  at[0].id = cudaLaunchAttributeClusterDimension;
  at[0].val.clusterDim.x = MC ? 2 : 1; at[0].val.clusterDim.y = 1; at[0].val.clusterDim.z = 1;
  cfg.attrs = at; cfg.numAttrs = 1;
  cudaLaunchKernelEx(&cfg, k_mega, mX, mWq, mK, mV, mWo, mWg, mWu, mWd, prm);
}
```

```cpp
#include <cuda_runtime.h>
#include <cuda_bf16.h>
#include <cuda.h>
#include <stdint.h>

typedef __nv_bfloat16 bf16;

constexpr int SQ = 2048, DM = 576, HQ = 32, HKV = 16, SK = 2048, DH = 128, FF = 4608;

#define XPF 0
#define WQPF0 0
#define WQPF1 0xff
#define MODG 0x225
#define FFN_GO 75
#define LAZY_LIMIT 1.0995116e12f
__device__ uint4 g_mod1[144];
__device__ uint4 g_mod2[288];
__device__ uint4 g_q[128 * 4 * 8 * 256];
__device__ float4 g_acc[16 * 2 * 72 * 4 * 32];
__device__ __align__(16) float g_y[2 * DM];
__device__ uint4 g_key[512];
__device__ uint32_t g_h2[SQ * DM / 2], g_x2[SQ * DM / 2];
__device__ unsigned int g_cnt[32 * 32];
__device__ unsigned int g_err;
#define HAS_ERR
enum { C_SIDE = 1, C_Y = 3, C_Q = 8 };

#define STAMP(i)
#define GSTAMP(i)
#define SETERR(v)
#define PSTAMP(t, i)

__device__ __forceinline__ uint32_t smem_u32(const void* p) { return (uint32_t)__cvta_generic_to_shared(p); }
__device__ __forceinline__ void mbar_init(uint32_t a, uint32_t cnt) { asm volatile("mbarrier.init.shared::cta.b64 [%0], %1;" ::"r"(a), "r"(cnt)); }
__device__ __forceinline__ void mbar_expect_tx(uint32_t a, uint32_t bytes) { asm volatile("mbarrier.arrive.expect_tx.shared::cta.b64 _, [%0], %1;" ::"r"(a), "r"(bytes) : "memory"); }
__device__ __forceinline__ void mbar_arrive_cl(uint32_t a_cluster) { asm volatile("mbarrier.arrive.shared::cluster.b64 _, [%0];" ::"r"(a_cluster) : "memory"); }
__device__ __forceinline__ void mbar_wait(uint32_t a, uint32_t parity) {
  asm volatile(
      "{\n.reg .pred p;\n.reg .u32 n;\nmov.u32 n, 0;\n"
      "WAIT_LOOP:\n"
      "mbarrier.try_wait.parity.shared::cta.b64 p, [%0], %1;\n"
      "@p bra WAIT_DONE;\n"
      "add.u32 n, n, 1;\n"
      "setp.lt.u32 p, n, 65536;\n"
      "@p bra WAIT_LOOP;\n"
      "WAIT_DONE:\n}\n" ::"r"(a), "r"(parity), "l"(&g_err) : "memory");
}
__device__ __forceinline__ unsigned ld_acquire(const unsigned* p) {
  unsigned v;
  asm volatile("ld.acquire.gpu.global.u32 %0, [%1];" : "=r"(v) : "l"(p) : "memory");
  return v;
}
__device__ __forceinline__ void cnt_wait(int idx, unsigned target) {
  uint32_t n = 0;
  while (ld_acquire(&g_cnt[idx * 32]) < target) {
    if (++n > (1u << 15)) { SETERR(2); break; }
  }
}
__device__ __forceinline__ unsigned cnt_arrive(int idx) {
  unsigned old;
  asm volatile("atom.add.acq_rel.gpu.global.u32 %0, [%1], 1;" : "=r"(old) : "l"(&g_cnt[idx * 32]) : "memory");
  return old;
}
__device__ __forceinline__ uint4 poll4(const uint4* p) {
  uint4 v;
  uint32_t n = 0;
  while (true) {
    asm volatile("ld.relaxed.gpu.global.v4.u32 {%0,%1,%2,%3}, [%4];" : "=r"(v.x), "=r"(v.y), "=r"(v.z), "=r"(v.w) : "l"(p) : "memory");
    if (v.x && v.y && v.z && v.w) break;
    if (++n > (1u << 15)) { SETERR(4); break; }
  }
  return v;
}
__device__ __forceinline__ uint32_t hmul2(uint32_t a, uint32_t b) { uint32_t r; asm("mul.rn.bf16x2 %0, %1, %2;" : "=r"(r) : "r"(a), "r"(b)); return r; }
__device__ __forceinline__ uint32_t hadd2(uint32_t a, uint32_t b) { uint32_t r; asm("add.rn.bf16x2 %0, %1, %2;" : "=r"(r) : "r"(a), "r"(b)); return r; }
__device__ __forceinline__ uint32_t hfma2(uint32_t a, uint32_t b, uint32_t c) { uint32_t r; asm("fma.rn.bf16x2 %0, %1, %2, %3;" : "=r"(r) : "r"(a), "r"(b), "r"(c)); return r; }
__device__ __forceinline__ void mma16816(float (&c)[4], uint32_t a0, uint32_t a1, uint32_t a2, uint32_t a3, uint32_t b0, uint32_t b1) {
  asm volatile("mma.sync.aligned.m16n8k16.row.col.f32.bf16.bf16.f32 {%0,%1,%2,%3}, {%4,%5,%6,%7}, {%8,%9}, {%0,%1,%2,%3};"
               : "+f"(c[0]), "+f"(c[1]), "+f"(c[2]), "+f"(c[3]) : "r"(a0), "r"(a1), "r"(a2), "r"(a3), "r"(b0), "r"(b1));
}
__device__ __forceinline__ void ldsm4t(uint32_t (&r)[4], uint32_t a) {
  asm volatile("ldmatrix.sync.aligned.m8n8.x4.trans.shared.b16 {%0,%1,%2,%3}, [%4];" : "=r"(r[0]), "=r"(r[1]), "=r"(r[2]), "=r"(r[3]) : "r"(a) : "memory");
}
__device__ __forceinline__ void ldsm4(uint32_t (&r)[4], uint32_t a) {
  asm volatile("ldmatrix.sync.aligned.m8n8.x4.shared.b16 {%0,%1,%2,%3}, [%4];" : "=r"(r[0]), "=r"(r[1]), "=r"(r[2]), "=r"(r[3]) : "r"(a) : "memory");
}
__device__ __forceinline__ void ldsm2t(uint32_t (&r)[2], uint32_t a) {
  asm volatile("ldmatrix.sync.aligned.m8n8.x2.trans.shared.b16 {%0,%1}, [%2];" : "=r"(r[0]), "=r"(r[1]) : "r"(a) : "memory");
}
__device__ __forceinline__ float warp_sum(float v) {
#pragma unroll
  for (int o = 16; o; o >>= 1) v += __shfl_xor_sync(~0u, v, o);
  return v;
}
__device__ __forceinline__ void tma_load_2d(uint32_t dst, const CUtensorMap* map, uint32_t mbar, int c0, int c1) {
  asm volatile("cp.async.bulk.tensor.2d.shared::cluster.global.mbarrier::complete_tx::bytes [%0], [%1, {%3, %4}], [%2];"
               ::"r"(dst), "l"(map), "r"(mbar), "r"(c0), "r"(c1) : "memory");
}
__device__ __forceinline__ void tma_load_2d_mc(uint32_t dst, const CUtensorMap* map, uint32_t mbar, int c0, int c1) {
  asm volatile("cp.async.bulk.tensor.2d.shared::cluster.global.mbarrier::complete_tx::bytes.multicast::cluster [%0], [%1, {%3, %4}], [%2], %5;"
               ::"r"(dst), "l"(map), "r"(mbar), "r"(c0), "r"(c1), "h"((uint16_t)3) : "memory");
}
__device__ __forceinline__ void tma_prefetch_2d(const CUtensorMap* map, int c0, int c1) {
  asm volatile("cp.async.bulk.prefetch.tensor.2d.L2.global.tile [%0, {%1, %2}];" ::"l"(map), "r"(c0), "r"(c1) : "memory");
}
__device__ __forceinline__ void bulk_prefetch(const void* p, uint32_t bytes) {
  asm volatile("cp.async.bulk.prefetch.L2.global [%0], %1;" ::"l"(p), "r"(bytes) : "memory");
}
__device__ __forceinline__ void bulk_load(uint32_t dst, const void* src, uint32_t bytes, uint32_t mbar) {
  asm volatile("cp.async.bulk.shared::cluster.global.mbarrier::complete_tx::bytes [%0], [%1], %2, [%3];"
               ::"r"(dst), "l"(src), "r"(bytes), "r"(mbar) : "memory");
}
__device__ __forceinline__ void wgmma_fence() { asm volatile("wgmma.fence.sync.aligned;" ::: "memory"); }
__device__ __forceinline__ void wgmma_commit() { asm volatile("wgmma.commit_group.sync.aligned;" ::: "memory"); }
template <int N> __device__ __forceinline__ void wgmma_wait() { asm volatile("wgmma.wait_group.sync.aligned %0;" ::"n"(N) : "memory"); }
__device__ __forceinline__ void fence_async() { asm volatile("fence.proxy.async.shared::cta;" ::: "memory"); }
__device__ __forceinline__ void bar_sync(int id, int n) { asm volatile("bar.sync %0, %1;" ::"r"(id), "r"(n) : "memory"); }
__device__ __forceinline__ void bar_arrive(int id, int n) { asm volatile("bar.arrive %0, %1;" ::"r"(id), "r"(n) : "memory"); }

__device__ __forceinline__ uint64_t mk_desc(uint32_t addr, uint32_t lbo_bytes, uint32_t sbo_bytes) {
  return (uint64_t)((addr & 0x3FFFF) >> 4) | ((uint64_t)((lbo_bytes >> 4) & 0x3FFF) << 16) |
         ((uint64_t)((sbo_bytes >> 4) & 0x3FFF) << 32) | ((uint64_t)1 << 62);
}

#define R32(d) \
  "+f"(d[0]), "+f"(d[1]), "+f"(d[2]), "+f"(d[3]), "+f"(d[4]), "+f"(d[5]), "+f"(d[6]), "+f"(d[7]), \
  "+f"(d[8]), "+f"(d[9]), "+f"(d[10]), "+f"(d[11]), "+f"(d[12]), "+f"(d[13]), "+f"(d[14]), "+f"(d[15]), \
  "+f"(d[16]), "+f"(d[17]), "+f"(d[18]), "+f"(d[19]), "+f"(d[20]), "+f"(d[21]), "+f"(d[22]), "+f"(d[23]), \
  "+f"(d[24]), "+f"(d[25]), "+f"(d[26]), "+f"(d[27]), "+f"(d[28]), "+f"(d[29]), "+f"(d[30]), "+f"(d[31])
#define R64(d) R32(d), \
  "+f"(d[32]), "+f"(d[33]), "+f"(d[34]), "+f"(d[35]), "+f"(d[36]), "+f"(d[37]), "+f"(d[38]), "+f"(d[39]), \
  "+f"(d[40]), "+f"(d[41]), "+f"(d[42]), "+f"(d[43]), "+f"(d[44]), "+f"(d[45]), "+f"(d[46]), "+f"(d[47]), \
  "+f"(d[48]), "+f"(d[49]), "+f"(d[50]), "+f"(d[51]), "+f"(d[52]), "+f"(d[53]), "+f"(d[54]), "+f"(d[55]), \
  "+f"(d[56]), "+f"(d[57]), "+f"(d[58]), "+f"(d[59]), "+f"(d[60]), "+f"(d[61]), "+f"(d[62]), "+f"(d[63])
#define S32 \
  "{%0,%1,%2,%3,%4,%5,%6,%7,%8,%9,%10,%11,%12,%13,%14,%15,%16,%17,%18,%19,%20,%21,%22,%23,%24,%25,%26,%27,%28,%29,%30,%31}"
#define S64 \
  "{%0,%1,%2,%3,%4,%5,%6,%7,%8,%9,%10,%11,%12,%13,%14,%15,%16,%17,%18,%19,%20,%21,%22,%23,%24,%25,%26,%27,%28,%29,%30,%31," \
  "%32,%33,%34,%35,%36,%37,%38,%39,%40,%41,%42,%43,%44,%45,%46,%47,%48,%49,%50,%51,%52,%53,%54,%55,%56,%57,%58,%59,%60,%61,%62,%63}"

template <int TB>
__device__ __forceinline__ void wgmma128_ss(float (&d)[64], uint64_t da, uint64_t db, int scale_d) {
  asm volatile("{\n.reg .pred p;\nsetp.ne.b32 p, %66, 0;\n"
               "wgmma.mma_async.sync.aligned.m64n128k16.f32.bf16.bf16 " S64 ", %64, %65, p, 1, 1, 0, %67;\n}\n"
               : R64(d) : "l"(da), "l"(db), "r"(scale_d), "n"(TB));
}
template <int TB>
__device__ __forceinline__ void wgmma64_ss(float (&d)[64], uint64_t da, uint64_t db, int scale_d) {
  asm volatile("{\n.reg .pred p;\nsetp.ne.b32 p, %34, 0;\n"
               "wgmma.mma_async.sync.aligned.m64n64k16.f32.bf16.bf16 " S32 ", %32, %33, p, 1, 1, 0, %35;\n}\n"
               : R32(d) : "l"(da), "l"(db), "r"(scale_d), "n"(TB));
}
template <int TB>
__device__ __forceinline__ void wgmma128_rs(float (&d)[64], uint32_t a0, uint32_t a1, uint32_t a2, uint32_t a3, uint64_t db, int scale_d) {
  asm volatile("{\n.reg .pred p;\nsetp.ne.b32 p, %69, 0;\n"
               "wgmma.mma_async.sync.aligned.m64n128k16.f32.bf16.bf16 " S64 ", {%64,%65,%66,%67}, %68, p, 1, 1, %70;\n}\n"
               : R64(d) : "r"(a0), "r"(a1), "r"(a2), "r"(a3), "l"(db), "r"(scale_d), "n"(TB));
}
__device__ __forceinline__ uint32_t pack_bf16(float a, float b) {
  uint32_t r;
  asm("cvt.rn.bf16x2.f32 %0, %1, %2;" : "=r"(r) : "f"(b), "f"(a));
  return r;
}
__device__ __forceinline__ float ex2(float x) { float y; asm("ex2.approx.ftz.f32 %0, %1;" : "=f"(y) : "f"(x)); return y; }
__device__ __forceinline__ float bfr(float x) { return __bfloat162float(__float2bfloat16(x)); }
__device__ __forceinline__ float bf_lo(uint32_t u) { return __uint_as_float(u << 16); }
__device__ __forceinline__ float bf_hi(uint32_t u) { return __uint_as_float(u & 0xffff0000u); }
__device__ __forceinline__ uint4 lds128(uint32_t a) {
  uint4 v;
  asm volatile("ld.shared.v4.b32 {%0,%1,%2,%3}, [%4];" : "=r"(v.x), "=r"(v.y), "=r"(v.z), "=r"(v.w) : "r"(a) : "memory");
  return v;
}
__device__ __forceinline__ void sts128(uint32_t a, uint4 v) {
  asm volatile("st.shared.v4.b32 [%0], {%1,%2,%3,%4};" ::"r"(a), "r"(v.x), "r"(v.y), "r"(v.z), "r"(v.w) : "memory");
}
__device__ __forceinline__ void red_add_v4(float4* p, float a, float b, float c, float d) {
  asm volatile("red.global.add.v4.f32 [%0], {%1,%2,%3,%4};" ::"l"(p), "f"(a), "f"(b), "f"(c), "f"(d) : "memory");
}
__device__ __forceinline__ float rcp(float x) { float y; asm("rcp.approx.ftz.f32 %0, %1;" : "=f"(y) : "f"(x)); return y; }
__device__ __forceinline__ float sqrt_a(float x) { float y; asm("sqrt.approx.ftz.f32 %0, %1;" : "=f"(y) : "f"(x)); return y; }
__device__ __forceinline__ float silu_bf(float v) { return bfr(v * rcp(1.f + __expf(-v))); }

constexpr int SM_STASH = 131072;
constexpr int SM_H = 81920;
constexpr int SM_MISC = 229376;
constexpr int SM_TOTAL = 232448;
constexpr int B_FULLQ = 0, B_EMPTYQ = 40, B_FULLA = 80, B_EMPTYA = 112, B_FULLO = 144, B_EMPTYO = 192, B_X = 240, B_FFN = 248;
constexpr int SM_MOD = SM_MISC + 256;
constexpr int SM_RED = SM_MISC + 2560;
constexpr int SM_WG = 0, SM_WU = 46080, SM_WD = 92160;
constexpr int SM_T = 147456;

struct Params {
  const bf16 *x, *k, *c, *w_mod, *w_r, *wo, *v, *wq;
  bf16* out;
};

__global__ void __launch_bounds__(384, 1)
k_mega(const __grid_constant__ CUtensorMap mX, const __grid_constant__ CUtensorMap mWq,
       const __grid_constant__ CUtensorMap mK, const __grid_constant__ CUtensorMap mV,
       const __grid_constant__ CUtensorMap mWo, const __grid_constant__ CUtensorMap mWg,
       const __grid_constant__ CUtensorMap mWu, const __grid_constant__ CUtensorMap mWd, const Params prm) {
  extern __shared__ __align__(1024) uint8_t smem_raw[];
  const uint32_t sb = smem_u32(smem_raw);
  const uint32_t sBar = sb + SM_MISC;
  const int tid = threadIdx.x, lane = tid & 31;
  PSTAMP(0, 84);
  const int warp = tid >> 5;
  const int b = blockIdx.x, rank = b & 1, qt = (b >> 1) & 15, kg = b >> 5, hg = kg * 2 + rank;
  const int hcol = (kg * 8 + rank) * DH;
  auto wq_prefetch = [&](int mask) {
    const bf16* wp = prm.wq + (size_t)(qt * 36 + ((tid - 128) >> 3)) * (HQ * DH) + hcol + ((tid & 6) * 2 + (tid & 1)) * 64;
    if ((mask >> (tid & 7)) & 1) {
      asm volatile("prefetch.global.L2 [%0];" ::"l"(wp));
      if (warp == 4) asm volatile("prefetch.global.L2 [%0];" ::"l"(wp + 32 * (HQ * DH)));
    }
  };
  if (warp >= 4) wq_prefetch(WQPF0);
  if (tid == 0) {
#pragma unroll
    for (int i = 0; i < 32; i++)
      mbar_init(sBar + i * 8, ((i >= 5 && i < 10) || (i >= 14 && i < 18)) ? 16 : (i >= 24 && i < 30) ? 8 : 1);
    asm volatile("fence.mbarrier_init.release.cluster;" ::: "memory");
    mbar_expect_tx(sBar + B_X, 9 * 16384);
  }
  __syncwarp();
  asm volatile("barrier.cluster.arrive.relaxed.aligned;" ::: "memory");
#define CL_WAIT() asm volatile("barrier.cluster.wait.acquire.aligned;" ::: "memory")
  const bool do_mod1 = warp >= 1 && warp < 4 && b < 72;
  if (warp < 4) {
    auto load_pair = [&](uint32_t dst, const CUtensorMap* m, uint32_t bar, int c0, int c1, int d0, int d1) {
      tma_load_2d(dst, m, bar, c0, c1);
      tma_load_2d(dst + 8192, m, bar, c0 + d0, c1 + d1);
    };
    if (warp == 0) {
      PSTAMP(0, 85);
      CL_WAIT();
      PSTAMP(0, 86);
      if (lane == 0) {
#pragma unroll
        for (int i = 0; i < 5; i++)
          if (i < 4 || rank == 0) tma_load_2d_mc(sb + SM_H + (2 * i + rank) * 16384, &mX, sBar + B_X, (2 * i + rank) * 64, qt * 128);
      }
    }
    PSTAMP(0, 87);
    if (do_mod1) {
      uint4 mv[12]; float ms[12];
      const int st = tid - 32;
#pragma unroll
      for (int i = 0; i < 12; i++) {
        const int r = (st >> 1) + 48 * i;
        mv[i] = __ldg(reinterpret_cast<const uint4*>(prm.w_mod + (size_t)r * (6 * DM) + b * 16 + (st & 1) * 8));
        ms[i] = __bfloat162float(prm.c[r]);
      }
      float a[8];
#pragma unroll
      for (int i = 0; i < 8; i++) a[i] = 0.f;
#pragma unroll
      for (int i = 0; i < 12; i++) {
        const float sv = silu_bf(ms[i]);
        if (i == 11 && sv != 123.f) PSTAMP(32, 88);
        a[0] += sv * bf_lo(mv[i].x); a[1] += sv * bf_hi(mv[i].x); a[2] += sv * bf_lo(mv[i].y); a[3] += sv * bf_hi(mv[i].y);
        a[4] += sv * bf_lo(mv[i].z); a[5] += sv * bf_hi(mv[i].z); a[6] += sv * bf_lo(mv[i].w); a[7] += sv * bf_hi(mv[i].w);
      }
      const bool u2 = lane & 2, u4 = lane & 4, u8 = lane & 8;
#pragma unroll
      for (int i = 0; i < 4; i++) { float snd = u2 ? a[i] : a[i + 4]; float kp = u2 ? a[i + 4] : a[i]; a[i] = kp + __shfl_xor_sync(~0u, snd, 2); }
#pragma unroll
      for (int i = 0; i < 2; i++) { float snd = u4 ? a[i] : a[i + 2]; float kp = u4 ? a[i + 2] : a[i]; a[i] = kp + __shfl_xor_sync(~0u, snd, 4); }
      { float snd = u8 ? a[0] : a[1]; float kp = u8 ? a[1] : a[0]; a[0] = kp + __shfl_xor_sync(~0u, snd, 8); }
      a[0] += __shfl_xor_sync(~0u, a[0], 16);
      float* const red = reinterpret_cast<float*>(smem_raw + SM_RED);
      if (lane < 16) red[(warp - 1) * 16 + (lane & 1) * 8 + (u2 ? 4 : 0) + (u4 ? 2 : 0) + (u8 ? 1 : 0)] = a[0];
      bar_sync(6, 96);
      if (tid < 40) {
        const float2 x = *reinterpret_cast<float2*>(red + lane * 2), y = *reinterpret_cast<float2*>(red + 16 + lane * 2), z = *reinterpret_cast<float2*>(red + 32 + lane * 2);
        uint32_t w = pack_bf16(x.x + y.x + z.x, x.y + y.y + z.y);
        if (b >= 36) w = hadd2(w, 0x3f803f80u);
        asm volatile("st.relaxed.gpu.global.u32 [%0], %1;" ::"l"(reinterpret_cast<uint32_t*>(g_mod1) + b * 8 + lane), "r"(~w) : "memory");
      }
    }
    __syncwarp();
    PSTAMP(32, 89);
    if (warp > 0) CL_WAIT();
    asm volatile("setmaxnreg.dec.sync.aligned.u32 40;");
    if (tid == 0) {
      uint32_t ph = 0;
      {
        int g5 = 0, c = 5, hs = 1;
#pragma unroll 1
        for (int i = 5; i < 36; i++) {
          const int g = i == 35 ? 2 : g5;
          g5 = g5 == 4 ? 0 : g5 + 1;
          mbar_wait(sBar + B_EMPTYQ + g * 8, (ph >> g) & 1);
          ph ^= 1u << g;
          mbar_expect_tx(sBar + B_FULLQ + g * 8, 16384);
          load_pair(sb + g * 16384, &mWq, sBar + B_FULLQ + g * 8, hcol + (hs & 3) * 256, c * 64, 64, 0);
          if (++c == 9) { c = 0; hs++; }
        }
      }
#pragma unroll 1
      for (int t = 0; t < 128; t++) {
        const int s = t & 3, it = t >> 1;
        if (t < 2) {
#pragma unroll 1
          for (int g = t * 2; g < t * 3 + 2; g++) mbar_wait(sBar + B_EMPTYQ + g * 8, (ph >> g) & 1);
        } else if (t >= 4) {
          mbar_wait(sBar + B_EMPTYA + s * 8, ((t >> 2) & 1) ^ 1);
        }
        mbar_expect_tx(sBar + B_FULLA + s * 8, 32768);
        tma_load_2d_mc(sb + s * 32768 + rank * 16384, (t & 1) ? &mV : &mK, sBar + B_FULLA + s * 8, rank * 64, kg * 4 * SK + it * 128);
      }
      mbar_wait(sBar + B_X, 1);
      {
        int g6 = 0, par = 1;
#pragma unroll 1
        for (int i = 0; i < 36; i++) {
          const int g = g6 < 4 ? g6 : g6 + 2;
          if (i < 6) mbar_wait(sBar + B_EMPTYA + (g >> 1) * 8, 1);
          else mbar_wait(sBar + B_EMPTYO + g6 * 8, par);
          mbar_expect_tx(sBar + B_FULLO + g6 * 8, 16384);
          const bool sm = i < 4;
          const int ch = (i - 4) >> 3, kc = (i - 4) & 7;
          load_pair(sb + g * 16384, &mWo, sBar + B_FULLO + g6 * 8, sm ? 512 : ch * 128, hcol + (sm ? i * 256 : (kc >> 1) * 256 + (kc & 1) * 64), sm ? 0 : 64, sm ? 64 : 0);
          if (++g6 == 6) { g6 = 0; par ^= 1; }
        }
      }
#pragma unroll 1
      for (int g6 = 0; g6 < 6; g6++) mbar_wait(sBar + B_EMPTYO + g6 * 8, 1);
      if (FFN_GO) mbar_wait(sBar + B_X, 0);
      mbar_expect_tx(sBar + B_FFN, 2 * 46080 + 9 * 6144);
#pragma unroll 1
      for (int i = 0; i < 3; i++) {
        tma_load_2d(sb + SM_WG + i * 15360, &mWg, sBar + B_FFN, (b * 36) & ~7, i * 192);
        tma_load_2d(sb + SM_WU + i * 15360, &mWu, sBar + B_FFN, (b * 36) & ~7, i * 192);
      }
#pragma unroll 1
      for (int i = 0; i < 9; i++) tma_load_2d(sb + SM_WD + i * 6144, &mWd, sBar + B_FFN, i * 64, b * 36);
    } else if (warp > 0) {
      const int st = tid - 32;
      mbar_wait(sBar + B_FULLQ, 0);
      mbar_wait(sBar + B_FULLQ, 1);
      const bf16* const kvp = (rank ? prm.v : prm.k) + ((size_t)kg * 4 * SK + qt * 128) * DH;
      if (st == 0) bulk_prefetch(kvp, 32768);
      mbar_wait(sBar + B_FULLA, 0);
      float4* z = g_acc + (size_t)b * 2304;
#pragma unroll 4
      for (int i = st; i < 2304; i += 96) z[i] = make_float4(0.f, 0.f, 0.f, 0.f);
      if (b == 127) {
#pragma unroll 1
        for (int i = st; i < 2 * DM; i += 96) g_y[i] = 0.f;
      }
      if (b < 96) {
        const int grp = b * 3 + warp - 1;
        float a[8];
#pragma unroll
        for (int i = 0; i < 8; i++) a[i] = 0.f;
#pragma unroll 2
        for (int r = lane; r < DM; r += 32) {
          uint4 v = __ldg(reinterpret_cast<const uint4*>(prm.w_mod + (size_t)r * (6 * DM) + 2 * DM + grp * 8));
          float s = silu_bf(__bfloat162float(prm.c[r]));
          a[0] += s * bf_lo(v.x); a[1] += s * bf_hi(v.x); a[2] += s * bf_lo(v.y); a[3] += s * bf_hi(v.y);
          a[4] += s * bf_lo(v.z); a[5] += s * bf_hi(v.z); a[6] += s * bf_lo(v.w); a[7] += s * bf_hi(v.w);
        }
#pragma unroll
        for (int i = 0; i < 8; i++) a[i] = warp_sum(a[i]);
        if (lane == 0) {
          const int kind = grp / 72, cp = (grp - kind * 72) * 4;
#pragma unroll
          for (int i = 0; i < 4; i++) {
            uint32_t w = pack_bf16(a[2 * i], a[2 * i + 1]);
            if (kind == 2) w = hadd2(w, 0x3f803f80u);
            reinterpret_cast<uint32_t*>(g_mod2)[(cp + i) * 4 + kind] = w;
          }
        }
      }
      __syncwarp();
      if (lane == 0) cnt_arrive(C_SIDE);
      if (tid == 32) {
#pragma unroll 1
        for (int p = 0; p < 22; p++) {
          mbar_wait(sBar + B_FULLA, p & 1);
          if ((p & 7) == 2) bulk_prefetch(kvp + (size_t)((p >> 3) + 1) * SK * DH, 32768);
          if (p == 17) bulk_prefetch(prm.wo + ((size_t)kg * 1024 + (b & 31) * 32) * DM, 32 * DM * 2);
          if (p >= 19) {
            const int i = p - 19;
            tma_prefetch_2d(&mWg, (b * 36) & ~7, i * 192); tma_prefetch_2d(&mWu, (b * 36) & ~7, i * 192);
            tma_prefetch_2d(&mWd, i * 192, b * 36); tma_prefetch_2d(&mWd, i * 192 + 64, b * 36); tma_prefetch_2d(&mWd, i * 192 + 128, b * 36);
          }
        }
        cnt_wait(C_SIDE, 128 * 3);
        asm volatile("mbarrier.arrive.shared::cta.b64 _, [%0];" ::"r"(sBar + B_X) : "memory");
      }
    }
  } else {
    const int cw = (warp >> 2) - 1;
    const int w8 = warp - 4;
    const int ct = tid - 128;
    const int g = lane >> 2, t4 = lane & 3;
    uint32_t relBar;
    asm volatile("mapa.shared::cluster.u32 %0, %1, %2;" : "=r"(relBar) : "r"(sBar), "r"(rank ^ (lane & 1)));
    auto release = [&](int off) {
      if (lane < 2) mbar_arrive_cl(relBar + off);
    };
    auto release1 = [&](int off) {
      if (lane == 0) mbar_arrive_cl(relBar + off);
    };
    STAMP(0); GSTAMP(90);
    CL_WAIT();
    if (tid == 128) {
#pragma unroll
      for (int i = 0; i < 5; i++) {
        mbar_expect_tx(sBar + B_FULLQ + i * 8, 16384);
        tma_load_2d(sb + i * 16384, &mWq, sBar + B_FULLQ + i * 8, hcol + 256, i * 64);
        tma_load_2d(sb + i * 16384 + 8192, &mWq, sBar + B_FULLQ + i * 8, hcol + 320, i * 64);
      }
    }
    __syncwarp();
    mbar_wait(sBar + B_X, 0);
    wq_prefetch(WQPF1);
    STAMP(1);
    float lnS[4], lnB[4];
    {
      const uint32_t la = sb + SM_H + (w8 * 16 + (lane & 15)) * 128 + (((lane >> 4) ^ (lane & 7)) << 4);
      const uint32_t one = 0x3f803f80u;
      float c[6][4];
#pragma unroll
      for (int i = 0; i < 24; i++) c[i >> 2][i & 3] = 0.f;
      uint32_t nA, nB;
      {
        uint32_t a[4];
        ldsm4(a, la);
        nA = __byte_perm(__shfl_sync(~0u, a[0], lane & 28), 0, 0x1010) ^ 0x80008000u;
        nB = __byte_perm(__shfl_sync(~0u, a[1], lane & 28), 0, 0x1010) ^ 0x80008000u;
      }
#pragma unroll 3
      for (int bx = 0; bx < 9; bx++) {
#pragma unroll
        for (int ks = 0; ks < 4; ks++) {
          uint32_t a[4];
          ldsm4(a, (la ^ (ks << 5)) + bx * 16384);
          a[0] = hadd2(a[0], nA); a[1] = hadd2(a[1], nB); a[2] = hadd2(a[2], nA); a[3] = hadd2(a[3], nB);
          mma16816(c[ks & 1], a[0], a[1], a[2], a[3], a[0], a[2]);
          mma16816(c[2 + (ks & 1)], a[0], a[1], a[2], a[3], a[1], a[3]);
          mma16816(c[4 + (ks & 1)], a[0], a[1], a[2], a[3], one, one);
        }
      }
      const float eA = (c[4][0] + c[5][0]) * (1.f / DM), eB = (c[4][2] + c[5][2]) * (1.f / DM);
      const float mA = eA - bf_lo(nA), mB = eB - bf_lo(nB);
      const float vA = ((g & 1) ? c[0][1] + c[1][1] : c[0][0] + c[1][0]) * (1.f / DM) - eA * eA;
      const float vB = ((g & 1) ? c[2][3] + c[3][3] : c[2][2] + c[3][2]) * (1.f / DM) - eB * eB;
      const float rA = rsqrtf(fmaxf(vA, 0.f) + 1e-5f), rB = rsqrtf(fmaxf(vB, 0.f) + 1e-5f);
#pragma unroll
      for (int i = 0; i < 4; i++) {
        const int rho = (i & 1) * 4 + (lane >> 3), src = rho * 4 + (rho >> 1);
        lnS[i] = __shfl_sync(~0u, (i >> 1) ? rB : rA, src);
        lnB[i] = __shfl_sync(~0u, (i >> 1) ? -mB * rB : -mA * rA, src);
      }
    }
    STAMP(2);
    if (ct < 144) {
      const uint4 v = poll4(g_mod1 + ct);
      sts128(sb + SM_MOD + ct * 16, make_uint4(~v.x, ~v.y, ~v.z, ~v.w));
    }
    bar_sync(5, 256);
    asm volatile("setmaxnreg.inc.sync.aligned.u32 232;");
    STAMP(3);
    const uint32_t lnA = sb + SM_H + (w8 * 16 + (lane >> 3)) * 128 + (((lane & 7) ^ (lane >> 3)) << 4);
    auto modulate = [&](int bx) {
      const uint4 sa = lds128(sb + SM_MOD + bx * 128 + (lane & 7) * 16), ca = lds128(sb + SM_MOD + 1152 + bx * 128 + (lane & 7) * 16);
      const uint32_t sv[4] = {sa.x, sa.y, sa.z, sa.w}, cv[4] = {ca.x, ca.y, ca.z, ca.w};
#pragma unroll
      for (int i = 0; i < 4; i++) {
        const uint32_t a = (lnA ^ ((i & 1) << 6)) + i * 512 + bx * 16384;
        const uint4 u = lds128(a);
        const uint32_t w[4] = {u.x, u.y, u.z, u.w};
        uint32_t o[4];
#pragma unroll
        for (int e = 0; e < 4; e++)
          o[e] = pack_bf16(fmaf(fmaf(bf_lo(w[e]), lnS[i], lnB[i]), bf_lo(cv[e]), bf_lo(sv[e])), fmaf(fmaf(bf_hi(w[e]), lnS[i], lnB[i]), bf_hi(cv[e]), bf_hi(sv[e])));
        sts128(a, make_uint4(o[0], o[1], o[2], o[3]));
      }
    };
    STAMP(4);
    float S[64], O[64];
    uint32_t P[32], Qf[32];
    const uint64_t dA_k = mk_desc(sb + cw * 8192, 16, 1024);
    const uint64_t dB_k = mk_desc(sb, 16, 1024);
    const uint64_t dB_n8 = mk_desc(sb, 8192, 1024);
    const uint64_t dB_n16 = mk_desc(sb, 16384, 1024);
    uint4* const qpark = g_q + (size_t)b * (4 * 8 * 256) + ct;
    {
      uint32_t ph = 0;
      int g5 = 0, prevg = 0;
#pragma unroll 1
      for (int hs = 1; hs <= 4; hs++) {
#pragma unroll 1
        for (int c = 0; c < 9; c++) {
          const int gr = (hs == 4 && c == 8) ? 2 : g5;
          g5 = g5 == 4 ? 0 : g5 + 1;
          if (hs == 1 && ((MODG >> c) & 1)) {
            int bx = c;
#pragma unroll 1
            do modulate(bx); while (!((MODG >> ++bx) & 1));
            fence_async();
            bar_sync(3 + cw, 128);
          }
          mbar_wait(sBar + B_FULLQ + gr * 8, (ph >> gr) & 1);
          ph ^= 1u << gr;
          wgmma_fence();
          const uint64_t da = dA_k + ((SM_H + c * 16384) >> 4), db = dB_n8 + ((gr * 16384) >> 4);
#pragma unroll
          for (int kk = 0; kk < 4; kk++) wgmma128_ss<1>(S, da + kk * 2, db + kk * 128, (c | kk) != 0);
          wgmma_commit();
          wgmma_wait<1>();
          if (c > 0) release(B_EMPTYQ + prevg * 8);
          prevg = gr;
        }
        wgmma_wait<0>();
        release(B_EMPTYQ + prevg * 8);
#pragma unroll
        for (int i = 0; i < 32; i++) Qf[i] = pack_bf16(S[2 * i], S[2 * i + 1]);
#pragma unroll
        for (int i = 0; i < 8; i++) qpark[((hs & 3) * 8 + i) * 256] = make_uint4(Qf[4 * i], Qf[4 * i + 1], Qf[4 * i + 2], Qf[4 * i + 3]);
        STAMP(79 + hs);
      }
    }
    STAMP(5);
    const float sc = 0.08838834764831845f * 1.4426950408889634f;
    float mb0 = 0.f, mb1 = 0.f, l0 = 0.f, l1 = 0.f;
    auto store_o = [&](uint32_t base) {
      float a0 = l0, a1 = l1;
      a0 += __shfl_xor_sync(~0u, a0, 1); a0 += __shfl_xor_sync(~0u, a0, 2);
      a1 += __shfl_xor_sync(~0u, a1, 1); a1 += __shfl_xor_sync(~0u, a1, 2);
      const float i0 = rcp(a0), i1 = rcp(a1);
      const uint32_t ra = base + (w8 * 16 + (lane & 15)) * 128 + (((lane >> 4) ^ (lane & 7)) << 4);
#pragma unroll
      for (int j = 0; j < 16; j += 2) {
        const uint32_t a = (ra ^ ((j & 7) << 4)) + (j >> 3) * 16384;
        asm volatile("stmatrix.sync.aligned.m8n8.x4.shared.b16 [%0], {%1,%2,%3,%4};" ::"r"(a),
                     "r"(pack_bf16(O[j * 4] * i0, O[j * 4 + 1] * i0)), "r"(pack_bf16(O[j * 4 + 2] * i1, O[j * 4 + 3] * i1)),
                     "r"(pack_bf16(O[j * 4 + 4] * i0, O[j * 4 + 5] * i0)), "r"(pack_bf16(O[j * 4 + 6] * i1, O[j * 4 + 7] * i1)) : "memory");
      }
    };
    auto row_max = [&](float& x0, float& x1) {
      float y0 = fmaxf(S[0], S[1]), y1 = fmaxf(S[2], S[3]), z0 = fmaxf(S[4], S[5]), z1 = fmaxf(S[6], S[7]);
#pragma unroll
      for (int j = 2; j < 16; j += 2) {
        y0 = fmaxf(y0, fmaxf(S[j * 4], S[j * 4 + 1])); y1 = fmaxf(y1, fmaxf(S[j * 4 + 2], S[j * 4 + 3]));
        z0 = fmaxf(z0, fmaxf(S[j * 4 + 4], S[j * 4 + 5])); z1 = fmaxf(z1, fmaxf(S[j * 4 + 6], S[j * 4 + 7]));
      }
      x0 = fmaxf(y0, z0); x1 = fmaxf(y1, z1);
      x0 = fmaxf(x0, __shfl_xor_sync(~0u, x0, 1)); x1 = fmaxf(x1, __shfl_xor_sync(~0u, x1, 1));
      x0 = fmaxf(x0, __shfl_xor_sync(~0u, x0, 2)); x1 = fmaxf(x1, __shfl_xor_sync(~0u, x1, 2));
    };
    float s0, s1;
    auto exps = [&](int j0, int j1) {
#pragma unroll
      for (int j = j0; j < j1; j++) {
        S[j * 4] = ex2(fmaf(S[j * 4], sc, -mb0)); S[j * 4 + 1] = ex2(fmaf(S[j * 4 + 1], sc, -mb0));
        S[j * 4 + 2] = ex2(fmaf(S[j * 4 + 2], sc, -mb1)); S[j * 4 + 3] = ex2(fmaf(S[j * 4 + 3], sc, -mb1));
        s0 += S[j * 4] + S[j * 4 + 1]; s1 += S[j * 4 + 2] + S[j * 4 + 3];
      }
    };
    auto cvtP = [&]() {
#pragma unroll
      for (int i = 0; i < 32; i++) P[i] = pack_bf16(S[2 * i], S[2 * i + 1]);
    };
    auto issue_qk = [&](int ks) {
      const uint64_t db = dB_k + ((ks * 32768) >> 4);
#pragma unroll
      for (int kk = 0; kk < 8; kk++)
        wgmma128_rs<0>(S, Qf[kk * 4], Qf[kk * 4 + 1], Qf[kk * 4 + 2], Qf[kk * 4 + 3], db + (kk >> 2) * 1024 + (kk & 3) * 2, kk != 0);
    };
    auto issue_pv = [&](int vs, int first) {
      const uint64_t db = dB_n16 + ((vs * 32768) >> 4);
#pragma unroll
      for (int kk = 0; kk < 8; kk++)
        wgmma128_rs<1>(O, P[kk * 4], P[kk * 4 + 1], P[kk * 4 + 2], P[kk * 4 + 3], db + kk * 128, kk ? 1 : !first);
    };
    auto sched_fence = [&]() {
      asm volatile("st.shared.f32 [%0], %1;" ::"r"(sb + SM_RED + lane * 4), "f"(S[31]) : "memory");
    };
    if (cw == 0) bar_arrive(1, 256);
#pragma unroll 1
    for (int h = 0; h < 4; h++) {
      {
        STAMP(6 + h * 16);
        mbar_wait(sBar + B_FULLA, 0);
        if (h > 0) mbar_wait(sBar + B_FULLA + 24, 1);
        bar_sync(1 + cw, 256);
        wgmma_fence();
        issue_qk(0);
        wgmma_commit();
        if (h > 0) { issue_pv(3, 0); wgmma_commit(); }
        else asm volatile("wgmma.commit_group.sync.aligned; // empty" ::: "memory");
        bar_arrive(2 - cw, 256);
        wgmma_wait<1>();
        release(B_EMPTYA);
        s0 = 0.f; s1 = 0.f;
        float x0, x1;
        row_max(x0, x1);
        mb0 = x0 * sc; mb1 = x1 * sc;
        exps(0, 8);
        sched_fence();
        wgmma_wait<0>();
        if (h > 0) {
          release(B_EMPTYA + 24);
          store_o(sb + SM_STASH + (h - 1) * 32768);
        }
        exps(8, 16);
        cvtP();
        l0 = s0; l1 = s1;
      }
#pragma unroll 1
      for (int j = 1; j < 16; j++) {
        const int ks = (j & 1) * 2, vs = 3 - ks;
        mbar_wait(sBar + B_FULLA + ks * 8, (j >> 1) & 1);
        mbar_wait(sBar + B_FULLA + vs * 8, ((j - 1) >> 1) & 1);
        bar_sync(1 + cw, 256);
        wgmma_fence();
        issue_qk(ks);
        wgmma_commit();
        issue_pv(vs, j == 1);
        wgmma_commit();
        bar_arrive(2 - cw, 256);
        wgmma_wait<1>();
        release(B_EMPTYA + ks * 8);
        if (j == 15 && h < 3) {
          const uint4* qp = qpark + (h + 1) * (8 * 256);
#pragma unroll
          for (int i = 0; i < 8; i++) {
            uint4 v = __ldcg(qp + i * 256);
            Qf[4 * i] = v.x; Qf[4 * i + 1] = v.y; Qf[4 * i + 2] = v.z; Qf[4 * i + 3] = v.w;
          }
        }
        s0 = 0.f; s1 = 0.f;
        exps(0, 8);
        sched_fence();
        wgmma_wait<0>();
        release(B_EMPTYA + vs * 8);
        bool bad = __any_sync(~0u, !(s0 <= LAZY_LIMIT && s1 <= LAZY_LIMIT));
        if (__builtin_expect(!bad, 1)) {
          exps(8, 16);
          cvtP();
          bad = __any_sync(~0u, !(s0 <= LAZY_LIMIT && s1 <= LAZY_LIMIT));
        }
        if (__builtin_expect(bad, 0)) {
          const uint32_t* kp = reinterpret_cast<const uint32_t*>(prm.k + ((size_t)(kg * 4 + h) * SK + j * 128 + g) * DH) + t4;
          const uint4* qp = qpark + h * (8 * 256);
          float4 tmp[16];
#pragma unroll 1
          for (int jn = 0; jn < 16; jn++) {
            float c[4] = {0.f, 0.f, 0.f, 0.f};
#pragma unroll 1
            for (int kk = 0; kk < 8; kk++) {
              const uint4 a = __ldcg(qp + kk * 256);
              mma16816(c, a.x, a.y, a.z, a.w, __ldg(kp + jn * 512 + kk * 8), __ldg(kp + jn * 512 + kk * 8 + 4));
            }
            tmp[jn] = make_float4(c[0], c[1], c[2], c[3]);
          }
#pragma unroll
          for (int jn = 0; jn < 16; jn++) { const float4 c = tmp[jn]; S[jn * 4] = c.x; S[jn * 4 + 1] = c.y; S[jn * 4 + 2] = c.z; S[jn * 4 + 3] = c.w; }
          float x0, x1;
          row_max(x0, x1);
          const float n0 = fmaxf(mb0, x0 * sc), n1 = fmaxf(mb1, x1 * sc);
          const float f0 = ex2(mb0 - n0), f1 = ex2(mb1 - n1);
          mb0 = n0; mb1 = n1;
          l0 *= f0; l1 *= f1;
#pragma unroll
          for (int i = 0; i < 16; i++) { O[i * 4] *= f0; O[i * 4 + 1] *= f0; O[i * 4 + 2] *= f1; O[i * 4 + 3] *= f1; }
          s0 = 0.f; s1 = 0.f;
          exps(0, 16);
          cvtP();
        }
        l0 += s0; l1 += s1;
      }
    }
    STAMP(70);
    mbar_wait(sBar + B_FULLA + 24, 1);
    if (cw == 0) bar_sync(1, 256);
    wgmma_fence();
    issue_pv(3, 0);
    wgmma_commit();
    wgmma_wait<0>();
    release(B_EMPTYA + 24);
    mbar_wait(sBar + B_EMPTYA + 16, 1);
    store_o(sb + 2 * 32768);
    fence_async();
    bar_sync(3 + cw, 128);
    STAMP(71);
    {
      float4* const accp = g_acc + ((size_t)(qt * 2 + cw) * 72 * 4 + (w8 & 3)) * 32 + lane;
      int g6 = 0, par = 0;
#pragma unroll 1
      for (int i = 0; i < 4; i++) {
        mbar_wait(sBar + B_FULLO + i * 8, 0);
        wgmma_fence();
        const uint64_t da = dA_k + ((i < 3 ? SM_STASH + i * 32768 : 65536) >> 4), db = dB_n8 + ((i * 16384) >> 4);
#pragma unroll
        for (int kk = 0; kk < 8; kk++) wgmma64_ss<1>(S, da + (kk >> 2) * 1024 + (kk & 3) * 2, db + kk * 128, (i | kk) != 0);
        wgmma_commit();
        wgmma_wait<1>();
        if (i > 0) release1(B_EMPTYO + (i - 1) * 8);
      }
      wgmma_wait<0>();
      release1(B_EMPTYO + 24);
      int prevg = 3;
      g6 = 4;
      auto chunk = [&](float (&acc)[64], float (&prev)[64], float4* pp, bool prev_full) {
#pragma unroll
        for (int kc = 0; kc < 8; kc++) {
          mbar_wait(sBar + B_FULLO + g6 * 8, par);
          wgmma_fence();
          const uint64_t da = dA_k + (((kc < 6 ? SM_STASH + (kc >> 1) * 32768 : 65536) + (kc & 1) * 16384) >> 4);
          const uint64_t db = dB_n8 + (uint32_t)((g6 + (g6 >> 2) * 2) * 1024);
#pragma unroll
          for (int kk = 0; kk < 4; kk++) wgmma128_ss<1>(acc, da + kk * 2, db + kk * 128, (kc | kk) != 0);
          wgmma_commit();
          if (kc < 4 || prev_full) {
            red_add_v4(pp + (2 * kc) * 128, prev[kc * 8], prev[kc * 8 + 1], prev[kc * 8 + 2], prev[kc * 8 + 3]);
            red_add_v4(pp + (2 * kc + 1) * 128, prev[kc * 8 + 4], prev[kc * 8 + 5], prev[kc * 8 + 6], prev[kc * 8 + 7]);
          }
          if (kc > 0) {
            wgmma_wait<1>();
            release1(B_EMPTYO + prevg * 8);
          }
          prevg = g6;
          if (++g6 == 6) { g6 = 0; par ^= 1; }
        }
        wgmma_wait<0>();
        release1(B_EMPTYO + prevg * 8);
      };
#pragma unroll 1
      for (int cp = 0; cp < 2; cp++) {
        chunk(O, S, accp + (cp ? 16 : 64) * 128, cp != 0);
        chunk(S, O, accp + cp * 32 * 128, true);
      }
      STAMP(72);
#pragma unroll
      for (int jb = 0; jb < 16; jb++) red_add_v4(accp + (48 + jb) * 128, S[jb * 4], S[jb * 4 + 1], S[jb * 4 + 2], S[jb * 4 + 3]);
    }
    bar_sync(5, 256);
    if (ct == 0) cnt_arrive(C_Q + qt);
    STAMP(73);
    {
      const int rowA = qt * 128 + hg * 16 + w8;
      const size_t oA = (size_t)rowA * (DM / 2) + lane, oB = oA + 8 * (DM / 2);
      uint32_t xa[9], xb[9], wr[9];
      uint4 md[9];
#pragma unroll
      for (int i = 0; i < 9; i++) {
        xa[i] = __ldg(reinterpret_cast<const uint32_t*>(prm.x) + oA + i * 32);
        xb[i] = __ldg(reinterpret_cast<const uint32_t*>(prm.x) + oB + i * 32);
        wr[i] = __ldg(reinterpret_cast<const uint32_t*>(prm.w_r) + lane + i * 32);
        md[i] = __ldcg(g_mod2 + lane + i * 32);
      }
      cnt_wait(C_Q + qt, 8);
      __syncwarp();
      STAMP(74);
      const float4* ap = g_acc + ((size_t)(qt * 2 + (hg >> 2)) * 72 * 4 + (hg & 3)) * 32 + g * 128 + w8 * 4 + t4;
      float4 av[9];
#pragma unroll
      for (int i = 0; i < 9; i++) av[i] = __ldcg(ap + i * 1024);
      if (FFN_GO == 74) if (ct == 0) asm volatile("mbarrier.arrive.shared::cta.b64 _, [%0];" ::"r"(sBar + B_X) : "memory");
      float sA = 0.f, sB = 0.f;
#pragma unroll
      for (int i = 0; i < 9; i++) {
        xa[i] = hadd2(xa[i], hmul2(md[i].x, pack_bf16(av[i].x, av[i].y)));
        xb[i] = hadd2(xb[i], hmul2(md[i].x, pack_bf16(av[i].z, av[i].w)));
        g_x2[oA + i * 32] = xa[i]; g_x2[oB + i * 32] = xb[i];
        sA += bf_lo(xa[i]) + bf_hi(xa[i]); sB += bf_lo(xb[i]) + bf_hi(xb[i]);
      }
      const float mA = warp_sum(sA) * (1.f / DM), mB = warp_sum(sB) * (1.f / DM);
      sA = 0.f; sB = 0.f;
#pragma unroll
      for (int i = 0; i < 9; i++) {
        const float d0 = bf_lo(xa[i]) - mA, d1 = bf_hi(xa[i]) - mA, d2 = bf_lo(xb[i]) - mB, d3 = bf_hi(xb[i]) - mB;
        sA += d0 * d0 + d1 * d1; sB += d2 * d2 + d3 * d3;
      }
      const float rA = rcp(bfr(sqrt_a(bfr(bfr(warp_sum(sA) * (1.f / DM)) + 1e-5f))));
      const float rB = rcp(bfr(sqrt_a(bfr(bfr(warp_sum(sB) * (1.f / DM)) + 1e-5f))));
      const uint32_t nmA = pack_bf16(-mA, -mA), nmB = pack_bf16(-mB, -mB);
      sA = 0.f; sB = 0.f;
      uint32_t ha[9], hb[9];
#pragma unroll
      for (int i = 0; i < 9; i++) {
        const uint32_t da = hadd2(xa[i], nmA), db = hadd2(xb[i], nmB);
        ha[i] = hadd2(hmul2(pack_bf16(bf_lo(da) * rA, bf_hi(da) * rA), md[i].z), md[i].y);
        hb[i] = hadd2(hmul2(pack_bf16(bf_lo(db) * rB, bf_hi(db) * rB), md[i].z), md[i].y);
        g_h2[oA + i * 32] = ha[i]; g_h2[oB + i * 32] = hb[i];
        const float w0 = bf_lo(wr[i]), w1 = bf_hi(wr[i]);
        sA += bf_lo(ha[i]) * w0 + bf_hi(ha[i]) * w1; sB += bf_lo(hb[i]) * w0 + bf_hi(hb[i]) * w1;
      }
      const uint32_t rr = pack_bf16(warp_sum(sA), warp_sum(sB));
      uint32_t u = ((lane & 1) ? rr : rr << 16) & 0xffff0000u;
      u = ((u & 0x7fff0000u) > 0x7f800000u) ? 0u : (u ^ ((u >> 31) ? 0xffff0000u : 0x80000000u));
      u |= 0xffffu - (rowA + (lane & 1) * 8);
      __syncwarp();
      if (lane < 2) asm volatile("st.release.gpu.global.u32 [%0], %1;" ::"l"(reinterpret_cast<uint32_t*>(g_key) + b * 16 + w8 * 2 + lane), "r"(u) : "memory");
#pragma unroll
      for (int i = 0; i < 9; i++) {
        reinterpret_cast<uint32_t*>(prm.out)[oA + i * 32] = hadd2(xa[i], hmul2(md[i].w, ha[i]));
        reinterpret_cast<uint32_t*>(prm.out)[oB + i * 32] = hadd2(xb[i], hmul2(md[i].w, hb[i]));
      }
    }
    if (FFN_GO == 75) if (ct == 0) asm volatile("mbarrier.arrive.shared::cta.b64 _, [%0];" ::"r"(sBar + B_X) : "memory");
    STAMP(75);
    uint32_t* const tsu = reinterpret_cast<uint32_t*>(smem_raw + SM_T);
    float* const tsf = reinterpret_cast<float*>(smem_raw + SM_T);
    uint32_t k1, k2;
    {
      const uint4 a = poll4(g_key + ct), c = poll4(g_key + 256 + ct);
      asm volatile("fence.acq_rel.gpu;" ::: "memory");
      auto merge = [](uint32_t& m1, uint32_t& m2, uint32_t n1, uint32_t n2) { m2 = max(min(m1, n1), max(m2, n2)); m1 = max(m1, n1); };
      k1 = max(a.x, a.y); k2 = min(a.x, a.y);
      merge(k1, k2, max(a.z, a.w), min(a.z, a.w));
      merge(k1, k2, max(c.x, c.y), min(c.x, c.y));
      merge(k1, k2, max(c.z, c.w), min(c.z, c.w));
      uint32_t m1 = __reduce_max_sync(~0u, k1);
      uint32_t m2 = __reduce_max_sync(~0u, k1 == m1 ? k2 : k1);
      if (lane == 0) { tsu[w8 * 2] = m1; tsu[w8 * 2 + 1] = m2; }
      bar_sync(5, 256);
      const uint32_t v = tsu[lane & 15];
      k1 = __reduce_max_sync(~0u, v);
      k2 = __reduce_max_sync(~0u, v == k1 ? 0u : v);
    }
    STAMP(76);
    const int row1 = (0xffff - (k1 & 0xffff)) & (SQ - 1), row2 = (0xffff - (k2 & 0xffff)) & (SQ - 1);
    {
      const int kq = w8 >> 1;
      uint32_t af[18];
      const uint32_t* hp = g_h2 + (size_t)(g ? row2 : row1) * (DM / 2) + kq * 72 + t4;
#pragma unroll
      for (int i = 0; i < 18; i++) af[i] = g < 2 ? __ldcg(hp + i * 4) : 0u;
      float c[5][4];
#pragma unroll
      for (int i = 0; i < 5; i++) c[i][0] = c[i][1] = c[i][2] = c[i][3] = 0.f;
      mbar_wait(sBar + B_FFN, 0);
      STAMP(77);
      const uint32_t wa = sb + ((w8 & 1) ? SM_WU : SM_WG) + (kq * 144 + (lane & 15)) * 80 + (lane >> 4) * 16;
#pragma unroll
      for (int ks = 0; ks < 9; ks++) {
        uint32_t b0[4], b1[4], b2[2];
        ldsm4t(b0, wa + ks * 1280); ldsm4t(b1, wa + ks * 1280 + 32); ldsm2t(b2, wa + ks * 1280 + 64 - (lane >> 4) * 16);
        mma16816(c[0], af[2 * ks], 0u, af[2 * ks + 1], 0u, b0[0], b0[1]);
        mma16816(c[1], af[2 * ks], 0u, af[2 * ks + 1], 0u, b0[2], b0[3]);
        mma16816(c[2], af[2 * ks], 0u, af[2 * ks + 1], 0u, b1[0], b1[1]);
        mma16816(c[3], af[2 * ks], 0u, af[2 * ks + 1], 0u, b1[2], b1[3]);
        mma16816(c[4], af[2 * ks], 0u, af[2 * ks + 1], 0u, b2[0], b2[1]);
      }
      float* const part = tsf + 64;
      if (g < 2) {
#pragma unroll
        for (int i = 0; i < 5; i++) *reinterpret_cast<float2*>(part + w8 * 80 + g * 40 + i * 8 + t4 * 2) = make_float2(c[i][0], c[i][1]);
      }
      bar_sync(5, 256);
      bf16* const act = reinterpret_cast<bf16*>(tsf + 768);
      if (ct < 96) {
        const int tok = ct >= 48, f = ct - tok * 48;
        float v = 0.f;
        if (f < 36) {
          const float* pp = part + tok * 40 + f + (b & 1) * 4;
          const float gs = (pp[0] + pp[160]) + (pp[320] + pp[480]), us = (pp[80] + pp[240]) + (pp[400] + pp[560]);
          v = silu_bf(bfr(gs)) * bfr(us);
        }
        act[ct] = __float2bfloat16(v);
      }
      bar_sync(5, 256);
      uint32_t a6[6];
#pragma unroll
      for (int i = 0; i < 6; i++) a6[i] = g < 2 ? reinterpret_cast<const uint32_t*>(act)[g * 24 + i * 4 + t4] : 0u;
#pragma unroll 3
      for (int i = 0; i < 9; i++) {
        const int nt = w8 * 9 + i;
        const uint32_t a = sb + SM_WD + (nt >> 3) * 6144 + lane * 128 + (((nt ^ lane) & 7) << 4);
        uint32_t b0[4], b2[2];
        ldsm4t(b0, a); ldsm2t(b2, a + 4096 - (lane >> 4) * 2048);
        float y[4] = {0.f, 0.f, 0.f, 0.f};
        mma16816(y, a6[0], 0u, a6[1], 0u, b0[0], b0[1]);
        mma16816(y, a6[2], 0u, a6[3], 0u, b0[2], b0[3]);
        mma16816(y, a6[4], 0u, a6[5], 0u, b2[0], b2[1]);
        if (g < 2) asm volatile("red.global.add.v2.f32 [%0], {%1,%2};" ::"l"(g_y + g * DM + nt * 8 + t4 * 2), "f"(y[0]), "f"(y[1]) : "memory");
      }
    }
    bar_sync(5, 256);
    STAMP(78);
    if (ct == 0) tsu[32] = cnt_arrive(C_Y);
    bar_sync(5, 256);
    if (tsu[32] == 127) {
#pragma unroll 1
      for (int i = ct; i < DM; i += 256) {
        const int tok = i >= DM / 2, cp = i - tok * (DM / 2);
        const uint32_t key = tok ? k2 : k1;
        const float r = __uint_as_float((key & 0xffff0000u) ^ ((key >> 31) ? 0x80000000u : 0xffff0000u));
        const float sg = rcp(1.f + __expf(-r));
        const size_t o = (size_t)(tok ? row2 : row1) * (DM / 2) + cp;
        const float2 ys = __ldcg(reinterpret_cast<const float2*>(g_y) + i);
        const uint32_t hb = hadd2(__ldcg(g_h2 + o), hmul2(pack_bf16(ys.x, ys.y), pack_bf16(sg, sg)));
        reinterpret_cast<uint32_t*>(prm.out)[o] = hadd2(__ldcg(g_x2 + o), hmul2(__ldcg(g_mod2 + cp).w, hb));
      }
      const uint4 z = make_uint4(0, 0, 0, 0);
      g_key[ct] = z; g_key[256 + ct] = z;
      if (ct < 144) g_mod1[ct] = z;
      if (ct < 24) g_cnt[ct * 32] = 0;
    }
    STAMP(79); GSTAMP(91);
  }
}

typedef CUresult (*PFN_enc)(CUtensorMap*, CUtensorMapDataType, cuuint32_t, void*, const cuuint64_t*, const cuuint64_t*,
                            const cuuint32_t*, const cuuint32_t*, CUtensorMapInterleave, CUtensorMapSwizzle,
                            CUtensorMapL2promotion, CUtensorMapFloatOOBfill);
static PFN_enc g_enc = nullptr;
static CUtensorMap mk_map(const void* p, uint64_t cols, uint64_t rows, uint32_t bc, uint32_t br, bool swz = true) {
  CUtensorMap m;
  cuuint64_t dims[2] = {cols, rows};
  cuuint64_t strides[1] = {cols * 2};
  cuuint32_t box[2] = {bc, br}, es[2] = {1, 1};
  g_enc(&m, CU_TENSOR_MAP_DATA_TYPE_BFLOAT16, 2, const_cast<void*>(p), dims, strides, box, es, CU_TENSOR_MAP_INTERLEAVE_NONE,
        swz ? CU_TENSOR_MAP_SWIZZLE_128B : CU_TENSOR_MAP_SWIZZLE_NONE, swz ? CU_TENSOR_MAP_L2_PROMOTION_L2_128B : CU_TENSOR_MAP_L2_PROMOTION_NONE,
        CU_TENSOR_MAP_FLOAT_OOB_FILL_NONE);
  return m;
}

extern "C" void kernel_launch(void* const* d_in, const int* in_sizes, int n_in, void* d_out, int out_size) {
  if (!g_enc) {
    cudaDriverEntryPointQueryResult st;
    cudaGetDriverEntryPoint("cuTensorMapEncodeTiled", (void**)&g_enc, cudaEnableDefault, &st);
    cudaFuncSetAttribute(k_mega, cudaFuncAttributeMaxDynamicSharedMemorySize, SM_TOTAL);
  }
  CUtensorMap mX = mk_map(d_in[0], DM, SQ, 64, 128);
  CUtensorMap mWq = mk_map(d_in[3], HQ * DH, DM, 64, 64);
  CUtensorMap mK = mk_map(d_in[1], DH, HKV * SK, 64, 128);
  CUtensorMap mV = mk_map(d_in[2], DH, HKV * SK, 64, 128);
  CUtensorMap mWo = mk_map(d_in[4], DM, HQ * DH, 64, 64);
  CUtensorMap mWg = mk_map(d_in[7], FF, DM, 40, 192, false);
  CUtensorMap mWu = mk_map(d_in[8], FF, DM, 40, 192, false);
  CUtensorMap mWd = mk_map(d_in[9], DM, FF, 64, 48);
  Params prm;
  prm.x = (const bf16*)d_in[0]; prm.k = (const bf16*)d_in[1]; prm.v = (const bf16*)d_in[2]; prm.wo = (const bf16*)d_in[4]; prm.wq = (const bf16*)d_in[3];
  prm.w_r = (const bf16*)d_in[6]; prm.c = (const bf16*)d_in[10]; prm.w_mod = (const bf16*)d_in[11];
  prm.out = (bf16*)d_out;
  cudaLaunchConfig_t cfg = {};
  cfg.gridDim = dim3(128); cfg.blockDim = dim3(384); cfg.dynamicSmemBytes = SM_TOTAL; cfg.stream = cudaStreamPerThread;
  cudaLaunchAttribute at[1];
  at[0].id = cudaLaunchAttributeClusterDimension;
  at[0].val.clusterDim.x = 2; at[0].val.clusterDim.y = 1; at[0].val.clusterDim.z = 1;
  cfg.attrs = at; cfg.numAttrs = 1;
  cudaLaunchKernelEx(&cfg, k_mega, mX, mWq, mK, mV, mWo, mWg, mWu, mWd, prm);
}
```

```cpp
#include <cuda_runtime.h>
#include <cuda_bf16.h>
#include <cuda.h>
#include <stdint.h>

typedef __nv_bfloat16 bf16;

constexpr int SQ = 2048, DM = 576, HQ = 32, HKV = 16, SK = 2048, DH = 128, FF = 4608;

#define XPF 0
#define WQPF0 0
#define WQPF1 0xff
#define FFNQ 8
#define WQPF2 0
#define QTH 7
#define MPF 1
#define KV0 16
#define KVS 2
#define LAZY_LIMIT 1.0995116e12f
__device__ uint4 g_mod1[8 * 144];
__device__ uint4 g_mod2[288];
__device__ uint4 g_q[128 * 4 * 8 * 256];
__device__ float4 g_acc[16 * 2 * 72 * 4 * 32];
__device__ __align__(16) float g_y[2 * DM];
__device__ uint4 g_key[512];
__device__ uint32_t g_h2[SQ * DM / 2], g_x2[SQ * DM / 2];
__device__ unsigned int g_cnt[32 * 32];
__device__ unsigned int g_err;
#define HAS_ERR
enum { C_SIDE = 1, C_Y = 3, C_Q = 8 };

#define STAMP(i)
#define GSTAMP(i)
#define SETERR(v)
#define PSTAMP(t, i)

__device__ __forceinline__ uint32_t smem_u32(const void* p) { return (uint32_t)__cvta_generic_to_shared(p); }
__device__ __forceinline__ void mbar_init(uint32_t a, uint32_t cnt) { asm volatile("mbarrier.init.shared::cta.b64 [%0], %1;" ::"r"(a), "r"(cnt)); }
__device__ __forceinline__ void mbar_expect_tx(uint32_t a, uint32_t bytes) { asm volatile("mbarrier.arrive.expect_tx.shared::cta.b64 _, [%0], %1;" ::"r"(a), "r"(bytes) : "memory"); }
__device__ __forceinline__ void mbar_arrive_cl(uint32_t a_cluster) { asm volatile("mbarrier.arrive.shared::cluster.b64 _, [%0];" ::"r"(a_cluster) : "memory"); }
__device__ __forceinline__ void mbar_wait(uint32_t a, uint32_t parity) {
  asm volatile(
      "{\n.reg .pred p;\n.reg .u32 n;\nmov.u32 n, 0;\n"
      "WAIT_LOOP:\n"
      "mbarrier.try_wait.parity.shared::cta.b64 p, [%0], %1;\n"
      "@p bra WAIT_DONE;\n"
      "add.u32 n, n, 1;\n"
      "setp.lt.u32 p, n, 65536;\n"
      "@p bra WAIT_LOOP;\n"
      "WAIT_DONE:\n}\n" ::"r"(a), "r"(parity), "l"(&g_err) : "memory");
}
__device__ __forceinline__ unsigned ld_acquire(const unsigned* p) {
  unsigned v;
  asm volatile("ld.acquire.gpu.global.u32 %0, [%1];" : "=r"(v) : "l"(p) : "memory");
  return v;
}
__device__ __forceinline__ void cnt_wait(int idx, unsigned target) {
  uint32_t n = 0;
  while (ld_acquire(&g_cnt[idx * 32]) < target) {
    if (++n > (1u << 15)) { SETERR(2); break; }
  }
}
__device__ __forceinline__ unsigned cnt_arrive(int idx) {
  unsigned old;
  asm volatile("atom.add.acq_rel.gpu.global.u32 %0, [%1], 1;" : "=r"(old) : "l"(&g_cnt[idx * 32]) : "memory");
  return old;
}
__device__ __forceinline__ uint4 poll4(const uint4* p) {
  uint4 v;
  uint32_t n = 0;
  while (true) {
    asm volatile("ld.relaxed.gpu.global.v4.u32 {%0,%1,%2,%3}, [%4];" : "=r"(v.x), "=r"(v.y), "=r"(v.z), "=r"(v.w) : "l"(p) : "memory");
    if (v.x && v.y && v.z && v.w) break;
    if (++n > (1u << 15)) { SETERR(4); break; }
  }
  return v;
}
__device__ __forceinline__ void poll8(const uint4* p, const uint4* q, uint4& v, uint4& w) {
  uint32_t n = 0;
  while (true) {
    asm volatile("ld.relaxed.gpu.global.v4.u32 {%0,%1,%2,%3}, [%4];" : "=r"(v.x), "=r"(v.y), "=r"(v.z), "=r"(v.w) : "l"(p) : "memory");
    asm volatile("ld.relaxed.gpu.global.v4.u32 {%0,%1,%2,%3}, [%4];" : "=r"(w.x), "=r"(w.y), "=r"(w.z), "=r"(w.w) : "l"(q) : "memory");
    if (v.x && v.y && v.z && v.w && w.x && w.y && w.z && w.w) break;
    if (++n > (1u << 15)) { SETERR(4); break; }
  }
}
__device__ __forceinline__ uint32_t hmul2(uint32_t a, uint32_t b) { uint32_t r; asm("mul.rn.bf16x2 %0, %1, %2;" : "=r"(r) : "r"(a), "r"(b)); return r; }
__device__ __forceinline__ uint32_t hadd2(uint32_t a, uint32_t b) { uint32_t r; asm("add.rn.bf16x2 %0, %1, %2;" : "=r"(r) : "r"(a), "r"(b)); return r; }
__device__ __forceinline__ uint32_t hfma2(uint32_t a, uint32_t b, uint32_t c) { uint32_t r; asm("fma.rn.bf16x2 %0, %1, %2, %3;" : "=r"(r) : "r"(a), "r"(b), "r"(c)); return r; }
__device__ __forceinline__ void mma16816(float (&c)[4], uint32_t a0, uint32_t a1, uint32_t a2, uint32_t a3, uint32_t b0, uint32_t b1) {
  asm volatile("mma.sync.aligned.m16n8k16.row.col.f32.bf16.bf16.f32 {%0,%1,%2,%3}, {%4,%5,%6,%7}, {%8,%9}, {%0,%1,%2,%3};"
               : "+f"(c[0]), "+f"(c[1]), "+f"(c[2]), "+f"(c[3]) : "r"(a0), "r"(a1), "r"(a2), "r"(a3), "r"(b0), "r"(b1));
}
__device__ __forceinline__ void mma1688(float (&c)[4], uint32_t a0, uint32_t a1, uint32_t b0) {
  asm volatile("mma.sync.aligned.m16n8k8.row.col.f32.bf16.bf16.f32 {%0,%1,%2,%3}, {%4,%5}, {%6}, {%0,%1,%2,%3};"
               : "+f"(c[0]), "+f"(c[1]), "+f"(c[2]), "+f"(c[3]) : "r"(a0), "r"(a1), "r"(b0));
}
__device__ __forceinline__ void ldsm4t(uint32_t (&r)[4], uint32_t a) {
  asm volatile("ldmatrix.sync.aligned.m8n8.x4.trans.shared.b16 {%0,%1,%2,%3}, [%4];" : "=r"(r[0]), "=r"(r[1]), "=r"(r[2]), "=r"(r[3]) : "r"(a) : "memory");
}
__device__ __forceinline__ void ldsm4(uint32_t (&r)[4], uint32_t a) {
  asm volatile("ldmatrix.sync.aligned.m8n8.x4.shared.b16 {%0,%1,%2,%3}, [%4];" : "=r"(r[0]), "=r"(r[1]), "=r"(r[2]), "=r"(r[3]) : "r"(a) : "memory");
}
__device__ __forceinline__ void ldsm2t(uint32_t (&r)[2], uint32_t a) {
  asm volatile("ldmatrix.sync.aligned.m8n8.x2.trans.shared.b16 {%0,%1}, [%2];" : "=r"(r[0]), "=r"(r[1]) : "r"(a) : "memory");
}
__device__ __forceinline__ float warp_sum(float v) {
#pragma unroll
  for (int o = 16; o; o >>= 1) v += __shfl_xor_sync(~0u, v, o);
  return v;
}
__device__ __forceinline__ void tma_load_2d(uint32_t dst, const CUtensorMap* map, uint32_t mbar, int c0, int c1) {
  asm volatile("cp.async.bulk.tensor.2d.shared::cluster.global.mbarrier::complete_tx::bytes [%0], [%1, {%3, %4}], [%2];"
               ::"r"(dst), "l"(map), "r"(mbar), "r"(c0), "r"(c1) : "memory");
}
__device__ __forceinline__ void tma_load_2d_mc(uint32_t dst, const CUtensorMap* map, uint32_t mbar, int c0, int c1) {
  asm volatile("cp.async.bulk.tensor.2d.shared::cluster.global.mbarrier::complete_tx::bytes.multicast::cluster [%0], [%1, {%3, %4}], [%2], %5;"
               ::"r"(dst), "l"(map), "r"(mbar), "r"(c0), "r"(c1), "h"((uint16_t)3) : "memory");
}
__device__ __forceinline__ void tma_prefetch_2d(const CUtensorMap* map, int c0, int c1) {
  asm volatile("cp.async.bulk.prefetch.tensor.2d.L2.global.tile [%0, {%1, %2}];" ::"l"(map), "r"(c0), "r"(c1) : "memory");
}
__device__ __forceinline__ void bulk_prefetch(const void* p, uint32_t bytes) {
  asm volatile("cp.async.bulk.prefetch.L2.global [%0], %1;" ::"l"(p), "r"(bytes) : "memory");
}
__device__ __forceinline__ void bulk_load(uint32_t dst, const void* src, uint32_t bytes, uint32_t mbar) {
  asm volatile("cp.async.bulk.shared::cluster.global.mbarrier::complete_tx::bytes [%0], [%1], %2, [%3];"
               ::"r"(dst), "l"(src), "r"(bytes), "r"(mbar) : "memory");
}
__device__ __forceinline__ void wgmma_fence() { asm volatile("wgmma.fence.sync.aligned;" ::: "memory"); }
__device__ __forceinline__ void wgmma_commit() { asm volatile("wgmma.commit_group.sync.aligned;" ::: "memory"); }
template <int N> __device__ __forceinline__ void wgmma_wait() { asm volatile("wgmma.wait_group.sync.aligned %0;" ::"n"(N) : "memory"); }
__device__ __forceinline__ void fence_async() { asm volatile("fence.proxy.async.shared::cta;" ::: "memory"); }
__device__ __forceinline__ void bar_sync(int id, int n) { asm volatile("bar.sync %0, %1;" ::"r"(id), "r"(n) : "memory"); }
__device__ __forceinline__ void bar_arrive(int id, int n) { asm volatile("bar.arrive %0, %1;" ::"r"(id), "r"(n) : "memory"); }

constexpr uint32_t SM_BASE = 1024;
__host__ __device__ constexpr uint32_t mk_desc(uint32_t addr, uint32_t lbo_bytes) { return ((addr & 0x3FFFF) >> 4) | ((lbo_bytes >> 4) << 16); }

#define R32(d) \
  "+f"(d[0]), "+f"(d[1]), "+f"(d[2]), "+f"(d[3]), "+f"(d[4]), "+f"(d[5]), "+f"(d[6]), "+f"(d[7]), \
  "+f"(d[8]), "+f"(d[9]), "+f"(d[10]), "+f"(d[11]), "+f"(d[12]), "+f"(d[13]), "+f"(d[14]), "+f"(d[15]), \
  "+f"(d[16]), "+f"(d[17]), "+f"(d[18]), "+f"(d[19]), "+f"(d[20]), "+f"(d[21]), "+f"(d[22]), "+f"(d[23]), \
  "+f"(d[24]), "+f"(d[25]), "+f"(d[26]), "+f"(d[27]), "+f"(d[28]), "+f"(d[29]), "+f"(d[30]), "+f"(d[31])
#define R64(d) R32(d), \
  "+f"(d[32]), "+f"(d[33]), "+f"(d[34]), "+f"(d[35]), "+f"(d[36]), "+f"(d[37]), "+f"(d[38]), "+f"(d[39]), \
  "+f"(d[40]), "+f"(d[41]), "+f"(d[42]), "+f"(d[43]), "+f"(d[44]), "+f"(d[45]), "+f"(d[46]), "+f"(d[47]), \
  "+f"(d[48]), "+f"(d[49]), "+f"(d[50]), "+f"(d[51]), "+f"(d[52]), "+f"(d[53]), "+f"(d[54]), "+f"(d[55]), \
  "+f"(d[56]), "+f"(d[57]), "+f"(d[58]), "+f"(d[59]), "+f"(d[60]), "+f"(d[61]), "+f"(d[62]), "+f"(d[63])
#define S32 \
  "{%0,%1,%2,%3,%4,%5,%6,%7,%8,%9,%10,%11,%12,%13,%14,%15,%16,%17,%18,%19,%20,%21,%22,%23,%24,%25,%26,%27,%28,%29,%30,%31}"
#define S64 \
  "{%0,%1,%2,%3,%4,%5,%6,%7,%8,%9,%10,%11,%12,%13,%14,%15,%16,%17,%18,%19,%20,%21,%22,%23,%24,%25,%26,%27,%28,%29,%30,%31," \
  "%32,%33,%34,%35,%36,%37,%38,%39,%40,%41,%42,%43,%44,%45,%46,%47,%48,%49,%50,%51,%52,%53,%54,%55,%56,%57,%58,%59,%60,%61,%62,%63}"

template <int TB>
__device__ __forceinline__ void wgmma128_rs(float (&d)[64], uint32_t a0, uint32_t a1, uint32_t a2, uint32_t a3, uint32_t db, int scale_d) {
  asm volatile("{\n.reg .pred p;\n.reg .b64 q;\nsetp.ne.b32 p, %69, 0;\nmov.b64 q, {%68, 0x40000040};\n"
               "wgmma.mma_async.sync.aligned.m64n128k16.f32.bf16.bf16 " S64 ", {%64,%65,%66,%67}, q, p, 1, 1, %70;\n}\n"
               : R64(d) : "r"(a0), "r"(a1), "r"(a2), "r"(a3), "r"(db), "r"(scale_d), "n"(TB));
}
__device__ __forceinline__ void wgmma64_rs(float (&d)[32], uint32_t a0, uint32_t a1, uint32_t a2, uint32_t a3, uint32_t db, int scale_d) {
  asm volatile("{\n.reg .pred p;\n.reg .b64 q;\nsetp.ne.b32 p, %37, 0;\nmov.b64 q, {%36, 0x40000040};\n"
               "wgmma.mma_async.sync.aligned.m64n64k16.f32.bf16.bf16 " S32 ", {%32,%33,%34,%35}, q, p, 1, 1, 1;\n}\n"
               : R32(d) : "r"(a0), "r"(a1), "r"(a2), "r"(a3), "r"(db), "r"(scale_d));
}
__device__ __forceinline__ uint32_t pack_bf16(float a, float b) {
  uint32_t r;
  asm("cvt.rn.bf16x2.f32 %0, %1, %2;" : "=r"(r) : "f"(b), "f"(a));
  return r;
}
__device__ __forceinline__ float ex2(float x) { float y; asm("ex2.approx.ftz.f32 %0, %1;" : "=f"(y) : "f"(x)); return y; }
__device__ __forceinline__ float bfr(float x) { return __bfloat162float(__float2bfloat16(x)); }
__device__ __forceinline__ float bf_lo(uint32_t u) { return __uint_as_float(u << 16); }
__device__ __forceinline__ float bf_hi(uint32_t u) { return __uint_as_float(u & 0xffff0000u); }
__device__ __forceinline__ uint4 lds128(uint32_t a) {
  uint4 v;
  asm volatile("ld.shared.v4.b32 {%0,%1,%2,%3}, [%4];" : "=r"(v.x), "=r"(v.y), "=r"(v.z), "=r"(v.w) : "r"(a) : "memory");
  return v;
}
__device__ __forceinline__ void sts128(uint32_t a, uint4 v) {
  asm volatile("st.shared.v4.b32 [%0], {%1,%2,%3,%4};" ::"r"(a), "r"(v.x), "r"(v.y), "r"(v.z), "r"(v.w) : "memory");
}
__device__ __forceinline__ void red_add_v4(float4* p, float a, float b, float c, float d) {
  asm volatile("red.global.add.v4.f32 [%0], {%1,%2,%3,%4};" ::"l"(p), "f"(a), "f"(b), "f"(c), "f"(d) : "memory");
}
__device__ __forceinline__ float rcp(float x) { float y; asm("rcp.approx.ftz.f32 %0, %1;" : "=f"(y) : "f"(x)); return y; }
__device__ __forceinline__ float sqrt_a(float x) { float y; asm("sqrt.approx.ftz.f32 %0, %1;" : "=f"(y) : "f"(x)); return y; }
__device__ __forceinline__ float silu_bf(float v) { return bfr(v * rcp(1.f + __expf(-v))); }

constexpr int SM_STASH = 131072;
constexpr int SM_QR = 81920;
constexpr int SM_XCH = 98304;
constexpr int SM_MISC = 229376;
constexpr int SM_TOTAL = 232448;
constexpr int B_FULLQ = 0, B_FULLA = 64, B_FULLO = 96, B_XF = 144, B_X = 272,
              B_EMPTYQ = 280, B_EMPTYO = 344, B_ST = 392,
              B_EMPTYA = 400, B_M = 432, B_FFN = 440;
constexpr int SM_MOD = SM_MISC + 448;
constexpr int SM_RED = SM_MISC + 2752;
constexpr int SM_ZERO = SM_MISC + 3040;
constexpr int SM_WG = 137216, SM_WU = 183296;
constexpr int SM_T = SM_XCH;

struct Params {
  const bf16 *x, *k, *c, *w_mod, *w_r, *wo, *v, *wq, *wg, *wu;
  bf16* out;
};

__global__ void __launch_bounds__(384, 1)
k_mega(const __grid_constant__ CUtensorMap mX, const __grid_constant__ CUtensorMap mWq,
       const __grid_constant__ CUtensorMap mK, const __grid_constant__ CUtensorMap mV,
       const __grid_constant__ CUtensorMap mWo, const __grid_constant__ CUtensorMap mWg,
       const __grid_constant__ CUtensorMap mWu, const __grid_constant__ CUtensorMap mWd, const Params prm) {
  extern __shared__ __align__(1024) uint8_t smem_raw[];
  const uint32_t sb = smem_u32(smem_raw);
  if ((sb & 0x3FFFF) != SM_BASE) __trap();
  const uint32_t sBar = sb + SM_MISC;
  const int tid = threadIdx.x, lane = tid & 31;
  PSTAMP(0, 84);
  const int warp = __shfl_sync(~0u, tid >> 5, 0);
  const int b = blockIdx.x, rank = b & 1, qt = (b >> 1) & 15, kg = b >> 5, hg = kg * 2 + rank;
  const int hcol = (kg * 8 + rank) * DH;
  auto wq_prefetch = [&](int mask) {
    const bf16* wp = prm.wq + (size_t)(qt * 36 + ((tid - 128) >> 3)) * (HQ * DH) + hcol + ((tid & 6) * 2 + (tid & 1)) * 64;
    if ((mask >> (tid & 7)) & 1) {
      asm volatile("prefetch.global.L2 [%0];" ::"l"(wp));
      if (warp == 4) asm volatile("prefetch.global.L2 [%0];" ::"l"(wp + 32 * (HQ * DH)));
    }
  };
  if (warp >= 4) wq_prefetch(WQPF0);
  if (lane == 0 && warp >= 4) {
    if (MPF && warp < 10 && b < 96) bulk_prefetch(prm.w_mod + (size_t)(b * 6 + warp - 4) * (6 * DM), 2 * DM * 2);
    const int c0 = warp < 9 ? 1 : 8, c1 = warp < 11 ? c0 : 16, c2 = warp < 11 ? c0 : 3;
#pragma unroll
    for (int j = 0; j < 7; j++) mbar_init(sBar + (warp - 4) * 56 + j * 8, j == 0 ? c0 : j < 5 ? c1 : c2);
    *reinterpret_cast<uint32_t*>(smem_raw + SM_ZERO) = 0;
    asm volatile("fence.mbarrier_init.release.cluster;" ::: "memory");
  }
  __syncwarp();
  asm volatile("barrier.cluster.arrive.relaxed.aligned;" ::: "memory");
#define CL_WAIT() asm volatile("barrier.cluster.wait.acquire.aligned;" ::: "memory")
  const bool do_mod1 = warp >= 1 && warp < 4 && b < 72;
  if (warp < 4) {
    asm volatile("setmaxnreg.dec.sync.aligned.u32 40;");
    if (warp == 0) {
      PSTAMP(0, 85);
      CL_WAIT();
      PSTAMP(0, 86);
      if (lane == 0) {
        mbar_expect_tx(sBar + B_X, 9 * 16384);
#pragma unroll
        for (int i = 0; i < 5; i++)
          if (i < 4 || rank == 0) tma_load_2d_mc(sb + (2 * i + rank) * 16384, &mX, sBar + B_X, (2 * i + rank) * 64, qt * 128);
      }
    }
    PSTAMP(0, 87);
    if (do_mod1) {
      const int st = tid - 32;
      const uint32_t stg = sb + SM_QR + 7 * 18432 + st * 16;
      {
        const bf16* wp = prm.w_mod + (size_t)(st >> 1) * (6 * DM) + b * 16 + (st & 1) * 8;
#pragma unroll
        for (int i = 0; i < 12; i++)
          asm volatile("cp.async.cg.shared.global [%0], [%1], 16;" ::"r"(stg + i * 1536), "l"(wp + (size_t)i * 48 * (6 * DM)) : "memory");
      }
      float* const sc = reinterpret_cast<float*>(smem_raw + SM_MOD);
#pragma unroll
      for (int i = 0; i < 3; i++) {
        const uint32_t v = __ldg(reinterpret_cast<const uint32_t*>(prm.c) + st + i * 96);
        *reinterpret_cast<float2*>(sc + (st + i * 96) * 2) = make_float2(silu_bf(bf_lo(v)), silu_bf(bf_hi(v)));
      }
      bar_sync(6, 96);
      PSTAMP(32, 88);
      asm volatile("cp.async.wait_all;" ::: "memory");
      PSTAMP(32, 93);
      float a[8];
#pragma unroll
      for (int i = 0; i < 8; i++) a[i] = 0.f;
#pragma unroll 3
      for (int i = 0; i < 12; i++) {
        const float sv = sc[(st >> 1) + 48 * i];
        const uint4 v = lds128(stg + i * 1536);
        a[0] += sv * bf_lo(v.x); a[1] += sv * bf_hi(v.x); a[2] += sv * bf_lo(v.y); a[3] += sv * bf_hi(v.y);
        a[4] += sv * bf_lo(v.z); a[5] += sv * bf_hi(v.z); a[6] += sv * bf_lo(v.w); a[7] += sv * bf_hi(v.w);
      }
      const bool u2 = lane & 2, u4 = lane & 4, u8 = lane & 8;
#pragma unroll
      for (int i = 0; i < 4; i++) { float snd = u2 ? a[i] : a[i + 4]; float kp = u2 ? a[i + 4] : a[i]; a[i] = kp + __shfl_xor_sync(~0u, snd, 2); }
#pragma unroll
      for (int i = 0; i < 2; i++) { float snd = u4 ? a[i] : a[i + 2]; float kp = u4 ? a[i + 2] : a[i]; a[i] = kp + __shfl_xor_sync(~0u, snd, 4); }
      { float snd = u8 ? a[0] : a[1]; float kp = u8 ? a[1] : a[0]; a[0] = kp + __shfl_xor_sync(~0u, snd, 8); }
      a[0] += __shfl_xor_sync(~0u, a[0], 16);
      float* const red = reinterpret_cast<float*>(smem_raw + SM_RED);
      if (lane < 16) red[(warp - 1) * 16 + (lane & 1) * 8 + (u2 ? 4 : 0) + (u4 ? 2 : 0) + (u8 ? 1 : 0)] = a[0];
      PSTAMP(32, 94);
      bar_sync(6, 96);
      PSTAMP(32, 95);
      if (st < 64) {
        const float* rp = red + (lane & 7) * 2;
        const float2 x = *reinterpret_cast<const float2*>(rp), y = *reinterpret_cast<const float2*>(rp + 16), z = *reinterpret_cast<const float2*>(rp + 32);
        uint32_t w = pack_bf16(x.x + y.x + z.x, x.y + y.y + z.y);
        if (b >= 36) w = hadd2(w, 0x3f803f80u);
        asm volatile("st.relaxed.gpu.global.u32 [%0], %1;" ::"l"(reinterpret_cast<uint32_t*>(g_mod1) + (st >> 3) * 576 + b * 8 + (lane & 7)), "r"(~w) : "memory");
      }
    }
    __syncwarp();
    PSTAMP(32, 89);
    if (warp > 0) {
      CL_WAIT();
      fence_async();
      if (tid < 104) {
        uint4 v, w;
        mbar_wait(sBar + B_X, 0);
        poll8(g_mod1 + (b & 7) * 144 + tid - 32, g_mod1 + (b & 7) * 144 + tid + 40, v, w);
        sts128(sb + SM_MOD + (tid - 32) * 32, make_uint4(~v.x, ~w.x, ~v.y, ~w.y));
        sts128(sb + SM_MOD + (tid - 32) * 32 + 16, make_uint4(~v.z, ~w.z, ~v.w, ~w.w));
      }
      __syncwarp();
      PSTAMP(32, 92);
      bar_arrive(3, 224);
      bar_arrive(4, 224);
      if (lane == 0) asm volatile("mbarrier.arrive.shared::cta.b64 _, [%0];" ::"r"(sBar + B_M) : "memory");
    }
    if (tid == 0) {
      auto kv_load = [&](int t) {
        const int s = t & 3;
        mbar_wait(sBar + B_EMPTYA + s * 8, (t >> 2) & 1);
        mbar_expect_tx(sBar + B_FULLA + s * 8, 32768);
        tma_load_2d_mc(sb + s * 32768 + rank * 16384, (t & 1) ? &mV : &mK, sBar + B_FULLA + s * 8, rank * 64, kg * 4 * SK + (t >> 1) * 128);
      };
#pragma unroll 1
      for (int i = 0; i < 32; i++) {
        const int hh = (i >> 2) + 2, g = i & 7;
        if (i == QTH) mbar_wait(sBar + B_M, 0);
        mbar_wait(sBar + B_EMPTYQ + g * 8, (i >> 3) & 1);
        mbar_expect_tx(sBar + B_FULLQ + g * 8, 18432);
        tma_load_2d(sb + SM_QR + g * 18432, &mWq, sBar + B_FULLQ + g * 8, hcol + (hh & 6) * 128 + (hh & 1) * 64, (i & 3) * 144);
        if ((i & ~4) == KV0) kv_load((i >> 2) & 1);
      }
#pragma unroll 1
      for (int u = 2; u < 128; u++) kv_load(u < 5 || u == 127 ? u : (u & 1) ? u + 1 : u - 1);
      mbar_wait(sBar + B_X, 1);
      {
        int ch = kg * 2, g = 0, par = 1;
        mbar_expect_tx(sBar + B_FFN, 9 * 5120);
#pragma unroll 1
        for (int i = 0; i < 39; i++) {
          if (i < 6) mbar_wait(sBar + B_EMPTYA + (g >> 1) * 8, 0);
          else mbar_wait(sBar + B_EMPTYO + g * 8, par);
          if (i < 36) {
            mbar_expect_tx(sBar + B_FULLO + g * 8, 16384);
            tma_load_2d(sb + g * 16384, &mWo, sBar + B_FULLO + g * 8, ch * 64, hcol + (i & 3) * 256);
            if ((i & 3) == 3 && ++ch == 9) ch = 0;
          } else {
#pragma unroll 1
            for (int f = g * 3; f < g * 3 + 3; f++) tma_load_2d(sb + g * 1024 + f * 5120, &mWd, sBar + B_FFN, f * 64, b * 36);
          }
          if (++g == 6) { g = 0; par ^= 1; }
        }
      }
    } else if (warp == 3) {
#pragma unroll 1
      for (int i = 0; i < 32; i++) {
        mbar_wait(sBar + B_FULLQ + (i & 7) * 8, (i >> 3) & 1);
        if ((i & 3) == 3) bar_sync(1, 288);
      }
#pragma unroll 1
      for (int t = 0; t < 128; t++) {
        mbar_wait(sBar + B_FULLA + (t & 3) * 8, (t >> 2) & 1);
        if (!(t & 1) || t == 127) bar_sync(1, 288);
      }
      int g = 0, par = 0;
#pragma unroll 1
      for (int i = 0; i < 36; i++) {
        mbar_wait(sBar + B_FULLO + g * 8, par);
        if (++g == 6) { g = 0; par ^= 1; }
        if (i & 1) bar_sync(1, 288);
      }
      bar_sync(1, 288);
    } else if (warp > 0) {
      const int st = tid - 32;
      mbar_wait(sBar + B_FULLQ, 0);
      mbar_wait(sBar + B_FULLQ, 1);
      const bf16* const kvp = (rank ? prm.v : prm.k) + ((size_t)kg * 4 * SK + qt * 128) * DH;
      if (st == 0) bulk_prefetch(kvp, 32768);
      mbar_wait(sBar + B_FULLA, 0);
      mbar_wait(sBar + B_FULLA, 1);
      float4* z = g_acc + (size_t)b * 2304;
#pragma unroll 4
      for (int i = st; i < 2304; i += 64) z[i] = make_float4(0.f, 0.f, 0.f, 0.f);
      if (b == 127) {
#pragma unroll 1
        for (int i = st; i < 2 * DM; i += 64) g_y[i] = 0.f;
      }
#pragma unroll 1
      for (int grp = b * 2 + warp - 1; grp < 288; grp += 256) {
        float a[8];
#pragma unroll
        for (int i = 0; i < 8; i++) a[i] = 0.f;
#pragma unroll 2
        for (int r = lane; r < DM; r += 32) {
          uint4 v = __ldg(reinterpret_cast<const uint4*>(prm.w_mod + (size_t)r * (6 * DM) + 2 * DM + grp * 8));
          float s = silu_bf(__bfloat162float(prm.c[r]));
          a[0] += s * bf_lo(v.x); a[1] += s * bf_hi(v.x); a[2] += s * bf_lo(v.y); a[3] += s * bf_hi(v.y);
          a[4] += s * bf_lo(v.z); a[5] += s * bf_hi(v.z); a[6] += s * bf_lo(v.w); a[7] += s * bf_hi(v.w);
        }
#pragma unroll
        for (int i = 0; i < 8; i++) a[i] = warp_sum(a[i]);
        if (lane == 0) {
          const int kind = grp / 72, cp = (grp - kind * 72) * 4;
#pragma unroll
          for (int i = 0; i < 4; i++) {
            uint32_t w = pack_bf16(a[2 * i], a[2 * i + 1]);
            if (kind == 2) w = hadd2(w, 0x3f803f80u);
            reinterpret_cast<uint32_t*>(g_mod2)[(cp + i) * 4 + kind] = w;
          }
        }
      }
      __syncwarp();
      if (lane == 0) cnt_arrive(C_SIDE);
      if (tid == 32) {
#pragma unroll 1
        for (int p = 3; p < 22; p++) {
          mbar_wait(sBar + B_FULLA, p & 1);
          if ((p & 7) == 3) bulk_prefetch(kvp + (size_t)((p >> 3) + 1) * SK * DH, 32768);
          if (p == 17) bulk_prefetch(prm.wo + ((size_t)kg * 1024 + (b & 31) * 32) * DM, 32 * DM * 2);
          if (p >= 19) {
            const int i = p - 19;
#pragma unroll 1
            for (int f = i * 192; f < i * 192 + 192; f += 64) {
              tma_prefetch_2d(&mWg, (b * 36) & ~7, f); tma_prefetch_2d(&mWu, (b * 36) & ~7, f); tma_prefetch_2d(&mWd, f, b * 36);
            }
          }
        }
        cnt_wait(C_SIDE, 128 * 2);
        asm volatile("mbarrier.arrive.shared::cta.b64 _, [%0];" ::"r"(sBar + B_X) : "memory");
      }
      __syncwarp();
      mbar_wait(sBar + B_ST, 0);
#pragma unroll 1
      for (int i = st; i < 5760; i += 64) {
        const int m = i >= 2880, c = i - m * 2880, r = c / 5;
        asm volatile("cp.async.cg.shared.global [%0], [%1], 16;" ::"r"(sb + SM_WG + i * 16), "l"((m ? prm.wu : prm.wg) + (size_t)r * FF + ((b * 36) & ~7) + (c - r * 5) * 8) : "memory");
        asm volatile("cp.async.commit_group;\ncp.async.wait_group %0;" ::"n"(FFNQ) : "memory");
      }
      asm volatile("cp.async.wait_all;" ::: "memory");
      __syncwarp();
      if (lane == 0) asm volatile("mbarrier.arrive.shared::cta.b64 _, [%0];" ::"r"(sBar + B_FFN) : "memory");
    }
  } else {
    const int cw = (warp >> 2) - 1;
    const int w8 = warp - 4;
    const int ct = tid - 128;
    const int g = lane >> 2, t4 = lane & 3;
    uint32_t relBar;
    asm volatile("mapa.shared::cluster.u32 %0, %1, %2;" : "=r"(relBar) : "r"(sBar), "r"(rank ^ (lane & 1)));
    auto release = [&](int off) {
      if (lane < 2) mbar_arrive_cl(relBar + off);
    };
    auto release1 = [&](int off) {
      if (lane == 0) mbar_arrive_cl(relBar + off);
    };
    auto turn_begin = [&]() { bar_sync(1 + cw, 288 - cw * 32); wgmma_fence(); };
    auto turn_end = [&]() { bar_arrive(2 - cw, 256 + cw * 32); };
    STAMP(0); GSTAMP(90);
    CL_WAIT();
    asm volatile("setmaxnreg.inc.sync.aligned.u32 232;");
    float S[64], O[64];
    uint32_t P[32], Qf[32];
    constexpr uint32_t dB_k = mk_desc(SM_BASE, 16);
    constexpr uint32_t dB_n16 = mk_desc(SM_BASE, 16384);
    uint4* const qpark = g_q + (size_t)b * (4 * 8 * 256) + ct;
    {
      uint32_t A[144];
      const uint32_t la = sb + (w8 * 16 + (lane & 15)) * 128 + (((lane >> 4) ^ (lane & 7)) << 4);
      mbar_wait(sBar + B_X, 0);
      wq_prefetch(WQPF1);
      STAMP(1);
#pragma unroll
      for (int k = 0; k < 36; k++) {
        uint32_t a[4];
        ldsm4(a, (la ^ ((k & 3) << 5)) + (k >> 2) * 16384);
        A[k * 4] = a[0]; A[k * 4 + 1] = a[1]; A[k * 4 + 2] = a[2]; A[k * 4 + 3] = a[3];
      }
      const uint32_t one = 0x3f803f80u;
      float c[4][4];
#pragma unroll
      for (int i = 0; i < 16; i++) c[i >> 2][i & 3] = 0.f;
#pragma unroll
      for (int k = 0; k < 36; k++) mma16816(c[k & 3], A[k * 4], A[k * 4 + 1], A[k * 4 + 2], A[k * 4 + 3], one, one);
      if (lane < 12) mbar_arrive_cl(lane < 4 ? relBar + B_EMPTYA + (lane >> 1) * 8 : sBar + B_EMPTYQ + (lane - 4) * 8);
      const float mA = ((c[0][0] + c[1][0]) + (c[2][0] + c[3][0])) * (1.f / DM), mB = ((c[0][2] + c[1][2]) + (c[2][2] + c[3][2])) * (1.f / DM);
      if (cw == 1) bar_sync(7, 256);
      uint32_t zero;
      asm volatile("ld.shared.b32 %0, [%1];" : "=r"(zero) : "r"(sb + SM_ZERO) : "memory");
      const uint32_t nA = pack_bf16(-mA, -mA) | zero, nB = pack_bf16(-mB, -mB) | zero;
      const float eA = mA + bf_lo(nA), eB = mB + bf_lo(nB);
#pragma unroll
      for (int i = 0; i < 16; i++) c[i >> 2][i & 3] = 0.f;
#pragma unroll
      for (int k = 0; k < 36; k++) {
        A[k * 4] = hadd2(A[k * 4], nA); A[k * 4 + 1] = hadd2(A[k * 4 + 1], nB); A[k * 4 + 2] = hadd2(A[k * 4 + 2], nA); A[k * 4 + 3] = hadd2(A[k * 4 + 3], nB);
        mma16816(c[k & 3], hmul2(A[k * 4], A[k * 4]), hmul2(A[k * 4 + 1], A[k * 4 + 1]), hmul2(A[k * 4 + 2], A[k * 4 + 2]), hmul2(A[k * 4 + 3], A[k * 4 + 3]), one, one);
      }
      const float vA = (c[0][0] + c[1][0]) + (c[2][0] + c[3][0]), vB = (c[0][2] + c[1][2]) + (c[2][2] + c[3][2]);
      const float rA = rsqrtf(fmaxf(vA * (1.f / DM) - eA * eA, 0.f) + 1e-5f), rB = rsqrtf(fmaxf(vB * (1.f / DM) - eB * eB, 0.f) + 1e-5f);
      const uint32_t hA = pack_bf16(rA, rA), hB = pack_bf16(rB, rB);
      const uint32_t lA = pack_bf16(rA - bf_lo(hA), rA - bf_lo(hA)), lB = pack_bf16(rB - bf_lo(hB), rB - bf_lo(hB));
      const uint32_t oA = pack_bf16(-eA * rA, -eA * rA), oB = pack_bf16(-eB * rB, -eB * rB);
#pragma unroll
      for (int i = 0; i < 144; i++) A[i] = hfma2(A[i], (i & 1) ? hB : hA, hfma2(A[i], (i & 1) ? lB : lA, (i & 1) ? oB : oA));
      asm volatile("st.shared.b32 [%0], %1;" ::"r"(sb + SM_ZERO + 4), "r"(A[143] ^ A[100]) : "memory");
      if (cw == 0) bar_arrive(7, 256);
      STAMP(2);
      bar_sync(3 + cw, 224);
      wq_prefetch(WQPF2);
      STAMP(3);
#pragma unroll
      for (int k = 0; k < 72; k++) {
        const uint2 m = *reinterpret_cast<const uint2*>(smem_raw + SM_MOD + (k * 4 + t4) * 8);
        A[k * 2] = hfma2(A[k * 2], m.y, m.x); A[k * 2 + 1] = hfma2(A[k * 2 + 1], m.y, m.x);
      }
      STAMP(4);
      float qa[32];
      if (cw == 0) bar_arrive(1, 288);
#pragma unroll 1
      for (int hh = 2;; hh++) {
        const int gr = (hh & 1) * 4;
#pragma unroll
        for (int p = 0; p < 4; p++) {
          if (p == 0) turn_begin();
          const uint32_t db = dB_k + (SM_QR >> 4) + (gr + p) * 1152;
#pragma unroll
          for (int kk = 0; kk < 9; kk++)
            wgmma64_rs(qa, A[p * 36 + kk * 4], A[p * 36 + kk * 4 + 1], A[p * 36 + kk * 4 + 2], A[p * 36 + kk * 4 + 3], db + kk * 128, (p | kk) != 0);
        }
        wgmma_commit();
        turn_end();
        wgmma_wait<0>();
        if (lane < 4) mbar_arrive_cl(sBar + B_EMPTYQ + (gr + lane) * 8);
        if (hh == 8 && lane < 4) mbar_arrive_cl(relBar + B_EMPTYA + 16 + (lane >> 1) * 8);
#pragma unroll
        for (int j = 0; j < 4; j++)
          qpark[((hh & 7) * 4 + j) * 256] = make_uint4(pack_bf16(qa[8 * j], qa[8 * j + 1]), pack_bf16(qa[8 * j + 2], qa[8 * j + 3]),
                                                       pack_bf16(qa[8 * j + 4], qa[8 * j + 5]), pack_bf16(qa[8 * j + 6], qa[8 * j + 7]));
        if (hh == 9) break;
      }
#pragma unroll
      for (int j = 0; j < 4; j++) {
        const uint4 v = __ldcg(qpark + j * 256);
        Qf[4 * j] = v.x; Qf[4 * j + 1] = v.y; Qf[4 * j + 2] = v.z; Qf[4 * j + 3] = v.w;
      }
#pragma unroll
      for (int j = 0; j < 16; j++) Qf[16 + j] = pack_bf16(qa[2 * j], qa[2 * j + 1]);
    }
    STAMP(5);
    const float sc = 0.08838834764831845f * 1.4426950408889634f;
    float mb0 = 0.f, mb1 = 0.f, l0 = 0.f, l1 = 0.f;
    float i0, i1;
    auto o_scale = [&]() {
      float a0 = l0, a1 = l1;
      a0 += __shfl_xor_sync(~0u, a0, 1); a0 += __shfl_xor_sync(~0u, a0, 2);
      a1 += __shfl_xor_sync(~0u, a1, 1); a1 += __shfl_xor_sync(~0u, a1, 2);
      i0 = rcp(a0); i1 = rcp(a1);
    };
    auto o_frag = [&](int i) {
      return make_uint4(pack_bf16(O[i * 8] * i0, O[i * 8 + 1] * i0), pack_bf16(O[i * 8 + 2] * i1, O[i * 8 + 3] * i1),
                        pack_bf16(O[i * 8 + 4] * i0, O[i * 8 + 5] * i0), pack_bf16(O[i * 8 + 6] * i1, O[i * 8 + 7] * i1));
    };
    auto row_max = [&](float& x0, float& x1) {
      float y0 = fmaxf(S[0], S[1]), y1 = fmaxf(S[2], S[3]), z0 = fmaxf(S[4], S[5]), z1 = fmaxf(S[6], S[7]);
#pragma unroll
      for (int j = 2; j < 16; j += 2) {
        y0 = fmaxf(y0, fmaxf(S[j * 4], S[j * 4 + 1])); y1 = fmaxf(y1, fmaxf(S[j * 4 + 2], S[j * 4 + 3]));
        z0 = fmaxf(z0, fmaxf(S[j * 4 + 4], S[j * 4 + 5])); z1 = fmaxf(z1, fmaxf(S[j * 4 + 6], S[j * 4 + 7]));
      }
      x0 = fmaxf(y0, z0); x1 = fmaxf(y1, z1);
      x0 = fmaxf(x0, __shfl_xor_sync(~0u, x0, 1)); x1 = fmaxf(x1, __shfl_xor_sync(~0u, x1, 1));
      x0 = fmaxf(x0, __shfl_xor_sync(~0u, x0, 2)); x1 = fmaxf(x1, __shfl_xor_sync(~0u, x1, 2));
    };
    float s0, s1;
    auto exps = [&](int j0, int j1) {
#pragma unroll
      for (int j = j0; j < j1; j++) {
        S[j * 4] = ex2(fmaf(S[j * 4], sc, -mb0)); S[j * 4 + 1] = ex2(fmaf(S[j * 4 + 1], sc, -mb0));
        S[j * 4 + 2] = ex2(fmaf(S[j * 4 + 2], sc, -mb1)); S[j * 4 + 3] = ex2(fmaf(S[j * 4 + 3], sc, -mb1));
        s0 += S[j * 4] + S[j * 4 + 1]; s1 += S[j * 4 + 2] + S[j * 4 + 3];
      }
    };
    auto cvtP = [&]() {
#pragma unroll
      for (int i = 0; i < 32; i++) P[i] = pack_bf16(S[2 * i], S[2 * i + 1]);
    };
    auto issue_qk = [&](int ks) {
      const uint32_t db = dB_k + ((ks * 32768) >> 4);
#pragma unroll
      for (int kk = 0; kk < 8; kk++)
        wgmma128_rs<0>(S, Qf[kk * 4], Qf[kk * 4 + 1], Qf[kk * 4 + 2], Qf[kk * 4 + 3], db + (kk >> 2) * 1024 + (kk & 3) * 2, kk != 0);
    };
    auto issue_pv = [&](int vs, int first) {
      const uint32_t db = dB_n16 + ((vs * 32768) >> 4);
#pragma unroll
      for (int kk = 0; kk < 8; kk++)
        wgmma128_rs<1>(O, P[kk * 4], P[kk * 4 + 1], P[kk * 4 + 2], P[kk * 4 + 3], db + kk * 128, kk ? 1 : !first);
    };
    auto sched_fence = [&]() {
      asm volatile("st.shared.f32 [%0], %1;" ::"r"(sb + SM_RED + lane * 4), "f"(S[31]) : "memory");
    };
#pragma unroll 1
    for (int h = 0; h < 4; h++) {
      {
        STAMP(6 + h * 16);
        turn_begin();
        issue_qk(0);
        wgmma_commit();
        if (h > 0) { issue_pv(3, 0); wgmma_commit(); }
        else asm volatile("wgmma.commit_group.sync.aligned; // empty" ::: "memory");
        turn_end();
        wgmma_wait<1>();
        release(B_EMPTYA);
        s0 = 0.f; s1 = 0.f;
        float x0, x1;
        row_max(x0, x1);
        mb0 = x0 * sc; mb1 = x1 * sc;
        exps(0, 8);
        sched_fence();
        wgmma_wait<0>();
        if (h > 0) {
          release(B_EMPTYA + 24);
          o_scale();
#pragma unroll
          for (int i = 0; i < 8; i++) sts128(sb + SM_STASH + (h - 1) * 32768 + i * 4096 + ct * 16, o_frag(i));
        }
        exps(8, 16);
        cvtP();
        l0 = s0; l1 = s1;
      }
#pragma unroll 1
      for (int j = 1; j < 16; j++) {
        const int ks = (j & 1) * 2, vs = 3 - ks;
        turn_begin();
        issue_qk(ks);
        wgmma_commit();
        issue_pv(vs, j == 1);
        wgmma_commit();
        turn_end();
        wgmma_wait<1>();
        release(B_EMPTYA + ks * 8);
        if (j == 15 && h < 3) {
          const uint4* qp = qpark + (h + 1) * (8 * 256);
#pragma unroll
          for (int i = 0; i < 8; i++) {
            uint4 v = __ldcg(qp + i * 256);
            Qf[4 * i] = v.x; Qf[4 * i + 1] = v.y; Qf[4 * i + 2] = v.z; Qf[4 * i + 3] = v.w;
          }
        }
        s0 = 0.f; s1 = 0.f;
        exps(0, 8);
        sched_fence();
        wgmma_wait<0>();
        release(B_EMPTYA + vs * 8);
        bool bad = __any_sync(~0u, !(s0 <= LAZY_LIMIT && s1 <= LAZY_LIMIT));
        if (__builtin_expect(!bad, 1)) {
          exps(8, 16);
          cvtP();
          bad = __any_sync(~0u, !(s0 <= LAZY_LIMIT && s1 <= LAZY_LIMIT));
        }
        if (__builtin_expect(bad, 0)) {
          const uint32_t* kp = reinterpret_cast<const uint32_t*>(prm.k + ((size_t)(kg * 4 + h) * SK + j * 128 + g) * DH) + t4;
          const uint4* qp = qpark + h * (8 * 256);
          float4 tmp[16];
#pragma unroll 1
          for (int jn = 0; jn < 16; jn++) {
            float c[4] = {0.f, 0.f, 0.f, 0.f};
#pragma unroll 1
            for (int kk = 0; kk < 8; kk++) {
              const uint4 a = __ldcg(qp + kk * 256);
              mma16816(c, a.x, a.y, a.z, a.w, __ldg(kp + jn * 512 + kk * 8), __ldg(kp + jn * 512 + kk * 8 + 4));
            }
            tmp[jn] = make_float4(c[0], c[1], c[2], c[3]);
          }
#pragma unroll
          for (int jn = 0; jn < 16; jn++) { const float4 c = tmp[jn]; S[jn * 4] = c.x; S[jn * 4 + 1] = c.y; S[jn * 4 + 2] = c.z; S[jn * 4 + 3] = c.w; }
          float x0, x1;
          row_max(x0, x1);
          const float n0 = fmaxf(mb0, x0 * sc), n1 = fmaxf(mb1, x1 * sc);
          const float f0 = ex2(mb0 - n0), f1 = ex2(mb1 - n1);
          mb0 = n0; mb1 = n1;
          l0 *= f0; l1 *= f1;
#pragma unroll
          for (int i = 0; i < 16; i++) { O[i * 4] *= f0; O[i * 4 + 1] *= f0; O[i * 4 + 2] *= f1; O[i * 4 + 3] *= f1; }
          s0 = 0.f; s1 = 0.f;
          exps(0, 16);
          cvtP();
        }
        l0 += s0; l1 += s1;
      }
    }
    STAMP(70);
    turn_begin();
    issue_pv(3, 0);
    wgmma_commit();
    turn_end();
    {
      uint32_t A[128];
#pragma unroll
      for (int i = 0; i < 16; i++) {
        const uint4 v = lds128(sb + SM_STASH + i * 4096 + ct * 16);
        A[i * 4] = v.x; A[i * 4 + 1] = v.y; A[i * 4 + 2] = v.z; A[i * 4 + 3] = v.w;
      }
      o_scale();
      if (lane < 2) mbar_expect_tx(sBar + B_XF + w8 * 8 + lane * 64, 2048);
      wgmma_wait<0>();
      release(B_EMPTYA + 24);
#pragma unroll
      for (int i = 16; i < 24; i++) {
        const uint4 v = lds128(sb + SM_STASH + i * 4096 + ct * 16);
        A[i * 4] = v.x; A[i * 4 + 1] = v.y; A[i * 4 + 2] = v.z; A[i * 4 + 3] = v.w;
      }
#pragma unroll
      for (int i = 0; i < 8; i++) {
        const uint4 v = o_frag(i);
        A[96 + i * 4] = v.x; A[96 + i * 4 + 1] = v.y; A[96 + i * 4 + 2] = v.z; A[96 + i * 4 + 3] = v.w;
      }
      if (__any_sync(~0u, A[95] != 0x12345678u || A[64] != 0x9abcdef0u || lane == 0)) release1(B_ST);
      STAMP(71);
      float4* const accp = g_acc + ((size_t)(qt * 2 + cw) * 72 * 4 + (w8 & 3)) * 32 + lane;
      const uint32_t xb = sb + SM_XCH + w8 * 2048 + lane * 16;
      const uint32_t peer = __shfl_sync(~0u, relBar, 1) - sBar;
      float c0[32], c1[32];
      int gr = 0, par = 0, ch = kg * 2;
      float4* pp = accp;
      auto send = [&](const float* v, int xp) {
#pragma unroll
        for (int j = 0; j < 4; j++)
          asm volatile("st.async.shared::cluster.mbarrier::complete_tx::bytes.v4.f32 [%0], {%1,%2,%3,%4}, [%5];" ::"r"(xb + peer + xp * 16384 + j * 512),
                       "f"(v[j * 4]), "f"(v[j * 4 + 1]), "f"(v[j * 4 + 2]), "f"(v[j * 4 + 3]), "r"(sBar + B_XF + xp * 64 + w8 * 8 + peer) : "memory");
      };
      auto recv = [&](const float* v, float4* q, int xp) {
#pragma unroll
        for (int j = 0; j < 4; j++) {
          const uint4 u = lds128(xb + xp * 16384 + j * 512);
          red_add_v4(q + j * 128, v[j * 4] + __uint_as_float(u.x), v[j * 4 + 1] + __uint_as_float(u.y), v[j * 4 + 2] + __uint_as_float(u.z), v[j * 4 + 3] + __uint_as_float(u.w));
        }
      };
      auto chunk = [&](float (&acc)[32], float (&prev)[32], bool has_prev, bool last, int xp) {
#pragma unroll
        for (int hd = 0; hd < 4; hd++) {
          if (!(hd & 1)) turn_begin();
          const uint32_t db = dB_k + (gr + (hd & 1)) * 1024;
#pragma unroll
          for (int kk = 0; kk < 8; kk++)
            wgmma64_rs(acc, A[hd * 32 + kk * 4], A[hd * 32 + kk * 4 + 1], A[hd * 32 + kk * 4 + 2], A[hd * 32 + kk * 4 + 3], db + kk * 128, (hd | kk) != 0);
          wgmma_commit();
          if (hd & 1) {
            turn_end();
            if (hd == 1 && has_prev) {
              mbar_wait(sBar + B_XF + (xp ^ 1) * 64 + w8 * 8, par);
              if (rank) recv(prev + 16, pp + 512, xp ^ 1); else recv(prev, pp, xp ^ 1);
              if (lane == 0) mbar_expect_tx(sBar + B_XF + (xp ^ 1) * 64 + w8 * 8, 2048);
              if (!xp) par ^= 1;
            }
            wgmma_wait<1>();
            release1(B_EMPTYO + gr * 8);
            wgmma_wait<0>();
            release1(B_EMPTYO + gr * 8 + 8);
            if ((gr += 2) == 6) gr = 0;
          }
        }
        pp = accp + ch * 1024;
        if (++ch == 9) ch = 0;
        if (!last) {
          if (!has_prev) mbar_wait(sBar + B_EMPTYA + 24, 0);
          if (rank) send(acc, xp); else send(acc + 16, xp);
        }
      };
#pragma unroll 1
      for (int cp = 0;; cp++) {
        chunk(c0, c1, cp != 0, cp == 4, 0);
        if (cp == 4) break;
        chunk(c1, c0, true, false, 1);
      }
      STAMP(72);
#pragma unroll
      for (int jb = 0; jb < 8; jb++) red_add_v4(pp + jb * 128, c0[jb * 4], c0[jb * 4 + 1], c0[jb * 4 + 2], c0[jb * 4 + 3]);
      if (cw == 0) bar_sync(1, 288);
    }
    bar_sync(5, 256);
    if (ct == 0) cnt_arrive(C_Q + qt);
    STAMP(73);
    {
      const int rowA = qt * 128 + hg * 16 + w8;
      const size_t oA = (size_t)rowA * (DM / 2) + lane, oB = oA + 8 * (DM / 2);
      uint32_t xa[9], xb[9], wr[9];
      uint4 md[9];
#pragma unroll
      for (int i = 0; i < 9; i++) {
        xa[i] = __ldg(reinterpret_cast<const uint32_t*>(prm.x) + oA + i * 32);
        xb[i] = __ldg(reinterpret_cast<const uint32_t*>(prm.x) + oB + i * 32);
        wr[i] = __ldg(reinterpret_cast<const uint32_t*>(prm.w_r) + lane + i * 32);
        md[i] = __ldcg(g_mod2 + lane + i * 32);
      }
      cnt_wait(C_Q + qt, 8);
      __syncwarp();
      STAMP(74);
      const float4* ap = g_acc + ((size_t)(qt * 2 + (hg >> 2)) * 72 * 4 + (hg & 3)) * 32 + g * 128 + w8 * 4 + t4;
      float4 av[9];
#pragma unroll
      for (int i = 0; i < 9; i++) av[i] = __ldcg(ap + i * 1024);
      float sA = 0.f, sB = 0.f;
#pragma unroll
      for (int i = 0; i < 9; i++) {
        xa[i] = hadd2(xa[i], hmul2(md[i].x, pack_bf16(av[i].x, av[i].y)));
        xb[i] = hadd2(xb[i], hmul2(md[i].x, pack_bf16(av[i].z, av[i].w)));
        g_x2[oA + i * 32] = xa[i]; g_x2[oB + i * 32] = xb[i];
        sA += bf_lo(xa[i]) + bf_hi(xa[i]); sB += bf_lo(xb[i]) + bf_hi(xb[i]);
      }
      const float mA = warp_sum(sA) * (1.f / DM), mB = warp_sum(sB) * (1.f / DM);
      sA = 0.f; sB = 0.f;
#pragma unroll
      for (int i = 0; i < 9; i++) {
        const float d0 = bf_lo(xa[i]) - mA, d1 = bf_hi(xa[i]) - mA, d2 = bf_lo(xb[i]) - mB, d3 = bf_hi(xb[i]) - mB;
        sA += d0 * d0 + d1 * d1; sB += d2 * d2 + d3 * d3;
      }
      const float rA = rcp(bfr(sqrt_a(bfr(bfr(warp_sum(sA) * (1.f / DM)) + 1e-5f))));
      const float rB = rcp(bfr(sqrt_a(bfr(bfr(warp_sum(sB) * (1.f / DM)) + 1e-5f))));
      const uint32_t nmA = pack_bf16(-mA, -mA), nmB = pack_bf16(-mB, -mB);
      sA = 0.f; sB = 0.f;
      uint32_t ha[9], hb[9];
#pragma unroll
      for (int i = 0; i < 9; i++) {
        const uint32_t da = hadd2(xa[i], nmA), db = hadd2(xb[i], nmB);
        ha[i] = hadd2(hmul2(pack_bf16(bf_lo(da) * rA, bf_hi(da) * rA), md[i].z), md[i].y);
        hb[i] = hadd2(hmul2(pack_bf16(bf_lo(db) * rB, bf_hi(db) * rB), md[i].z), md[i].y);
        g_h2[oA + i * 32] = ha[i]; g_h2[oB + i * 32] = hb[i];
        const float w0 = bf_lo(wr[i]), w1 = bf_hi(wr[i]);
        sA += bf_lo(ha[i]) * w0 + bf_hi(ha[i]) * w1; sB += bf_lo(hb[i]) * w0 + bf_hi(hb[i]) * w1;
      }
      const uint32_t rr = pack_bf16(warp_sum(sA), warp_sum(sB));
      uint32_t u = ((lane & 1) ? rr : rr << 16) & 0xffff0000u;
      u = ((u & 0x7fff0000u) > 0x7f800000u) ? 0u : (u ^ ((u >> 31) ? 0xffff0000u : 0x80000000u));
      u |= 0xffffu - (rowA + (lane & 1) * 8);
      __syncwarp();
      if (lane < 2) asm volatile("st.release.gpu.global.u32 [%0], %1;" ::"l"(reinterpret_cast<uint32_t*>(g_key) + b * 16 + w8 * 2 + lane), "r"(u) : "memory");
#pragma unroll
      for (int i = 0; i < 9; i++) {
        reinterpret_cast<uint32_t*>(prm.out)[oA + i * 32] = hadd2(xa[i], hmul2(md[i].w, ha[i]));
        reinterpret_cast<uint32_t*>(prm.out)[oB + i * 32] = hadd2(xb[i], hmul2(md[i].w, hb[i]));
      }
    }
    STAMP(75);
    uint32_t* const tsu = reinterpret_cast<uint32_t*>(smem_raw + SM_T);
    float* const tsf = reinterpret_cast<float*>(smem_raw + SM_T);
    uint32_t k1, k2;
    {
      uint4 a, c;
      poll8(g_key + ct, g_key + 256 + ct, a, c);
      asm volatile("fence.acq_rel.gpu;" ::: "memory");
      auto merge = [](uint32_t& m1, uint32_t& m2, uint32_t n1, uint32_t n2) { m2 = max(min(m1, n1), max(m2, n2)); m1 = max(m1, n1); };
      k1 = max(a.x, a.y); k2 = min(a.x, a.y);
      merge(k1, k2, max(a.z, a.w), min(a.z, a.w));
      merge(k1, k2, max(c.x, c.y), min(c.x, c.y));
      merge(k1, k2, max(c.z, c.w), min(c.z, c.w));
      uint32_t m1 = __reduce_max_sync(~0u, k1);
      uint32_t m2 = __reduce_max_sync(~0u, k1 == m1 ? k2 : k1);
      if (lane == 0) { tsu[w8 * 2] = m1; tsu[w8 * 2 + 1] = m2; }
      bar_sync(5, 256);
      const uint32_t v = tsu[lane & 15];
      k1 = __reduce_max_sync(~0u, v);
      k2 = __reduce_max_sync(~0u, v == k1 ? 0u : v);
    }
    STAMP(76);
    const int row1 = (0xffff - (k1 & 0xffff)) & (SQ - 1), row2 = (0xffff - (k2 & 0xffff)) & (SQ - 1);
    {
      const int kq = w8 >> 1;
      uint32_t af[18];
      const uint32_t* hp = g_h2 + (size_t)(g ? row2 : row1) * (DM / 2) + kq * 72 + t4;
#pragma unroll
      for (int i = 0; i < 18; i++) af[i] = g < 2 ? __ldcg(hp + i * 4) : 0u;
      float c[5][4];
#pragma unroll
      for (int i = 0; i < 5; i++) c[i][0] = c[i][1] = c[i][2] = c[i][3] = 0.f;
      mbar_wait(sBar + B_FFN, 0);
      STAMP(77);
      const uint32_t wa = sb + ((w8 & 1) ? SM_WU : SM_WG) + (kq * 144 + (lane & 15)) * 80 + (lane >> 4) * 16;
#pragma unroll
      for (int ks = 0; ks < 9; ks++) {
        uint32_t b0[4], b1[4], b2[2];
        ldsm4t(b0, wa + ks * 1280); ldsm4t(b1, wa + ks * 1280 + 32); ldsm2t(b2, wa + ks * 1280 + 64 - (lane >> 4) * 16);
        mma16816(c[0], af[2 * ks], 0u, af[2 * ks + 1], 0u, b0[0], b0[1]);
        mma16816(c[1], af[2 * ks], 0u, af[2 * ks + 1], 0u, b0[2], b0[3]);
        mma16816(c[2], af[2 * ks], 0u, af[2 * ks + 1], 0u, b1[0], b1[1]);
        mma16816(c[3], af[2 * ks], 0u, af[2 * ks + 1], 0u, b1[2], b1[3]);
        mma16816(c[4], af[2 * ks], 0u, af[2 * ks + 1], 0u, b2[0], b2[1]);
      }
      float* const part = tsf + 64;
      if (g < 2) {
#pragma unroll
        for (int i = 0; i < 5; i++) *reinterpret_cast<float2*>(part + w8 * 80 + g * 40 + i * 8 + t4 * 2) = make_float2(c[i][0], c[i][1]);
      }
      bar_sync(5, 256);
      bf16* const act = reinterpret_cast<bf16*>(tsf + 768);
      if (ct < 96) {
        const int tok = ct >= 48, f = ct - tok * 48;
        float v = 0.f;
        if (f < 36) {
          const float* pp = part + tok * 40 + f + (b & 1) * 4;
          const float gs = (pp[0] + pp[160]) + (pp[320] + pp[480]), us = (pp[80] + pp[240]) + (pp[400] + pp[560]);
          v = silu_bf(bfr(gs)) * bfr(us);
        }
        act[ct] = __float2bfloat16(v);
      }
      bar_sync(5, 256);
      uint32_t a6[5];
#pragma unroll
      for (int i = 0; i < 5; i++) a6[i] = g < 2 ? reinterpret_cast<const uint32_t*>(act)[g * 24 + i * 4 + t4] : 0u;
#pragma unroll 3
      for (int i = 0; i < 9; i++) {
        const int nt = w8 * 9 + i;
        const uint32_t a = sb + (nt >> 3) * 5120 + (nt / 24) * 1024 + lane * 128 + (((nt ^ lane) & 7) << 4);
        uint32_t b0[4], b2;
        ldsm4t(b0, a);
        asm volatile("ldmatrix.sync.aligned.m8n8.x1.trans.shared.b16 {%0}, [%1];" : "=r"(b2) : "r"(a + 4096) : "memory");
        float y[4] = {0.f, 0.f, 0.f, 0.f};
        mma16816(y, a6[0], 0u, a6[1], 0u, b0[0], b0[1]);
        mma16816(y, a6[2], 0u, a6[3], 0u, b0[2], b0[3]);
        mma16816(y, a6[4], 0u, 0u, 0u, b2, 0u);
        if (g < 2) asm volatile("red.global.add.v2.f32 [%0], {%1,%2};" ::"l"(g_y + g * DM + nt * 8 + t4 * 2), "f"(y[0]), "f"(y[1]) : "memory");
      }
    }
    bar_sync(5, 256);
    STAMP(78);
    if (ct == 0) tsu[32] = cnt_arrive(C_Y);
    bar_sync(5, 256);
    if (tsu[32] == 127) {
#pragma unroll 1
      for (int i = ct; i < DM; i += 256) {
        const int tok = i >= DM / 2, cp = i - tok * (DM / 2);
        const uint32_t key = tok ? k2 : k1;
        const float r = __uint_as_float((key & 0xffff0000u) ^ ((key >> 31) ? 0x80000000u : 0xffff0000u));
        const float sg = rcp(1.f + __expf(-r));
        const size_t o = (size_t)(tok ? row2 : row1) * (DM / 2) + cp;
        const float2 ys = __ldcg(reinterpret_cast<const float2*>(g_y) + i);
        const uint32_t hb = hadd2(__ldcg(g_h2 + o), hmul2(pack_bf16(ys.x, ys.y), pack_bf16(sg, sg)));
        reinterpret_cast<uint32_t*>(prm.out)[o] = hadd2(__ldcg(g_x2 + o), hmul2(__ldcg(g_mod2 + cp).w, hb));
      }
      const uint4 z = make_uint4(0, 0, 0, 0);
      g_key[ct] = z; g_key[256 + ct] = z;
#pragma unroll 1
      for (int i = ct; i < 8 * 144; i += 256) g_mod1[i] = z;
      if (ct < 24) g_cnt[ct * 32] = 0;
    }
    STAMP(79); GSTAMP(91);
  }
}

typedef CUresult (*PFN_enc)(CUtensorMap*, CUtensorMapDataType, cuuint32_t, void*, const cuuint64_t*, const cuuint64_t*,
                            const cuuint32_t*, const cuuint32_t*, CUtensorMapInterleave, CUtensorMapSwizzle,
                            CUtensorMapL2promotion, CUtensorMapFloatOOBfill);
static PFN_enc g_enc = nullptr;
static CUtensorMap mk_map(const void* p, uint64_t cols, uint64_t rows, uint32_t bc, uint32_t br, bool swz = true) {
  CUtensorMap m;
  cuuint64_t dims[2] = {cols, rows};
  cuuint64_t strides[1] = {cols * 2};
  cuuint32_t box[2] = {bc, br}, es[2] = {1, 1};
  g_enc(&m, CU_TENSOR_MAP_DATA_TYPE_BFLOAT16, 2, const_cast<void*>(p), dims, strides, box, es, CU_TENSOR_MAP_INTERLEAVE_NONE,
        swz ? CU_TENSOR_MAP_SWIZZLE_128B : CU_TENSOR_MAP_SWIZZLE_NONE, swz ? CU_TENSOR_MAP_L2_PROMOTION_L2_128B : CU_TENSOR_MAP_L2_PROMOTION_NONE,
        CU_TENSOR_MAP_FLOAT_OOB_FILL_NONE);
  return m;
}

extern "C" void kernel_launch(void* const* d_in, const int* in_sizes, int n_in, void* d_out, int out_size) {
  if (!g_enc) {
    cudaDriverEntryPointQueryResult st;
    cudaGetDriverEntryPoint("cuTensorMapEncodeTiled", (void**)&g_enc, cudaEnableDefault, &st);
    cudaFuncSetAttribute(k_mega, cudaFuncAttributeMaxDynamicSharedMemorySize, SM_TOTAL);
  }
  CUtensorMap mX = mk_map(d_in[0], DM, SQ, 64, 128);
  CUtensorMap mWq = mk_map(d_in[3], HQ * DH, DM, 64, 144);
  CUtensorMap mK = mk_map(d_in[1], DH, HKV * SK, 64, 128);
  CUtensorMap mV = mk_map(d_in[2], DH, HKV * SK, 64, 128);
  CUtensorMap mWo = mk_map(d_in[4], DM, HQ * DH, 64, 128);
  CUtensorMap mWg = mk_map(d_in[7], FF, DM, 40, 64, false);
  CUtensorMap mWu = mk_map(d_in[8], FF, DM, 40, 64, false);
  CUtensorMap mWd = mk_map(d_in[9], DM, FF, 64, 40);
  Params prm;
  prm.x = (const bf16*)d_in[0]; prm.k = (const bf16*)d_in[1]; prm.v = (const bf16*)d_in[2]; prm.wo = (const bf16*)d_in[4]; prm.wq = (const bf16*)d_in[3];
  prm.w_r = (const bf16*)d_in[6]; prm.c = (const bf16*)d_in[10]; prm.w_mod = (const bf16*)d_in[11];
  prm.wg = (const bf16*)d_in[7]; prm.wu = (const bf16*)d_in[8];
  prm.out = (bf16*)d_out;
  cudaLaunchConfig_t cfg = {};
  cfg.gridDim = dim3(128); cfg.blockDim = dim3(384); cfg.dynamicSmemBytes = SM_TOTAL; cfg.stream = cudaStreamPerThread;
  cudaLaunchAttribute at[1];
  at[0].id = cudaLaunchAttributeClusterDimension;
  at[0].val.clusterDim.x = 2; at[0].val.clusterDim.y = 1; at[0].val.clusterDim.z = 1;
  cfg.attrs = at; cfg.numAttrs = 1;
  cudaLaunchKernelEx(&cfg, k_mega, mX, mWq, mK, mV, mWo, mWg, mWu, mWd, prm);
}
```

```cpp
#include <cuda_runtime.h>
#include <cuda_bf16.h>
#include <cuda.h>
#include <stdint.h>

typedef __nv_bfloat16 bf16;

constexpr int SQ = 2048, DM = 576, HQ = 32, HKV = 16, SK = 2048, DH = 128, FF = 4608;

#define XPF 0
#define WQPF0 0
#define WQPF1 0xff
#define FFNQ 2
#define WQPF2 0
#define QTH 7
#define MPF 1
#define FILLP 26
#define FILL0 10
#define FFN0 20
#define FILLN 6
#define FFNB 6
#define PF0 13
#define FFNR 1
#define FFND 1
#define KV0 16
#define KVS 2
#define LAZY_LIMIT 1.0995116e12f
__device__ uint4 g_mod1[8 * 144];
__device__ uint4 g_mod2[288];
__device__ uint4 g_q[128 * 4 * 8 * 256];
constexpr int Z_ACC = 0;
constexpr int Z_KEY = 16 * 2 * 72 * 4 * 32;
constexpr int Z_N = 2368;
__device__ uint4 g_zero[128 * Z_N];
constexpr int F_HX = 0;
constexpr int F_YP = 128 * 2 * 144;
constexpr int F_P = F_YP + 36 * 128 * 8;
constexpr int F_N = 288 + 288 + 8 * 12 * 32;
__device__ uint4 g_ones[128 * F_N];
#define g_acc reinterpret_cast<float4*>(g_zero)
__device__ unsigned int g_cnt[136 * 32];
__device__ unsigned int g_err;
#define HAS_ERR
enum { C_SIDE = 1, C_Q = 8 };

#define STAMP(i)
#define KSTAMP(i)
#define GSTAMP(i)
#define SETERR(v)
#define PSTAMP(t, i)

__device__ __forceinline__ uint32_t smem_u32(const void* p) { return (uint32_t)__cvta_generic_to_shared(p); }
__device__ __forceinline__ void mbar_init(uint32_t a, uint32_t cnt) { asm volatile("mbarrier.init.shared::cta.b64 [%0], %1;" ::"r"(a), "r"(cnt)); }
__device__ __forceinline__ void mbar_expect_tx(uint32_t a, uint32_t bytes) { asm volatile("mbarrier.arrive.expect_tx.shared::cta.b64 _, [%0], %1;" ::"r"(a), "r"(bytes) : "memory"); }
__device__ __forceinline__ void mbar_arrive_cl(uint32_t a_cluster) { asm volatile("mbarrier.arrive.shared::cluster.b64 _, [%0];" ::"r"(a_cluster) : "memory"); }
__device__ __forceinline__ void mbar_wait(uint32_t a, uint32_t parity) {
  asm volatile(
      "{\n.reg .pred p;\n.reg .u32 n;\nmov.u32 n, 0;\n"
      "WAIT_LOOP:\n"
      "mbarrier.try_wait.parity.shared::cta.b64 p, [%0], %1;\n"
      "@p bra WAIT_DONE;\n"
      "add.u32 n, n, 1;\n"
      "setp.lt.u32 p, n, 65536;\n"
      "@p bra WAIT_LOOP;\n"
      "WAIT_DONE:\n}\n" ::"r"(a), "r"(parity), "l"(&g_err) : "memory");
}
__device__ __forceinline__ unsigned ld_acquire(const unsigned* p) {
  unsigned v;
  asm volatile("ld.acquire.gpu.global.u32 %0, [%1];" : "=r"(v) : "l"(p) : "memory");
  return v;
}
__device__ __forceinline__ void cnt_wait(int idx, unsigned target) {
  uint32_t n = 0;
  while (ld_acquire(&g_cnt[idx * 32]) < target) {
    if (++n > (1u << 15)) { SETERR(2); break; }
  }
}
__device__ __forceinline__ unsigned cnt_arrive(int idx) {
  unsigned old;
  asm volatile("atom.add.acq_rel.gpu.global.u32 %0, [%1], 1;" : "=r"(old) : "l"(&g_cnt[idx * 32]) : "memory");
  return old;
}
__device__ __forceinline__ uint4 poll4(const uint4* p) {
  uint4 v;
  uint32_t n = 0;
  while (true) {
    asm volatile("ld.relaxed.gpu.global.v4.u32 {%0,%1,%2,%3}, [%4];" : "=r"(v.x), "=r"(v.y), "=r"(v.z), "=r"(v.w) : "l"(p) : "memory");
    if (v.x && v.y && v.z && v.w) break;
    if (++n > (1u << 15)) { SETERR(4); break; }
  }
  return v;
}
__device__ __forceinline__ void poll8(const uint4* p, const uint4* q, uint4& v, uint4& w) {
  uint32_t n = 0;
  while (true) {
    asm volatile("ld.relaxed.gpu.global.v4.u32 {%0,%1,%2,%3}, [%4];" : "=r"(v.x), "=r"(v.y), "=r"(v.z), "=r"(v.w) : "l"(p) : "memory");
    asm volatile("ld.relaxed.gpu.global.v4.u32 {%0,%1,%2,%3}, [%4];" : "=r"(w.x), "=r"(w.y), "=r"(w.z), "=r"(w.w) : "l"(q) : "memory");
    if (v.x && v.y && v.z && v.w && w.x && w.y && w.z && w.w) break;
    if (++n > (1u << 15)) { SETERR(4); break; }
  }
}
__device__ __forceinline__ uint4 ldr4(const void* p) {
  uint4 v;
  asm volatile("ld.relaxed.gpu.global.v4.u32 {%0,%1,%2,%3}, [%4];" : "=r"(v.x), "=r"(v.y), "=r"(v.z), "=r"(v.w) : "l"(p) : "memory");
  return v;
}
__device__ __forceinline__ uint2 ldr2(const void* p) {
  uint2 v;
  asm volatile("ld.relaxed.gpu.global.v2.u32 {%0,%1}, [%2];" : "=r"(v.x), "=r"(v.y) : "l"(p) : "memory");
  return v;
}
__device__ __forceinline__ void str1(void* p, uint32_t v) { asm volatile("st.relaxed.gpu.global.u32 [%0], %1;" ::"l"(p), "r"(v) : "memory"); }
__device__ __forceinline__ bool unset(uint4 v) { return v.x == ~0u || v.y == ~0u || v.z == ~0u || v.w == ~0u; }
__device__ __forceinline__ uint32_t hmul2(uint32_t a, uint32_t b) { uint32_t r; asm("mul.rn.bf16x2 %0, %1, %2;" : "=r"(r) : "r"(a), "r"(b)); return r; }
__device__ __forceinline__ uint32_t hadd2(uint32_t a, uint32_t b) { uint32_t r; asm("add.rn.bf16x2 %0, %1, %2;" : "=r"(r) : "r"(a), "r"(b)); return r; }
__device__ __forceinline__ uint32_t hfma2(uint32_t a, uint32_t b, uint32_t c) { uint32_t r; asm("fma.rn.bf16x2 %0, %1, %2, %3;" : "=r"(r) : "r"(a), "r"(b), "r"(c)); return r; }
__device__ __forceinline__ void mma16816(float (&c)[4], uint32_t a0, uint32_t a1, uint32_t a2, uint32_t a3, uint32_t b0, uint32_t b1) {
  asm volatile("mma.sync.aligned.m16n8k16.row.col.f32.bf16.bf16.f32 {%0,%1,%2,%3}, {%4,%5,%6,%7}, {%8,%9}, {%0,%1,%2,%3};"
               : "+f"(c[0]), "+f"(c[1]), "+f"(c[2]), "+f"(c[3]) : "r"(a0), "r"(a1), "r"(a2), "r"(a3), "r"(b0), "r"(b1));
}
__device__ __forceinline__ void mma1688(float (&c)[4], uint32_t a0, uint32_t a1, uint32_t b0) {
  asm volatile("mma.sync.aligned.m16n8k8.row.col.f32.bf16.bf16.f32 {%0,%1,%2,%3}, {%4,%5}, {%6}, {%0,%1,%2,%3};"
               : "+f"(c[0]), "+f"(c[1]), "+f"(c[2]), "+f"(c[3]) : "r"(a0), "r"(a1), "r"(b0));
}
__device__ __forceinline__ void ldsm4t(uint32_t (&r)[4], uint32_t a) {
  asm volatile("ldmatrix.sync.aligned.m8n8.x4.trans.shared.b16 {%0,%1,%2,%3}, [%4];" : "=r"(r[0]), "=r"(r[1]), "=r"(r[2]), "=r"(r[3]) : "r"(a) : "memory");
}
__device__ __forceinline__ void ldsm4(uint32_t (&r)[4], uint32_t a) {
  asm volatile("ldmatrix.sync.aligned.m8n8.x4.shared.b16 {%0,%1,%2,%3}, [%4];" : "=r"(r[0]), "=r"(r[1]), "=r"(r[2]), "=r"(r[3]) : "r"(a) : "memory");
}
__device__ __forceinline__ void ldsm2t(uint32_t (&r)[2], uint32_t a) {
  asm volatile("ldmatrix.sync.aligned.m8n8.x2.trans.shared.b16 {%0,%1}, [%2];" : "=r"(r[0]), "=r"(r[1]) : "r"(a) : "memory");
}
__device__ __forceinline__ float warp_sum(float v) {
#pragma unroll
  for (int o = 16; o; o >>= 1) v += __shfl_xor_sync(~0u, v, o);
  return v;
}
__device__ __forceinline__ void tma_load_2d(uint32_t dst, const CUtensorMap* map, uint32_t mbar, int c0, int c1) {
  asm volatile("cp.async.bulk.tensor.2d.shared::cluster.global.mbarrier::complete_tx::bytes [%0], [%1, {%3, %4}], [%2];"
               ::"r"(dst), "l"(map), "r"(mbar), "r"(c0), "r"(c1) : "memory");
}
__device__ __forceinline__ void tma_load_2d_mc(uint32_t dst, const CUtensorMap* map, uint32_t mbar, int c0, int c1) {
  asm volatile("cp.async.bulk.tensor.2d.shared::cluster.global.mbarrier::complete_tx::bytes.multicast::cluster [%0], [%1, {%3, %4}], [%2], %5;"
               ::"r"(dst), "l"(map), "r"(mbar), "r"(c0), "r"(c1), "h"((uint16_t)3) : "memory");
}
__device__ __forceinline__ void tma_prefetch_2d(const CUtensorMap* map, int c0, int c1) {
  asm volatile("cp.async.bulk.prefetch.tensor.2d.L2.global.tile [%0, {%1, %2}];" ::"l"(map), "r"(c0), "r"(c1) : "memory");
}
__device__ __forceinline__ void bulk_prefetch(const void* p, uint32_t bytes) {
  asm volatile("cp.async.bulk.prefetch.L2.global [%0], %1;" ::"l"(p), "r"(bytes) : "memory");
}
__device__ __forceinline__ void bulk_load(uint32_t dst, const void* src, uint32_t bytes, uint32_t mbar) {
  asm volatile("cp.async.bulk.shared::cluster.global.mbarrier::complete_tx::bytes [%0], [%1], %2, [%3];"
               ::"r"(dst), "l"(src), "r"(bytes), "r"(mbar) : "memory");
}
__device__ __forceinline__ void wgmma_fence() { asm volatile("wgmma.fence.sync.aligned;" ::: "memory"); }
__device__ __forceinline__ void wgmma_commit() { asm volatile("wgmma.commit_group.sync.aligned;" ::: "memory"); }
template <int N> __device__ __forceinline__ void wgmma_wait() { asm volatile("wgmma.wait_group.sync.aligned %0;" ::"n"(N) : "memory"); }
__device__ __forceinline__ void fence_async() { asm volatile("fence.proxy.async.shared::cta;" ::: "memory"); }
__device__ __forceinline__ void bar_sync(int id, int n) { asm volatile("bar.sync %0, %1;" ::"r"(id), "r"(n) : "memory"); }
__device__ __forceinline__ void bar_arrive(int id, int n) { asm volatile("bar.arrive %0, %1;" ::"r"(id), "r"(n) : "memory"); }

constexpr uint32_t SM_BASE = 1024;
__host__ __device__ constexpr uint32_t mk_desc(uint32_t addr, uint32_t lbo_bytes) { return ((addr & 0x3FFFF) >> 4) | ((lbo_bytes >> 4) << 16); }

#define R32(d) \
  "+f"(d[0]), "+f"(d[1]), "+f"(d[2]), "+f"(d[3]), "+f"(d[4]), "+f"(d[5]), "+f"(d[6]), "+f"(d[7]), \
  "+f"(d[8]), "+f"(d[9]), "+f"(d[10]), "+f"(d[11]), "+f"(d[12]), "+f"(d[13]), "+f"(d[14]), "+f"(d[15]), \
  "+f"(d[16]), "+f"(d[17]), "+f"(d[18]), "+f"(d[19]), "+f"(d[20]), "+f"(d[21]), "+f"(d[22]), "+f"(d[23]), \
  "+f"(d[24]), "+f"(d[25]), "+f"(d[26]), "+f"(d[27]), "+f"(d[28]), "+f"(d[29]), "+f"(d[30]), "+f"(d[31])
#define R64(d) R32(d), \
  "+f"(d[32]), "+f"(d[33]), "+f"(d[34]), "+f"(d[35]), "+f"(d[36]), "+f"(d[37]), "+f"(d[38]), "+f"(d[39]), \
  "+f"(d[40]), "+f"(d[41]), "+f"(d[42]), "+f"(d[43]), "+f"(d[44]), "+f"(d[45]), "+f"(d[46]), "+f"(d[47]), \
  "+f"(d[48]), "+f"(d[49]), "+f"(d[50]), "+f"(d[51]), "+f"(d[52]), "+f"(d[53]), "+f"(d[54]), "+f"(d[55]), \
  "+f"(d[56]), "+f"(d[57]), "+f"(d[58]), "+f"(d[59]), "+f"(d[60]), "+f"(d[61]), "+f"(d[62]), "+f"(d[63])
#define S32 \
  "{%0,%1,%2,%3,%4,%5,%6,%7,%8,%9,%10,%11,%12,%13,%14,%15,%16,%17,%18,%19,%20,%21,%22,%23,%24,%25,%26,%27,%28,%29,%30,%31}"
#define S64 \
  "{%0,%1,%2,%3,%4,%5,%6,%7,%8,%9,%10,%11,%12,%13,%14,%15,%16,%17,%18,%19,%20,%21,%22,%23,%24,%25,%26,%27,%28,%29,%30,%31," \
  "%32,%33,%34,%35,%36,%37,%38,%39,%40,%41,%42,%43,%44,%45,%46,%47,%48,%49,%50,%51,%52,%53,%54,%55,%56,%57,%58,%59,%60,%61,%62,%63}"

template <int TB>
__device__ __forceinline__ void wgmma128_rs(float (&d)[64], uint32_t a0, uint32_t a1, uint32_t a2, uint32_t a3, uint32_t db, int scale_d) {
  asm volatile("{\n.reg .pred p;\n.reg .b64 q;\nsetp.ne.b32 p, %69, 0;\nmov.b64 q, {%68, 0x40000040};\n"
               "wgmma.mma_async.sync.aligned.m64n128k16.f32.bf16.bf16 " S64 ", {%64,%65,%66,%67}, q, p, 1, 1, %70;\n}\n"
               : R64(d) : "r"(a0), "r"(a1), "r"(a2), "r"(a3), "r"(db), "r"(scale_d), "n"(TB));
}
__device__ __forceinline__ void wgmma64_rs(float (&d)[32], uint32_t a0, uint32_t a1, uint32_t a2, uint32_t a3, uint32_t db, int scale_d) {
  asm volatile("{\n.reg .pred p;\n.reg .b64 q;\nsetp.ne.b32 p, %37, 0;\nmov.b64 q, {%36, 0x40000040};\n"
               "wgmma.mma_async.sync.aligned.m64n64k16.f32.bf16.bf16 " S32 ", {%32,%33,%34,%35}, q, p, 1, 1, 1;\n}\n"
               : R32(d) : "r"(a0), "r"(a1), "r"(a2), "r"(a3), "r"(db), "r"(scale_d));
}
__device__ __forceinline__ uint32_t pack_bf16(float a, float b) {
  uint32_t r;
  asm("cvt.rn.bf16x2.f32 %0, %1, %2;" : "=r"(r) : "f"(b), "f"(a));
  return r;
}
__device__ __forceinline__ float ex2(float x) { float y; asm("ex2.approx.ftz.f32 %0, %1;" : "=f"(y) : "f"(x)); return y; }
__device__ __forceinline__ float bfr(float x) { return __bfloat162float(__float2bfloat16(x)); }
__device__ __forceinline__ float bf_lo(uint32_t u) { return __uint_as_float(u << 16); }
__device__ __forceinline__ float bf_hi(uint32_t u) { return __uint_as_float(u & 0xffff0000u); }
__device__ __forceinline__ uint4 lds128(uint32_t a) {
  uint4 v;
  asm volatile("ld.shared.v4.b32 {%0,%1,%2,%3}, [%4];" : "=r"(v.x), "=r"(v.y), "=r"(v.z), "=r"(v.w) : "r"(a) : "memory");
  return v;
}
__device__ __forceinline__ void sts128(uint32_t a, uint4 v) {
  asm volatile("st.shared.v4.b32 [%0], {%1,%2,%3,%4};" ::"r"(a), "r"(v.x), "r"(v.y), "r"(v.z), "r"(v.w) : "memory");
}
__device__ __forceinline__ void red_add_v4(float4* p, float a, float b, float c, float d) {
  asm volatile("red.global.add.v4.f32 [%0], {%1,%2,%3,%4};" ::"l"(p), "f"(a), "f"(b), "f"(c), "f"(d) : "memory");
}
__device__ __forceinline__ float rcp(float x) { float y; asm("rcp.approx.ftz.f32 %0, %1;" : "=f"(y) : "f"(x)); return y; }
__device__ __forceinline__ float sqrt_a(float x) { float y; asm("sqrt.approx.ftz.f32 %0, %1;" : "=f"(y) : "f"(x)); return y; }
__device__ __forceinline__ float silu_bf(float v) { return bfr(v * rcp(1.f + __expf(-v))); }

constexpr int SM_STASH = 131072;
constexpr int SM_QR = 81920;
constexpr int SM_XCH = 98304;
constexpr int SM_MISC = 229376;
constexpr int SM_TOTAL = 232448;
constexpr int B_FULLQ = 0, B_FULLA = 64, B_FULLO = 96, B_FFN = 160, B_RD = 168, B_MD = 176, B_X = 272,
              B_EMPTYQ = 280, B_EMPTYO = 344, B_ST = 392,
              B_EMPTYA = 400, B_M = 432, B_XF = 144;
constexpr int SM_MOD = SM_MISC + 448;
constexpr int SM_FILL = SM_MISC + 512;
constexpr int SM_RED = SM_MISC + 2752;
constexpr int SM_ZERO = SM_MISC + 3040;
constexpr int SM_WG = 137216, SM_WU = 183296;
constexpr int SM_T = SM_XCH;
constexpr int SM_OUT = SM_MISC - 32768;
constexpr int SM_MD = SM_STASH;

struct Params {
  const bf16 *x, *k, *c, *w_mod, *w_r, *wo, *v, *wq, *wg, *wu, *wd;
  bf16* out;
};

__global__ void __launch_bounds__(384, 1)
k_mega(const __grid_constant__ CUtensorMap mX, const __grid_constant__ CUtensorMap mWq,
       const __grid_constant__ CUtensorMap mK, const __grid_constant__ CUtensorMap mV,
       const __grid_constant__ CUtensorMap mWo, const __grid_constant__ CUtensorMap mWg,
       const __grid_constant__ CUtensorMap mWu, const __grid_constant__ CUtensorMap mWd, const Params prm) {
  extern __shared__ __align__(1024) uint8_t smem_raw[];
  const uint32_t sb = smem_u32(smem_raw);
  if ((sb & 0x3FFFF) != SM_BASE) __trap();
  const uint32_t sBar = sb + SM_MISC;
  const int tid = threadIdx.x, lane = tid & 31;
  PSTAMP(0, 84);
  const int warp = __shfl_sync(~0u, tid >> 5, 0);
  const int b = blockIdx.x, rank = b & 1, qt = (b >> 1) & 15, kg = b >> 5, hg = kg * 2 + rank;
  const int hcol = (kg * 8 + rank) * DH;
  auto wq_prefetch = [&](int mask) {
    const bf16* wp = prm.wq + (size_t)(qt * 36 + ((tid - 128) >> 3)) * (HQ * DH) + hcol + ((tid & 6) * 2 + (tid & 1)) * 64;
    if ((mask >> (tid & 7)) & 1) {
      asm volatile("prefetch.global.L2 [%0];" ::"l"(wp));
      if (warp == 4) asm volatile("prefetch.global.L2 [%0];" ::"l"(wp + 32 * (HQ * DH)));
    }
  };
  if (warp >= 4) wq_prefetch(WQPF0);
  if (lane == 0 && warp >= 4) {
    if (MPF && warp < 10 && b < 96) bulk_prefetch(prm.w_mod + (size_t)(b * 6 + warp - 4) * (6 * DM), 2 * DM * 2);
    const int c0 = warp < 9 ? 1 : 8, c1 = warp < 11 ? c0 : 16, c2 = warp < 11 ? c0 : 3;
#pragma unroll
    for (int j = 0; j < 7; j++) mbar_init(sBar + (warp - 4) * 56 + j * 8, (warp == 6 && (j & 6) == 4) ? 2 : j == 0 ? c0 : j < 5 ? c1 : c2);
    *reinterpret_cast<uint32_t*>(smem_raw + SM_ZERO) = 0;
    asm volatile("fence.mbarrier_init.release.cluster;" ::: "memory");
  }
  __syncwarp();
  asm volatile("barrier.cluster.arrive.relaxed.aligned;" ::: "memory");
#define CL_WAIT() asm volatile("barrier.cluster.wait.acquire.aligned;" ::: "memory")
  const bool do_mod1 = warp >= 1 && warp < 4 && b < 72;
  if (warp < 4) {
    asm volatile("setmaxnreg.dec.sync.aligned.u32 40;");
    if (warp == 0) {
      PSTAMP(0, 85);
      CL_WAIT();
      PSTAMP(0, 86);
      if (lane == 0) {
        mbar_expect_tx(sBar + B_X, 9 * 16384);
#pragma unroll
        for (int i = 0; i < 5; i++)
          if (i < 4 || rank == 0) tma_load_2d_mc(sb + (2 * i + rank) * 16384, &mX, sBar + B_X, (2 * i + rank) * 64, qt * 128);
      }
    }
    PSTAMP(0, 87);
    if (do_mod1) {
      const int st = tid - 32;
      const uint32_t stg = sb + SM_QR + 7 * 18432 + st * 16;
      {
        const bf16* wp = prm.w_mod + (size_t)(st >> 1) * (6 * DM) + b * 16 + (st & 1) * 8;
#pragma unroll
        for (int i = 0; i < 12; i++)
          asm volatile("cp.async.cg.shared.global [%0], [%1], 16;" ::"r"(stg + i * 1536), "l"(wp + (size_t)i * 48 * (6 * DM)) : "memory");
      }
      float* const sc = reinterpret_cast<float*>(smem_raw + SM_MOD);
#pragma unroll
      for (int i = 0; i < 3; i++) {
        const uint32_t v = __ldg(reinterpret_cast<const uint32_t*>(prm.c) + st + i * 96);
        *reinterpret_cast<float2*>(sc + (st + i * 96) * 2) = make_float2(silu_bf(bf_lo(v)), silu_bf(bf_hi(v)));
      }
      bar_sync(6, 96);
      PSTAMP(32, 88);
      asm volatile("cp.async.wait_all;" ::: "memory");
      PSTAMP(32, 93);
      float a[8];
#pragma unroll
      for (int i = 0; i < 8; i++) a[i] = 0.f;
#pragma unroll 3
      for (int i = 0; i < 12; i++) {
        const float sv = sc[(st >> 1) + 48 * i];
        const uint4 v = lds128(stg + i * 1536);
        a[0] += sv * bf_lo(v.x); a[1] += sv * bf_hi(v.x); a[2] += sv * bf_lo(v.y); a[3] += sv * bf_hi(v.y);
        a[4] += sv * bf_lo(v.z); a[5] += sv * bf_hi(v.z); a[6] += sv * bf_lo(v.w); a[7] += sv * bf_hi(v.w);
      }
      const bool u2 = lane & 2, u4 = lane & 4, u8 = lane & 8;
#pragma unroll
      for (int i = 0; i < 4; i++) { float snd = u2 ? a[i] : a[i + 4]; float kp = u2 ? a[i + 4] : a[i]; a[i] = kp + __shfl_xor_sync(~0u, snd, 2); }
#pragma unroll
      for (int i = 0; i < 2; i++) { float snd = u4 ? a[i] : a[i + 2]; float kp = u4 ? a[i + 2] : a[i]; a[i] = kp + __shfl_xor_sync(~0u, snd, 4); }
      { float snd = u8 ? a[0] : a[1]; float kp = u8 ? a[1] : a[0]; a[0] = kp + __shfl_xor_sync(~0u, snd, 8); }
      a[0] += __shfl_xor_sync(~0u, a[0], 16);
      float* const red = reinterpret_cast<float*>(smem_raw + SM_RED);
      if (lane < 16) red[(warp - 1) * 16 + (lane & 1) * 8 + (u2 ? 4 : 0) + (u4 ? 2 : 0) + (u8 ? 1 : 0)] = a[0];
      PSTAMP(32, 94);
      bar_sync(6, 96);
      PSTAMP(32, 95);
      if (st < 64) {
        const float* rp = red + (lane & 7) * 2;
        const float2 x = *reinterpret_cast<const float2*>(rp), y = *reinterpret_cast<const float2*>(rp + 16), z = *reinterpret_cast<const float2*>(rp + 32);
        uint32_t w = pack_bf16(x.x + y.x + z.x, x.y + y.y + z.y);
        if (b >= 36) w = hadd2(w, 0x3f803f80u);
        asm volatile("st.relaxed.gpu.global.u32 [%0], %1;" ::"l"(reinterpret_cast<uint32_t*>(g_mod1) + (st >> 3) * 576 + b * 8 + (lane & 7)), "r"(~w) : "memory");
      }
    }
    __syncwarp();
    PSTAMP(32, 89);
    if (warp > 0) {
      CL_WAIT();
      fence_async();
      if (tid < 104) {
        uint4 v, w;
        mbar_wait(sBar + B_X, 0);
        poll8(g_mod1 + (b & 7) * 144 + tid - 32, g_mod1 + (b & 7) * 144 + tid + 40, v, w);
        sts128(sb + SM_MOD + (tid - 32) * 32, make_uint4(~v.x, ~w.x, ~v.y, ~w.y));
        sts128(sb + SM_MOD + (tid - 32) * 32 + 16, make_uint4(~v.z, ~w.z, ~v.w, ~w.w));
      }
      __syncwarp();
      PSTAMP(32, 92);
      bar_arrive(3, 224);
      bar_arrive(4, 224);
      if (lane == 0) asm volatile("mbarrier.arrive.shared::cta.b64 _, [%0];" ::"r"(sBar + B_M) : "memory");
    }
    if (tid == 0) {
      auto kv_load = [&](int t) {
        const int s = t & 3;
        mbar_wait(sBar + B_EMPTYA + s * 8, (t >> 2) & 1);
        mbar_expect_tx(sBar + B_FULLA + s * 8, 32768);
        tma_load_2d_mc(sb + s * 32768 + rank * 16384, (t & 1) ? &mV : &mK, sBar + B_FULLA + s * 8, rank * 64, kg * 4 * SK + (t >> 1) * 128);
      };
#pragma unroll 1
      for (int i = 0; i < 32; i++) {
        const int hh = (i >> 2) + 2, g = i & 7;
        if (i == QTH) mbar_wait(sBar + B_M, 0);
        mbar_wait(sBar + B_EMPTYQ + g * 8, (i >> 3) & 1);
        mbar_expect_tx(sBar + B_FULLQ + g * 8, 18432);
        tma_load_2d(sb + SM_QR + g * 18432, &mWq, sBar + B_FULLQ + g * 8, hcol + (hh & 6) * 128 + (hh & 1) * 64, (i & 3) * 144);
        if ((i & ~4) == KV0) kv_load((i >> 2) & 1);
      }
#pragma unroll 1
      for (int u = 2; u < 128; u++) kv_load(u < 5 || u == 127 ? u : (u & 1) ? u + 1 : u - 1);
      mbar_wait(sBar + B_X, 1);
      {
        int ch = kg * 2, g = 0, par = 1, fb = 0;
        mbar_expect_tx(sBar + B_FFN, 9 * 5120 + 2 * DM * 80);
#pragma unroll 1
        for (int i = 0; i < 39; i++) {
          if (i < 6) mbar_wait(sBar + B_EMPTYA + (g >> 1) * 8, 0);
          else mbar_wait(sBar + B_EMPTYO + g * 8, par);
          if (i < 36) {
            mbar_expect_tx(sBar + B_FULLO + g * 8, 16384);
            tma_load_2d(sb + g * 16384, &mWo, sBar + B_FULLO + g * 8, ch * 64, hcol + (i & 3) * 256);
            if ((i & 3) == 3 && ++ch == 9) ch = 0;
            if (i == 7) {
              mbar_wait(sBar + B_ST, 0);
              asm volatile("fence.proxy.async;" ::: "memory");
              mbar_expect_tx(sBar + B_MD, 5760);
              bulk_load(sb + SM_MD, g_mod2, 4608, sBar + B_MD);
              bulk_load(sb + SM_MD + 4608, prm.w_r, 1152, sBar + B_MD);
            }
            if (i >= FFN0) {
#pragma unroll 1
              for (const int fe = i == 35 ? 24 : min(15, (i - FFN0 + 1) * FFNR / FFND); fb < fe; fb++) {
                const int m = fb >= 12;
                if (fb == 15) mbar_wait(sBar + B_RD, 0);
                tma_load_2d(sb + SM_WG + fb * 3840, m ? &mWu : &mWg, sBar + B_FFN, (b * 36) & ~7, (fb - m * 12) * 48);
              }
            }
          } else {
#pragma unroll 1
            for (int f = g * 3; f < g * 3 + 3; f++) tma_load_2d(sb + g * 1024 + f * 5120, &mWd, sBar + B_FFN, f * 64, b * 36);
          }
          if (++g == 6) { g = 0; par ^= 1; }
        }
      }
    } else if (warp == 3) {
#pragma unroll 1
      for (int i = 0; i < 32; i++) {
        mbar_wait(sBar + B_FULLQ + (i & 7) * 8, (i >> 3) & 1);
        if ((i & 3) == 3) { KSTAMP(170 + (i >> 2) * 2); bar_sync(1, 288); KSTAMP(171 + (i >> 2) * 2); }
      }
#pragma unroll 1
      for (int u = 0; u < 128; u++) {
        const int t = (u == 0 || u == 127) ? u : (u & 1) ? u + 1 : u - 1;
        mbar_wait(sBar + B_FULLA + (t & 3) * 8, (t >> 2) & 1);
        if (!(t & 1) || t == 127) { KSTAMP((t + 1) & ~1); bar_sync(1, 288); KSTAMP(((t + 1) & ~1) + 1); }
        else { KSTAMP(190 + (t >> 1)); bar_sync(10, 160); }
      }
      int g = 0, par = 0;
      if (lane < 2) mbar_expect_tx(sBar + B_XF + lane * 8, 16384);
#pragma unroll 1
      for (int i = 0; i < 36; i++) {
        mbar_wait(sBar + B_FULLO + g * 8, par);
        if (++g == 6) { g = 0; par ^= 1; }
        if ((i & 3) == 3 && i > 3 && i < 35) {
          const uint32_t xf = sBar + B_XF + ((i - 4) & 4) * 2;
          KSTAMP(260 + (i >> 2));
          mbar_wait(xf, ((i - 4) >> 3) & 1);
          __syncwarp();
          if (lane == 0) mbar_expect_tx(xf, 16384);
        }
        if (i & 1) { KSTAMP(129 + i); bar_sync(1, 288); KSTAMP(130 + i); }
      }
    } else if (warp > 0) {
      const int st = tid - 32;
      mbar_wait(sBar + B_FULLQ, 0);
      mbar_wait(sBar + B_FULLQ, 1);
      const bf16* const kvp = (rank ? prm.v : prm.k) + ((size_t)kg * 4 * SK + qt * 128) * DH;
      if (st == 0) bulk_prefetch(kvp, 32768);
      mbar_wait(sBar + B_FULLA, 0);
      mbar_wait(sBar + B_FULLA, 1);
      if (warp == 1) {
#pragma unroll 1
        for (int grp = b; grp < 288; grp += 128) {
          float a[8];
#pragma unroll
          for (int i = 0; i < 8; i++) a[i] = 0.f;
#pragma unroll 2
          for (int r = lane; r < DM; r += 32) {
            uint4 v = __ldg(reinterpret_cast<const uint4*>(prm.w_mod + (size_t)r * (6 * DM) + 2 * DM + grp * 8));
            float s = silu_bf(__bfloat162float(prm.c[r]));
            a[0] += s * bf_lo(v.x); a[1] += s * bf_hi(v.x); a[2] += s * bf_lo(v.y); a[3] += s * bf_hi(v.y);
            a[4] += s * bf_lo(v.z); a[5] += s * bf_hi(v.z); a[6] += s * bf_lo(v.w); a[7] += s * bf_hi(v.w);
          }
#pragma unroll
          for (int i = 0; i < 8; i++) a[i] = warp_sum(a[i]);
          if (lane == 0) {
            const int kind = grp / 72, cp = (grp - kind * 72) * 4;
#pragma unroll
            for (int i = 0; i < 4; i++) {
              uint32_t w = pack_bf16(a[2 * i], a[2 * i + 1]);
              if (kind == 2) w = hadd2(w, 0x3f803f80u);
              reinterpret_cast<uint32_t*>(g_mod2)[(cp + i) * 4 + kind] = w;
            }
          }
        }
        __syncwarp();
        if (lane == 0) cnt_arrive(C_SIDE);
        {
          if (lane == 0) asm volatile("mbarrier.arrive.shared::cta.b64 _, [%0];" ::"r"(sBar + B_XF) : "memory");
          int ch = kg * 2;
#pragma unroll 1
          for (int k = 0; k < 14; k++) {
            bar_sync(8 + (k & 1), 160);
            if (lane == 0) {
              asm volatile("cp.reduce.async.bulk.global.shared::cta.bulk_group.add.f32 [%0], [%1], 8192;" ::"l"(g_acc + ((qt * 2 + (k & 1)) * 72 + ch * 8 + rank * 4) * 128),
                           "r"(sb + SM_OUT + (k & 3) * 8192) : "memory");
              if (k & 1) {
                asm volatile("cp.async.bulk.commit_group;\ncp.async.bulk.wait_group.read 1;" ::: "memory");
                asm volatile("mbarrier.arrive.shared::cta.b64 _, [%0];" ::"r"(sBar + B_XF + ((k & 2) ? 0 : 8)) : "memory");
                if (++ch == 9) ch = 0;
              }
            }
            __syncwarp();
          }
        }
        PSTAMP(32, 56);
        if (lane == 0) {
          asm volatile("cp.async.bulk.wait_group.read 0;" ::: "memory");
          asm volatile("mbarrier.arrive.shared::cta.b64 _, [%0];" ::"r"(sBar + B_RD) : "memory");
          asm volatile("cp.async.bulk.wait_group 0;" ::: "memory");
          PSTAMP(32, 58);
        }
        __syncwarp();
        if (lane < 8) asm volatile("red.relaxed.gpu.global.add.u32 [%0], 1;" ::"l"(&g_cnt[(C_Q + qt * 8 + lane) * 32]) : "memory");
        if (lane == 0) {
          PSTAMP(32, 57);
          cnt_wait(C_Q + qt * 8 + hg, 16);
          mbar_wait(sBar + B_MD, 0);
        }
        __syncwarp();
        PSTAMP(32, 59);
        bar_arrive(11, 288);
        uint32_t k1 = 0, k2 = 0;
        uint4 hv[5];
        auto h_load = [&]() {
          const int r1 = ~k1 & (SQ - 1), r2 = ~k2 & (SQ - 1);
          const int c1 = ((r1 >> 5) & 3) * 32 + (r1 >> 7) * 2 + ((r1 >> 4) & 1), c2 = ((r2 >> 5) & 3) * 32 + (r2 >> 7) * 2 + ((r2 >> 4) & 1);
          const int o1 = c1 * 288, o2 = c2 * 288 + (c1 == c2 ? 144 : 0) - 72;
#pragma unroll
          for (int i = 0; i < 5; i++) {
            const int e = i * 32 + lane;
            if (i < 4 || lane < 16) hv[i] = ldr4(g_ones + F_HX + (e < 72 ? o1 : o2) + e);
          }
        };
#pragma unroll
        for (int i = 0; i < 5; i++) hv[i] = make_uint4(0u, 0u, 0u, 0u);
        const uint4* kp = g_zero + Z_KEY + (b & 31) * 64 + lane * 2;
        auto merge = [](uint32_t& m1, uint32_t& m2, uint32_t n1, uint32_t n2) { m2 = max(min(m1, n1), max(m2, n2)); m1 = max(m1, n1); };
#pragma unroll 1
        for (uint32_t n = 0;; n++) {
          uint4 a = ldr4(kp);
          const uint4 c = ldr4(kp + 1);
          const bool all = __all_sync(~0u, a.x && a.y && a.z && a.w && c.x && c.y && c.z && c.w);
          merge(a.x, a.y, a.z, a.w);
          merge(a.x, a.y, c.x, c.y);
          merge(a.x, a.y, c.z, c.w);
          const uint32_t m1 = __reduce_max_sync(~0u, a.x);
          const uint32_t m2 = __reduce_max_sync(~0u, a.x == m1 ? a.y : a.x);
          bool bad = m1 != k1 || m2 != k2;
#pragma unroll
          for (int i = 0; i < 5; i++) bad |= unset(hv[i]);
          bad = __any_sync(~0u, bad);
          if (all && !bad) break;
          if (n > (1u << 15)) { SETERR(4); break; }
          if (bad) { k1 = m1; k2 = m2; h_load(); }
        }
        PSTAMP(32, 60);
#pragma unroll
        for (int i = 0; i < 5; i++)
          if (i < 4 || lane < 16) sts128(sb + SM_T + 4096 + (i * 32 + lane) * 16, hv[i]);
        if (lane == 0) asm volatile("st.shared.v2.b32 [%0], {%1,%2};" ::"r"(sb + SM_T + 128), "r"(k1), "r"(k2) : "memory");
        PSTAMP(32, 61);
        bar_arrive(12, 288);
      } else {
#pragma unroll
        for (int i = 0; i < 4; i++) sts128(sb + SM_FILL + i * 512 + lane * 16, i < 2 ? make_uint4(0u, 0u, 0u, 0u) : make_uint4(~0u, ~0u, ~0u, ~0u));
        fence_async();
        __syncwarp();
#pragma unroll 1
        for (int p = 2; p < FILLP; p++) {
          mbar_wait(sBar + B_FULLA, p & 1);
          if (lane == 0) {
            if ((p & 7) == 3 && p < 24) bulk_prefetch(kvp + (size_t)((p >> 3) + 1) * SK * DH, 32768);
            if (p == 17) bulk_prefetch(prm.wo + ((size_t)kg * 1024 + (b & 31) * 32) * DM, 32 * DM * 2);
            if (p >= PF0 && p < PF0 + 9) {
              const int i = p - PF0, m = i / 3;
              bulk_prefetch((m == 0 ? prm.wg : m == 1 ? prm.wu : prm.wd) + (size_t)(b * 3 + i - m * 3) * (DM * 12), DM * 24);
            }
          }
          __syncwarp();
          if (p >= FILL0 && lane < FILLN) {
            const int i = (p - FILL0) * FILLN + lane;
            if (i < (Z_N + F_N) / 64)
              asm volatile("cp.async.bulk.global.shared::cta.bulk_group [%0], [%1], 1024;" ::"l"(i < Z_N / 64 ? g_zero + b * Z_N + i * 64 : g_ones + b * F_N - Z_N + i * 64),
                           "r"(sb + SM_FILL + (i < Z_N / 64 ? 0 : 1024)) : "memory");
          }
        }
        asm volatile("cp.async.bulk.commit_group;\ncp.async.bulk.wait_group 0;\nfence.proxy.async;" ::: "memory");
        __syncwarp();
        PSTAMP(64, 51);
        if (lane == 0) {
          cnt_arrive(C_SIDE);
          PSTAMP(64, 52);
          cnt_wait(C_SIDE, 128 * 2);
          PSTAMP(64, 53);
          asm volatile("mbarrier.arrive.shared::cta.b64 _, [%0];" ::"r"(sBar + B_X) : "memory");
        }
        __syncwarp();
      }
    }
  } else {
    const int cw = (warp >> 2) - 1;
    const int w8 = warp - 4;
    const int ct = tid - 128;
    const int g = lane >> 2, t4 = lane & 3;
    uint32_t relBar;
    asm volatile("mapa.shared::cluster.u32 %0, %1, %2;" : "=r"(relBar) : "r"(sBar), "r"(rank ^ (lane & 1)));
    auto release = [&](int off) {
      if (lane < 2) mbar_arrive_cl(relBar + off);
    };
    auto release1 = [&](int off) {
      if (lane == 0) mbar_arrive_cl(relBar + off);
    };
    auto turn_begin = [&]() { bar_sync(1 + cw, 288 - cw * 32); wgmma_fence(); };
    auto turn_end = [&]() { bar_arrive(2 - cw, 256 + cw * 32); };
    STAMP(0); GSTAMP(90);
    CL_WAIT();
    asm volatile("setmaxnreg.inc.sync.aligned.u32 232;");
    float S[64], O[64];
    uint32_t P[32], Qf[32];
    constexpr uint32_t dB_k = mk_desc(SM_BASE, 16);
    constexpr uint32_t dB_n16 = mk_desc(SM_BASE, 16384);
    uint4* const qpark = g_q + (size_t)b * (4 * 8 * 256) + ct;
    {
      uint32_t A[144];
      const uint32_t la = sb + (w8 * 16 + (lane & 15)) * 128 + (((lane >> 4) ^ (lane & 7)) << 4);
      mbar_wait(sBar + B_X, 0);
      wq_prefetch(WQPF1);
      STAMP(1);
#pragma unroll
      for (int k = 0; k < 36; k++) {
        uint32_t a[4];
        ldsm4(a, (la ^ ((k & 3) << 5)) + (k >> 2) * 16384);
        A[k * 4] = a[0]; A[k * 4 + 1] = a[1]; A[k * 4 + 2] = a[2]; A[k * 4 + 3] = a[3];
      }
      const uint32_t one = 0x3f803f80u;
      float c[4][4];
#pragma unroll
      for (int i = 0; i < 16; i++) c[i >> 2][i & 3] = 0.f;
#pragma unroll
      for (int k = 0; k < 36; k++) mma16816(c[k & 3], A[k * 4], A[k * 4 + 1], A[k * 4 + 2], A[k * 4 + 3], one, one);
      if (lane < 12) mbar_arrive_cl(lane < 4 ? relBar + B_EMPTYA + (lane >> 1) * 8 : sBar + B_EMPTYQ + (lane - 4) * 8);
      const float mA = ((c[0][0] + c[1][0]) + (c[2][0] + c[3][0])) * (1.f / DM), mB = ((c[0][2] + c[1][2]) + (c[2][2] + c[3][2])) * (1.f / DM);
      if (cw == 1) bar_sync(7, 256);
      uint32_t zero;
      asm volatile("ld.shared.b32 %0, [%1];" : "=r"(zero) : "r"(sb + SM_ZERO) : "memory");
      const uint32_t nA = pack_bf16(-mA, -mA) | zero, nB = pack_bf16(-mB, -mB) | zero;
      const float eA = mA + bf_lo(nA), eB = mB + bf_lo(nB);
#pragma unroll
      for (int i = 0; i < 16; i++) c[i >> 2][i & 3] = 0.f;
#pragma unroll
      for (int k = 0; k < 36; k++) {
        A[k * 4] = hadd2(A[k * 4], nA); A[k * 4 + 1] = hadd2(A[k * 4 + 1], nB); A[k * 4 + 2] = hadd2(A[k * 4 + 2], nA); A[k * 4 + 3] = hadd2(A[k * 4 + 3], nB);
        mma16816(c[k & 3], hmul2(A[k * 4], A[k * 4]), hmul2(A[k * 4 + 1], A[k * 4 + 1]), hmul2(A[k * 4 + 2], A[k * 4 + 2]), hmul2(A[k * 4 + 3], A[k * 4 + 3]), one, one);
      }
      const float vA = (c[0][0] + c[1][0]) + (c[2][0] + c[3][0]), vB = (c[0][2] + c[1][2]) + (c[2][2] + c[3][2]);
      const float rA = rsqrtf(fmaxf(vA * (1.f / DM) - eA * eA, 0.f) + 1e-5f), rB = rsqrtf(fmaxf(vB * (1.f / DM) - eB * eB, 0.f) + 1e-5f);
      const uint32_t hA = pack_bf16(rA, rA), hB = pack_bf16(rB, rB);
      const uint32_t lA = pack_bf16(rA - bf_lo(hA), rA - bf_lo(hA)), lB = pack_bf16(rB - bf_lo(hB), rB - bf_lo(hB));
      const uint32_t oA = pack_bf16(-eA * rA, -eA * rA), oB = pack_bf16(-eB * rB, -eB * rB);
#pragma unroll
      for (int i = 0; i < 144; i++) A[i] = hfma2(A[i], (i & 1) ? hB : hA, hfma2(A[i], (i & 1) ? lB : lA, (i & 1) ? oB : oA));
      asm volatile("st.shared.b32 [%0], %1;" ::"r"(sb + SM_ZERO + 4), "r"(A[143] ^ A[100]) : "memory");
      if (cw == 0) bar_arrive(7, 256);
      STAMP(2);
      bar_sync(3 + cw, 224);
      wq_prefetch(WQPF2);
      STAMP(3);
#pragma unroll
      for (int k = 0; k < 72; k++) {
        const uint2 m = *reinterpret_cast<const uint2*>(smem_raw + SM_MOD + (k * 4 + t4) * 8);
        A[k * 2] = hfma2(A[k * 2], m.y, m.x); A[k * 2 + 1] = hfma2(A[k * 2 + 1], m.y, m.x);
      }
      STAMP(4);
      float qa[32];
      if (cw == 0) bar_arrive(1, 288);
#pragma unroll 1
      for (int hh = 2;; hh++) {
        const int gr = (hh & 1) * 4;
#pragma unroll
        for (int p = 0; p < 4; p++) {
          if (p == 0) turn_begin();
          const uint32_t db = dB_k + (SM_QR >> 4) + (gr + p) * 1152;
#pragma unroll
          for (int kk = 0; kk < 9; kk++)
            wgmma64_rs(qa, A[p * 36 + kk * 4], A[p * 36 + kk * 4 + 1], A[p * 36 + kk * 4 + 2], A[p * 36 + kk * 4 + 3], db + kk * 128, (p | kk) != 0);
        }
        wgmma_commit();
        turn_end();
        wgmma_wait<0>();
        if (lane < 4) mbar_arrive_cl(sBar + B_EMPTYQ + (gr + lane) * 8);
        if (hh == 8 && lane < 4) mbar_arrive_cl(relBar + B_EMPTYA + 16 + (lane >> 1) * 8);
#pragma unroll
        for (int j = 0; j < 4; j++)
          qpark[((hh & 7) * 4 + j) * 256] = make_uint4(pack_bf16(qa[8 * j], qa[8 * j + 1]), pack_bf16(qa[8 * j + 2], qa[8 * j + 3]),
                                                       pack_bf16(qa[8 * j + 4], qa[8 * j + 5]), pack_bf16(qa[8 * j + 6], qa[8 * j + 7]));
        if (hh == 9) break;
      }
#pragma unroll
      for (int j = 0; j < 4; j++) {
        const uint4 v = __ldcg(qpark + j * 256);
        Qf[4 * j] = v.x; Qf[4 * j + 1] = v.y; Qf[4 * j + 2] = v.z; Qf[4 * j + 3] = v.w;
      }
#pragma unroll
      for (int j = 0; j < 16; j++) Qf[16 + j] = pack_bf16(qa[2 * j], qa[2 * j + 1]);
    }
    STAMP(5);
    const float sc = 0.08838834764831845f * 1.4426950408889634f;
    float mb0 = 0.f, mb1 = 0.f, l0 = 0.f, l1 = 0.f;
    float i0, i1;
    auto o_scale = [&]() {
      float a0 = l0, a1 = l1;
      a0 += __shfl_xor_sync(~0u, a0, 1); a0 += __shfl_xor_sync(~0u, a0, 2);
      a1 += __shfl_xor_sync(~0u, a1, 1); a1 += __shfl_xor_sync(~0u, a1, 2);
      i0 = rcp(a0); i1 = rcp(a1);
    };
    auto o_frag = [&](int i) {
      return make_uint4(pack_bf16(O[i * 8] * i0, O[i * 8 + 1] * i0), pack_bf16(O[i * 8 + 2] * i1, O[i * 8 + 3] * i1),
                        pack_bf16(O[i * 8 + 4] * i0, O[i * 8 + 5] * i0), pack_bf16(O[i * 8 + 6] * i1, O[i * 8 + 7] * i1));
    };
    auto row_max = [&](float& x0, float& x1) {
      float y0 = fmaxf(S[0], S[1]), y1 = fmaxf(S[2], S[3]), z0 = fmaxf(S[4], S[5]), z1 = fmaxf(S[6], S[7]);
#pragma unroll
      for (int j = 2; j < 16; j += 2) {
        y0 = fmaxf(y0, fmaxf(S[j * 4], S[j * 4 + 1])); y1 = fmaxf(y1, fmaxf(S[j * 4 + 2], S[j * 4 + 3]));
        z0 = fmaxf(z0, fmaxf(S[j * 4 + 4], S[j * 4 + 5])); z1 = fmaxf(z1, fmaxf(S[j * 4 + 6], S[j * 4 + 7]));
      }
      x0 = fmaxf(y0, z0); x1 = fmaxf(y1, z1);
      x0 = fmaxf(x0, __shfl_xor_sync(~0u, x0, 1)); x1 = fmaxf(x1, __shfl_xor_sync(~0u, x1, 1));
      x0 = fmaxf(x0, __shfl_xor_sync(~0u, x0, 2)); x1 = fmaxf(x1, __shfl_xor_sync(~0u, x1, 2));
    };
    float s0, s1;
    auto exps = [&](int j0, int j1) {
#pragma unroll
      for (int j = j0; j < j1; j++) {
        S[j * 4] = ex2(fmaf(S[j * 4], sc, -mb0)); S[j * 4 + 1] = ex2(fmaf(S[j * 4 + 1], sc, -mb0));
        S[j * 4 + 2] = ex2(fmaf(S[j * 4 + 2], sc, -mb1)); S[j * 4 + 3] = ex2(fmaf(S[j * 4 + 3], sc, -mb1));
        s0 += S[j * 4] + S[j * 4 + 1]; s1 += S[j * 4 + 2] + S[j * 4 + 3];
      }
    };
    auto cvtP = [&]() {
#pragma unroll
      for (int i = 0; i < 32; i++) P[i] = pack_bf16(S[2 * i], S[2 * i + 1]);
    };
    auto issue_qk = [&](int ks) {
      const uint32_t db = dB_k + ((ks * 32768) >> 4);
#pragma unroll
      for (int kk = 0; kk < 8; kk++)
        wgmma128_rs<0>(S, Qf[kk * 4], Qf[kk * 4 + 1], Qf[kk * 4 + 2], Qf[kk * 4 + 3], db + (kk >> 2) * 1024 + (kk & 3) * 2, kk != 0);
    };
    auto issue_pv = [&](int vs, int first) {
      const uint32_t db = dB_n16 + ((vs * 32768) >> 4);
#pragma unroll
      for (int kk = 0; kk < 8; kk++)
        wgmma128_rs<1>(O, P[kk * 4], P[kk * 4 + 1], P[kk * 4 + 2], P[kk * 4 + 3], db + kk * 128, kk ? 1 : !first);
    };
    auto sched_fence = [&]() {
      asm volatile("st.shared.f32 [%0], %1;" ::"r"(sb + SM_RED + lane * 4), "f"(S[31]) : "memory");
    };
#pragma unroll 1
    for (int h = 0; h < 4; h++) {
      {
        STAMP(6 + h * 16);
        turn_begin();
        issue_qk(0);
        wgmma_commit();
        if (h > 0) { if (cw == 0) bar_sync(10, 160); issue_pv(3, 0); wgmma_commit(); }
        else asm volatile("wgmma.commit_group.sync.aligned; // empty" ::: "memory");
        turn_end();
        wgmma_wait<1>();
        release(B_EMPTYA);
        s0 = 0.f; s1 = 0.f;
        float x0, x1;
        row_max(x0, x1);
        mb0 = x0 * sc; mb1 = x1 * sc;
        exps(0, 8);
        sched_fence();
        wgmma_wait<0>();
        if (h > 0) {
          release(B_EMPTYA + 24);
          o_scale();
#pragma unroll
          for (int i = 0; i < 8; i++) sts128(sb + SM_STASH + (h - 1) * 32768 + i * 4096 + ct * 16, o_frag(i));
        }
        exps(8, 16);
        cvtP();
        l0 = s0; l1 = s1;
      }
#pragma unroll 1
      for (int j = 1; j < 16; j++) {
        const int ks = (j & 1) * 2, vs = 3 - ks;
        turn_begin();
        issue_qk(ks);
        wgmma_commit();
        if (cw == 0) bar_sync(10, 160);
        issue_pv(vs, j == 1);
        wgmma_commit();
        turn_end();
        wgmma_wait<1>();
        release(B_EMPTYA + ks * 8);
        if (j == 15 && h < 3) {
          const uint4* qp = qpark + (h + 1) * (8 * 256);
#pragma unroll
          for (int i = 0; i < 8; i++) {
            uint4 v = __ldcg(qp + i * 256);
            Qf[4 * i] = v.x; Qf[4 * i + 1] = v.y; Qf[4 * i + 2] = v.z; Qf[4 * i + 3] = v.w;
          }
        }
        s0 = 0.f; s1 = 0.f;
        exps(0, 8);
        sched_fence();
        wgmma_wait<0>();
        release(B_EMPTYA + vs * 8);
        bool bad = __any_sync(~0u, !(s0 <= LAZY_LIMIT && s1 <= LAZY_LIMIT));
        if (__builtin_expect(!bad, 1)) {
          exps(8, 16);
          cvtP();
          bad = __any_sync(~0u, !(s0 <= LAZY_LIMIT && s1 <= LAZY_LIMIT));
        }
        if (__builtin_expect(bad, 0)) {
          const uint32_t* kp = reinterpret_cast<const uint32_t*>(prm.k + ((size_t)(kg * 4 + h) * SK + j * 128 + g) * DH) + t4;
          const uint4* qp = qpark + h * (8 * 256);
          float4 tmp[16];
#pragma unroll 1
          for (int jn = 0; jn < 16; jn++) {
            float c[4] = {0.f, 0.f, 0.f, 0.f};
#pragma unroll 1
            for (int kk = 0; kk < 8; kk++) {
              const uint4 a = __ldcg(qp + kk * 256);
              mma16816(c, a.x, a.y, a.z, a.w, __ldg(kp + jn * 512 + kk * 8), __ldg(kp + jn * 512 + kk * 8 + 4));
            }
            tmp[jn] = make_float4(c[0], c[1], c[2], c[3]);
          }
#pragma unroll
          for (int jn = 0; jn < 16; jn++) { const float4 c = tmp[jn]; S[jn * 4] = c.x; S[jn * 4 + 1] = c.y; S[jn * 4 + 2] = c.z; S[jn * 4 + 3] = c.w; }
          float x0, x1;
          row_max(x0, x1);
          const float n0 = fmaxf(mb0, x0 * sc), n1 = fmaxf(mb1, x1 * sc);
          const float f0 = ex2(mb0 - n0), f1 = ex2(mb1 - n1);
          mb0 = n0; mb1 = n1;
          l0 *= f0; l1 *= f1;
#pragma unroll
          for (int i = 0; i < 16; i++) { O[i * 4] *= f0; O[i * 4 + 1] *= f0; O[i * 4 + 2] *= f1; O[i * 4 + 3] *= f1; }
          s0 = 0.f; s1 = 0.f;
          exps(0, 16);
          cvtP();
        }
        l0 += s0; l1 += s1;
      }
    }
    STAMP(70);
    turn_begin();
    issue_pv(3, 0);
    wgmma_commit();
    turn_end();
    {
      uint32_t A[128];
#pragma unroll
      for (int i = 0; i < 16; i++) {
        const uint4 v = lds128(sb + SM_STASH + i * 4096 + ct * 16);
        A[i * 4] = v.x; A[i * 4 + 1] = v.y; A[i * 4 + 2] = v.z; A[i * 4 + 3] = v.w;
      }
      o_scale();
      wgmma_wait<0>();
      release(B_EMPTYA + 24);
#pragma unroll
      for (int i = 16; i < 24; i++) {
        const uint4 v = lds128(sb + SM_STASH + i * 4096 + ct * 16);
        A[i * 4] = v.x; A[i * 4 + 1] = v.y; A[i * 4 + 2] = v.z; A[i * 4 + 3] = v.w;
      }
#pragma unroll
      for (int i = 0; i < 8; i++) {
        const uint4 v = o_frag(i);
        A[96 + i * 4] = v.x; A[96 + i * 4 + 1] = v.y; A[96 + i * 4 + 2] = v.z; A[96 + i * 4 + 3] = v.w;
      }
      if (__any_sync(~0u, A[95] != 0x12345678u || A[64] != 0x9abcdef0u || lane == 0)) release1(B_ST);
      STAMP(71);
      const uint32_t xb = sb + SM_XCH + cw * 8192 + (w8 & 3) * 512 + lane * 16;
      const uint32_t peer = __shfl_sync(~0u, relBar, 1) - sBar;
      float c0[32], c1[32];
      int gr = 0;
      auto send = [&](const float* v, int xp) {
#pragma unroll
        for (int j = 0; j < 4; j++)
          asm volatile("st.async.shared::cluster.mbarrier::complete_tx::bytes.v4.f32 [%0], {%1,%2,%3,%4}, [%5];" ::"r"(xb + peer + xp * 16384 + j * 2048),
                       "f"(v[j * 4]), "f"(v[j * 4 + 1]), "f"(v[j * 4 + 2]), "f"(v[j * 4 + 3]), "r"(sBar + B_XF + xp * 8 + peer) : "memory");
      };
      uint4* const hand = g_ones + F_P + (qt * 24 + cw) * 1024 + (w8 & 3) * 32 + lane;
      auto st4 = [&](uint4* q, float x, float y, float z, float w) {
        asm volatile("st.relaxed.gpu.global.v4.f32 [%0], {%1,%2,%3,%4};" ::"l"(q), "f"(x), "f"(y), "f"(z), "f"(w) : "memory");
      };
      auto recv = [&](const float* v, int xp, bool last) {
        uint4 u[4];
#pragma unroll
        for (int j = 0; j < 4; j++) u[j] = lds128(xb + xp * 16384 + j * 2048);
#pragma unroll
        for (int j = 0; j < 4; j++) {
          const float x = v[j * 4] + __uint_as_float(u[j].x), y = v[j * 4 + 1] + __uint_as_float(u[j].y), z = v[j * 4 + 2] + __uint_as_float(u[j].z), w = v[j * 4 + 3] + __uint_as_float(u[j].w);
          if (last) st4(hand + kg * 2048 + rank * 512 + j * 128, x, y, z, w);
          else sts128(xb + (SM_OUT - SM_XCH) + xp * 16384 + j * 2048, make_uint4(__float_as_uint(x), __float_as_uint(y), __float_as_uint(z), __float_as_uint(w)));
        }
      };
      auto chunk = [&](float (&acc)[32], float (&prev)[32], bool has_prev, bool last, int xp) {
#pragma unroll
        for (int hd = 0; hd < 4; hd++) {
          if (!(hd & 1)) turn_begin();
          const uint32_t db = dB_k + (gr + (hd & 1)) * 1024;
#pragma unroll
          for (int kk = 0; kk < 8; kk++)
            wgmma64_rs(acc, A[hd * 32 + kk * 4], A[hd * 32 + kk * 4 + 1], A[hd * 32 + kk * 4 + 2], A[hd * 32 + kk * 4 + 3], db + kk * 128, (hd | kk) != 0);
          wgmma_commit();
          if (hd & 1) {
            if (hd == 1 || !last || cw == 0) turn_end();
            if (hd == 1 && last) {
              mbar_wait(sBar + B_XF + 8, 1);
              if (rank) recv(prev + 16, 1, true); else recv(prev, 1, true);
            }
            if (hd == 3 && has_prev && !last) {
              if (rank) recv(prev + 16, xp ^ 1, false); else recv(prev, xp ^ 1, false);
              fence_async();
              bar_arrive(8 + cw, 160);
            }
            wgmma_wait<1>();
            release1(B_EMPTYO + gr * 8);
            wgmma_wait<0>();
            release1(B_EMPTYO + gr * 8 + 8);
            if ((gr += 2) == 6) gr = 0;
          }
        }
        if (!last) {
          if (!has_prev) mbar_wait(sBar + B_EMPTYA + 24, 0);
          if (rank) send(acc, xp); else send(acc + 16, xp);
        }
      };
#pragma unroll 1
      for (int cp = 0;; cp++) {
        chunk(c0, c1, cp != 0, cp == 4, 0);
        if (cp == 4) break;
        chunk(c1, c0, true, false, 1);
      }
      STAMP(72);
#pragma unroll
      for (int jb = 0; jb < 8; jb++) st4(hand + (4 + hg) * 2048 + jb * 128, c0[jb * 4], c0[jb * 4 + 1], c0[jb * 4 + 2], c0[jb * 4 + 3]);
      if (lane == 0) asm volatile("red.relaxed.gpu.global.add.u32 [%0], 1;" ::"l"(&g_cnt[(C_Q + qt * 8 + w8) * 32]) : "memory");
    }
    STAMP(73);
    uint32_t* const tsu = reinterpret_cast<uint32_t*>(smem_raw + SM_T);
    float* const tsf = reinterpret_cast<float*>(smem_raw + SM_T);
    const int rowA = qt * 128 + hg * 16 + w8;
    const size_t oA = (size_t)rowA * (DM / 2) + lane, oB = oA + 8 * (DM / 2);
    uint32_t ya[9], yb[9];
    bool topA, topB;
    {
      uint32_t xa[9], xb[9], wr[9];
      uint4 md[9];
      {
        const int fo = w8 * 128 + (hg & 3) * 32 + lane;
        const uint4* pp = g_ones + F_P + (qt * 24 + (hg >> 2)) * 1024 + fo;
        uint4 pv[12];
#pragma unroll
        for (int i = 0; i < 9; i++) {
          xa[i] = __ldg(reinterpret_cast<const uint32_t*>(prm.x) + oA + i * 32);
          xb[i] = __ldg(reinterpret_cast<const uint32_t*>(prm.x) + oB + i * 32);
        }
        bar_sync(11, 288);
        STAMP(74);
        const float4* ap = g_acc + (size_t)(qt * 2 + (hg >> 2)) * 72 * 128 + fo;
        float4 av[9];
#pragma unroll
        for (int i = 0; i < 9; i++) av[i] = __ldcg(ap + i * 1024);
#pragma unroll
        for (int i = 0; i < 12; i++) pv[i] = ldr4(pp + i * 2048);
#pragma unroll
        for (int i = 0; i < 9; i++) {
          md[i] = lds128(sb + SM_MD + (lane + i * 32) * 16);
          wr[i] = *reinterpret_cast<const uint32_t*>(smem_raw + SM_MD + 4608 + (lane + i * 32) * 4);
        }
#pragma unroll 1
        for (uint32_t n = 0;; n++) {
          bool bad = false;
#pragma unroll
          for (int i = 0; i < 12; i++) bad |= unset(pv[i]);
          if (!__any_sync(~0u, bad)) break;
          if (n > (1u << 15)) { SETERR(8); break; }
#pragma unroll
          for (int i = 0; i < 12; i++) pv[i] = ldr4(pp + i * 2048);
        }
        STAMP(40);
#pragma unroll
        for (int i = 0; i < 4; i++) {
          float4& a = av[(2 * i + 8) % 9];
          float4& c = av[(2 * i + 7) % 9];
          const uint4 &u = pv[4 + 2 * i], &v = pv[5 + 2 * i], &w = pv[i];
          a.x += __uint_as_float(u.x) + __uint_as_float(v.x); a.y += __uint_as_float(u.y) + __uint_as_float(v.y);
          a.z += __uint_as_float(u.z) + __uint_as_float(v.z); a.w += __uint_as_float(u.w) + __uint_as_float(v.w);
          c.x += __uint_as_float(w.x); c.y += __uint_as_float(w.y); c.z += __uint_as_float(w.z); c.w += __uint_as_float(w.w);
        }
        uint32_t* const tr = tsu + 2048;
#pragma unroll
        for (int i = 0; i < 9; i++) {
          tr[g * 292 + i * 32 + w8 * 4 + t4] = pack_bf16(av[i].x, av[i].y);
          tr[(g + 8) * 292 + i * 32 + w8 * 4 + t4] = pack_bf16(av[i].z, av[i].w);
        }
        bar_sync(5, 256);
        STAMP(44);
#pragma unroll
        for (int i = 0; i < 9; i++) {
          xa[i] = hadd2(xa[i], hmul2(md[i].x, tr[w8 * 292 + i * 32 + lane]));
          xb[i] = hadd2(xb[i], hmul2(md[i].x, tr[(w8 + 8) * 292 + i * 32 + lane]));
        }
      }
      const uint32_t piv = __shfl_sync(~0u, __byte_perm(xa[0], xb[0], 0x5410), 0);
      const float pA = bf_lo(piv), pB = bf_hi(piv);
      float sA = 0.f, sB = 0.f, qA = 0.f, qB = 0.f;
#pragma unroll
      for (int i = 0; i < 9; i++) {
        const float d0 = bf_lo(xa[i]) - pA, d1 = bf_hi(xa[i]) - pA, d2 = bf_lo(xb[i]) - pB, d3 = bf_hi(xb[i]) - pB;
        sA += d0 + d1; sB += d2 + d3;
        qA = fmaf(d0, d0, fmaf(d1, d1, qA)); qB = fmaf(d2, d2, fmaf(d3, d3, qB));
      }
#pragma unroll
      for (int o = 16; o; o >>= 1) {
        sA += __shfl_xor_sync(~0u, sA, o); sB += __shfl_xor_sync(~0u, sB, o);
        qA += __shfl_xor_sync(~0u, qA, o); qB += __shfl_xor_sync(~0u, qB, o);
      }
      sA *= 1.f / DM; sB *= 1.f / DM;
      const float rA = rcp(bfr(sqrt_a(bfr(bfr(fmaxf(qA * (1.f / DM) - sA * sA, 0.f)) + 1e-5f))));
      const float rB = rcp(bfr(sqrt_a(bfr(bfr(fmaxf(qB * (1.f / DM) - sB * sB, 0.f)) + 1e-5f))));
      const uint32_t nmA = pack_bf16(-(pA + sA), -(pA + sA)), nmB = pack_bf16(-(pB + sB), -(pB + sB));
      sA = 0.f; sB = 0.f;
      uint32_t ha[9], hb[9];
#pragma unroll
      for (int i = 0; i < 9; i++) {
        const uint32_t da = hadd2(xa[i], nmA), db = hadd2(xb[i], nmB);
        ha[i] = hadd2(hmul2(pack_bf16(bf_lo(da) * rA, bf_hi(da) * rA), md[i].z), md[i].y);
        hb[i] = hadd2(hmul2(pack_bf16(bf_lo(db) * rB, bf_hi(db) * rB), md[i].z), md[i].y);
        const float w0 = bf_lo(wr[i]), w1 = bf_hi(wr[i]);
        sA += bf_lo(ha[i]) * w0 + bf_hi(ha[i]) * w1; sB += bf_lo(hb[i]) * w0 + bf_hi(hb[i]) * w1;
      }
      const uint32_t rr = pack_bf16(warp_sum(sA), warp_sum(sB));
      uint32_t u = ((lane & 1) ? rr : rr << 16) & 0xffff0000u;
      u = ((u & 0x7fff0000u) > 0x7f800000u) ? 0u : (u ^ ((u >> 31) ? 0xffff0000u : 0x80000000u));
      u |= 0xffffu - (rowA + (lane & 1) * 8);
      if (lane < 2) tsu[w8 * 2 + lane] = u;
      STAMP(41);
      bar_sync(5, 256);
      const uint32_t v = tsu[lane & 15];
      const uint32_t m1 = __reduce_max_sync(~0u, v), m2 = __reduce_max_sync(~0u, v == m1 ? 0u : v);
      if (w8 == 7) asm volatile("st.relaxed.gpu.global.v2.u32 [%0], {%1,%2};" ::"l"(reinterpret_cast<uint2*>(g_zero + Z_KEY) + lane * 128 + b), "r"(m1), "r"(m2) : "memory");
      const int r1 = ~m1 & (SQ - 1), r2 = ~m2 & (SQ - 1);
      topA = rowA == r1 || rowA == r2; topB = rowA + 8 == r1 || rowA + 8 == r2;
      uint32_t* const hx = reinterpret_cast<uint32_t*>(g_ones + F_HX + b * 288) + lane;
      if (topA) {
#pragma unroll
        for (int i = 0; i < 9; i++) str1(hx + (rowA == r2) * 576 + i * 32, ha[i]);
#pragma unroll
        for (int i = 0; i < 9; i++) str1(hx + (rowA == r2) * 576 + 288 + i * 32, xa[i]);
      }
      if (topB) {
#pragma unroll
        for (int i = 0; i < 9; i++) str1(hx + (rowA + 8 == r2) * 576 + i * 32, hb[i]);
#pragma unroll
        for (int i = 0; i < 9; i++) str1(hx + (rowA + 8 == r2) * 576 + 288 + i * 32, xb[i]);
      }
#pragma unroll
      for (int i = 0; i < 9; i++) { ya[i] = hadd2(xa[i], hmul2(md[i].w, ha[i])); yb[i] = hadd2(xb[i], hmul2(md[i].w, hb[i])); }
    }
    auto out_rows = [&](bool a, bool c) {
      if (a) {
#pragma unroll
        for (int i = 0; i < 9; i++) reinterpret_cast<uint32_t*>(prm.out)[oA + i * 32] = ya[i];
      }
      if (c) {
#pragma unroll
        for (int i = 0; i < 9; i++) reinterpret_cast<uint32_t*>(prm.out)[oB + i * 32] = yb[i];
      }
    };
    STAMP(75);
    const int kq = w8 >> 1;
    const int ng = w8 < 2 ? 3 : 2;
    uint32_t bg[9][10], bd[12][5];
    mbar_wait(sBar + B_FFN, 0);
    STAMP(42);
    {
      const uint32_t wa = sb + ((w8 & 1) ? SM_WU : SM_WG) + (kq * 144 + (lane & 6) * 2 + ((lane >> 2) & 2) + (lane & 1)) * 80 + (lane >> 4) * 16;
#pragma unroll
      for (int ks = 0; ks < 9; ks++) {
        uint32_t b0[4], b1[4], b2[2];
        ldsm4t(b0, wa + ks * 1280); ldsm4t(b1, wa + ks * 1280 + 32); ldsm2t(b2, wa + ks * 1280 + 64 - (lane >> 4) * 16);
#pragma unroll
        for (int i = 0; i < 4; i++) { bg[ks][i] = b0[i]; bg[ks][4 + i] = b1[i]; }
        bg[ks][8] = b2[0]; bg[ks][9] = b2[1];
      }
#pragma unroll
      for (int i = 0; i < 12; i++) {
        if (i < 8 || ng == 3) {
          const int bx = (w8 >> 1) + (i >> 2) * 4;
          const uint32_t a = sb + bx * 5120 + (bx / 3) * 1024 + lane * 128 + (((((w8 & 1) * 4 + (i & 3)) ^ lane) & 7) << 4);
          uint32_t b0[4];
          ldsm4t(b0, a);
          asm volatile("ldmatrix.sync.aligned.m8n8.x1.trans.shared.b16 {%0}, [%1];" : "=r"(bd[i][4]) : "r"(a + 4096) : "memory");
#pragma unroll
          for (int j = 0; j < 4; j++) bd[i][j] = b0[j];
        }
      }
    }
    out_rows(!topA, !topB);
    STAMP(43);
    bar_sync(12, 288);
    STAMP(76);
    {
      float c[2][5][4];
#pragma unroll
      for (int i = 0; i < 10; i++) c[i & 1][i >> 1][0] = c[i & 1][i >> 1][1] = c[i & 1][i >> 1][2] = c[i & 1][i >> 1][3] = 0.f;
      const uint2* hp = reinterpret_cast<const uint2*>(smem_raw + SM_T + 4096) + (g & 1) * 144 + kq * 36 + t4;
#pragma unroll
      for (int ks = 0; ks < 9; ks++) {
        const uint2 a = hp[ks * 4];
#pragma unroll
        for (int i = 0; i < 5; i++) mma16816(c[ks & 1][i], a.x, 0u, a.y, 0u, bg[ks][2 * i], bg[ks][2 * i + 1]);
      }
      float* const part = tsf + 64;
      if (g < 2) {
#pragma unroll
        for (int i = 0; i < 5; i++)
          *reinterpret_cast<float2*>(part + w8 * 80 + g * 40 + i * 8 + t4 * 2) = make_float2(c[0][i][0] + c[1][i][0], c[0][i][1] + c[1][i][1]);
      }
      STAMP(45);
      bar_sync(5, 256);
      STAMP(46);
      auto act2 = [&](int f) {
        const float2* pp = reinterpret_cast<const float2*>(part + (g & 1) * 40 + f + (b & 1) * 4);
        const float2 g0 = pp[0], g1 = pp[80], g2 = pp[160], g3 = pp[240], u0 = pp[40], u1 = pp[120], u2 = pp[200], u3 = pp[280];
        return pack_bf16(silu_bf(bfr((g0.x + g1.x) + (g2.x + g3.x))) * bfr((u0.x + u1.x) + (u2.x + u3.x)),
                         silu_bf(bfr((g0.y + g1.y) + (g2.y + g3.y))) * bfr((u0.y + u1.y) + (u2.y + u3.y)));
      };
      const uint32_t v0 = act2((g >> 1) * 8 + t4 * 2), v1 = act2(32 + (t4 & 1) * 2);
      uint32_t a6[5];
#pragma unroll
      for (int i = 0; i < 4; i++) a6[i] = __shfl_sync(~0u, v0, i * 8 + (lane & 7));
      a6[4] = t4 < 2 ? v1 : 0u;
      STAMP(47);
      float* const yp = reinterpret_cast<float*>(g_ones + F_YP) + ((w8 * 2 + (g & 1)) * 128 + b) * 32 + (g >> 1) * 8 + t4 * 2;
#pragma unroll
      for (int m = 0; m < 3; m++) {
        if (m < 2 || ng == 3) {
          float y[4][4];
#pragma unroll
          for (int i = 0; i < 4; i++) {
            y[i][0] = y[i][1] = y[i][2] = y[i][3] = 0.f;
            mma16816(y[i], a6[0], 0u, a6[1], 0u, bd[m * 4 + i][0], bd[m * 4 + i][1]);
          }
#pragma unroll
          for (int i = 0; i < 4; i++) mma16816(y[i], a6[2], 0u, a6[3], 0u, bd[m * 4 + i][2], bd[m * 4 + i][3]);
#pragma unroll
          for (int i = 0; i < 4; i++) mma1688(y[i], a6[4], 0u, bd[m * 4 + i][4]);
          const bool u1 = lane & 8, u2 = lane & 16;
          const float y0 = u2 ? (u1 ? y[3][0] : y[2][0]) : (u1 ? y[1][0] : y[0][0]), y1 = u2 ? (u1 ? y[3][1] : y[2][1]) : (u1 ? y[1][1] : y[0][1]);
          asm volatile("st.relaxed.gpu.global.v2.f32 [%0], {%1,%2};" ::"l"(yp + m * (16 * 4096)), "f"(y0), "f"(y1) : "memory");
        }
      }
    }
    STAMP(78);
    const uint32_t k1 = tsu[32], k2 = tsu[33];
    const int row1 = ~k1 & (SQ - 1), row2 = ~k2 & (SQ - 1);
    out_rows(topA && rowA != row1 && rowA != row2, topB && rowA + 8 != row1 && rowA + 8 != row2);
    const int f = b + 128 * (7 - w8);
    if (f < 144) {
      const int tok = (f >> 2) & 1, col = ((f >> 3) * 4 + (f & 3)) * 8 + (lane & 1) * 4 + (lane & 2) + ((lane >> 2) & 1);
      const uint32_t key = tok ? k2 : k1;
      const int row = tok ? row2 : row1;
      const int c1 = ((row1 >> 5) & 3) * 32 + (row1 >> 7) * 2 + ((row1 >> 4) & 1), cr = ((row >> 5) & 3) * 32 + (row >> 7) * 2 + ((row >> 4) & 1);
      const uint16_t* xp = reinterpret_cast<const uint16_t*>(g_ones + F_HX + cr * 288 + (tok && c1 == cr ? 144 : 0) + 72) + col;
      const float gb = __uint_as_float((uint32_t)__ldcg(reinterpret_cast<const unsigned short*>(g_mod2) + (col >> 1) * 8 + 6 + (col & 1)) << 16);
      const float hv = __uint_as_float((uint32_t)reinterpret_cast<const uint16_t*>(smem_raw + SM_T + 4096)[tok * DM + col] << 16);
      const float r = __uint_as_float((key & 0xffff0000u) ^ ((key >> 31) ? 0x80000000u : 0xffff0000u));
      const float sg = bfr(rcp(1.f + __expf(-r)));
      const uint4* pp = g_ones + F_YP + (f >> 2) * 1024 + (f & 3) * 2 + (lane >> 1) * 8 + (lane & 1);
      uint4 pv[8];
      uint16_t xv;
      PSTAMP(352, 62);
#pragma unroll 1
      for (uint32_t n = 0;; n++) {
        asm volatile("ld.relaxed.gpu.global.u16 %0, [%1];" : "=h"(xv) : "l"(xp) : "memory");
#pragma unroll
        for (int i = 0; i < 8; i++) pv[i] = ldr4(pp + i * 128);
        bool bad = xv == 0xffff;
#pragma unroll
        for (int i = 0; i < 8; i++) bad |= unset(pv[i]);
        if (!bad) break;
        if (n > (1u << 15)) { SETERR(32); break; }
      }
      __syncwarp();
      PSTAMP(352, 63);
      float s[4];
#pragma unroll
      for (int j = 0; j < 4; j++) {
        auto w = [&](int i) { return __uint_as_float(j == 0 ? pv[i].x : j == 1 ? pv[i].y : j == 2 ? pv[i].z : pv[i].w); };
        s[j] = ((w(0) + w(1)) + (w(2) + w(3))) + ((w(4) + w(5)) + (w(6) + w(7)));
      }
      const bool u2 = lane & 2, u4 = lane & 4;
#pragma unroll
      for (int i = 0; i < 2; i++) { const float snd = u2 ? s[i] : s[i + 2], kp = u2 ? s[i + 2] : s[i]; s[i] = kp + __shfl_xor_sync(~0u, snd, 2); }
      { const float snd = u4 ? s[0] : s[1], kp = u4 ? s[1] : s[0]; s[0] = kp + __shfl_xor_sync(~0u, snd, 4); }
      s[0] += __shfl_xor_sync(~0u, s[0], 8);
      s[0] += __shfl_xor_sync(~0u, s[0], 16);
      const float hh = bfr(hv + bfr(bfr(s[0]) * sg));
      if (lane < 8) prm.out[(size_t)row * DM + col] = __float2bfloat16(__uint_as_float((uint32_t)xv << 16) + bfr(gb * hh));
      PSTAMP(352, 49);
    }
    if (w8 == 5 && lane < 9) g_mod1[b * 9 + lane] = make_uint4(0u, 0u, 0u, 0u);
    if (w8 == 5 && lane == 9) g_cnt[(C_Q + b) * 32] = 0;
    if (w8 == 5 && lane == 10 && b == 0) g_cnt[C_SIDE * 32] = 0;
    STAMP(79); GSTAMP(91);
  }
}

typedef CUresult (*PFN_enc)(CUtensorMap*, CUtensorMapDataType, cuuint32_t, void*, const cuuint64_t*, const cuuint64_t*,
                            const cuuint32_t*, const cuuint32_t*, CUtensorMapInterleave, CUtensorMapSwizzle,
                            CUtensorMapL2promotion, CUtensorMapFloatOOBfill);
static PFN_enc g_enc = nullptr;
static CUtensorMap mk_map(const void* p, uint64_t cols, uint64_t rows, uint32_t bc, uint32_t br, bool swz = true) {
  CUtensorMap m;
  cuuint64_t dims[2] = {cols, rows};
  cuuint64_t strides[1] = {cols * 2};
  cuuint32_t box[2] = {bc, br}, es[2] = {1, 1};
  g_enc(&m, CU_TENSOR_MAP_DATA_TYPE_BFLOAT16, 2, const_cast<void*>(p), dims, strides, box, es, CU_TENSOR_MAP_INTERLEAVE_NONE,
        swz ? CU_TENSOR_MAP_SWIZZLE_128B : CU_TENSOR_MAP_SWIZZLE_NONE, swz ? CU_TENSOR_MAP_L2_PROMOTION_L2_128B : CU_TENSOR_MAP_L2_PROMOTION_NONE,
        CU_TENSOR_MAP_FLOAT_OOB_FILL_NONE);
  return m;
}

extern "C" void kernel_launch(void* const* d_in, const int* in_sizes, int n_in, void* d_out, int out_size) {
  if (!g_enc) {
    cudaDriverEntryPointQueryResult st;
    cudaGetDriverEntryPoint("cuTensorMapEncodeTiled", (void**)&g_enc, cudaEnableDefault, &st);
    cudaFuncSetAttribute(k_mega, cudaFuncAttributeMaxDynamicSharedMemorySize, SM_TOTAL);
  }
  CUtensorMap mX = mk_map(d_in[0], DM, SQ, 64, 128);
  CUtensorMap mWq = mk_map(d_in[3], HQ * DH, DM, 64, 144);
  CUtensorMap mK = mk_map(d_in[1], DH, HKV * SK, 64, 128);
  CUtensorMap mV = mk_map(d_in[2], DH, HKV * SK, 64, 128);
  CUtensorMap mWo = mk_map(d_in[4], DM, HQ * DH, 64, 128);
  CUtensorMap mWg = mk_map(d_in[7], FF, DM, 40, 48, false);
  CUtensorMap mWu = mk_map(d_in[8], FF, DM, 40, 48, false);
  CUtensorMap mWd = mk_map(d_in[9], DM, FF, 64, 40);
  Params prm;
  prm.x = (const bf16*)d_in[0]; prm.k = (const bf16*)d_in[1]; prm.v = (const bf16*)d_in[2]; prm.wo = (const bf16*)d_in[4]; prm.wq = (const bf16*)d_in[3];
  prm.w_r = (const bf16*)d_in[6]; prm.c = (const bf16*)d_in[10]; prm.w_mod = (const bf16*)d_in[11];
  prm.wg = (const bf16*)d_in[7]; prm.wu = (const bf16*)d_in[8]; prm.wd = (const bf16*)d_in[9];
  prm.out = (bf16*)d_out;
  cudaLaunchConfig_t cfg = {};
  cfg.gridDim = dim3(128); cfg.blockDim = dim3(384); cfg.dynamicSmemBytes = SM_TOTAL; cfg.stream = cudaStreamPerThread;
  cudaLaunchAttribute at[1];
  at[0].id = cudaLaunchAttributeClusterDimension;
  at[0].val.clusterDim.x = 2; at[0].val.clusterDim.y = 1; at[0].val.clusterDim.z = 1;
  cfg.attrs = at; cfg.numAttrs = 1;
  cudaLaunchKernelEx(&cfg, k_mega, mX, mWq, mK, mV, mWo, mWg, mWu, mWd, prm);
}
```

```cpp
#include <cuda_runtime.h>
#include <cuda_bf16.h>
#include <cuda.h>
#include <stdint.h>

typedef __nv_bfloat16 bf16;

constexpr int SQ = 2048, DM = 576, HQ = 32, HKV = 16, SK = 2048, DH = 128, FF = 4608;

#define XPF 0
#define WQPF0 0
#define WQPF1 0xff
#define FFNQ 2
#define WQPF2 0
#define QTH 7
#define MPF 1
#define FILLP 31
#define FILL0 25
#define FFN0 20
#define FILLN 8
#define FFNB 6
#define PF0 22
#define FFNR 1
#define FFND 1
#define KV0 16
#define KVS 2
#define QPF 6
#define EF 31
#define WOP 20
#define TLBW 0
#define NOFFN 0
#define FLATE 0
#define RELF 1
#define REL_FENCE() asm volatile("fence.acq_rel.gpu;" ::: "memory")
#define SIDEF 3
#define FFNE 15
#define TE_POS 8
#define LAZY_LIMIT 1.8446744e19f
#define LAZY_LOW 5.4210109e-20f
__device__ uint4 g_mod1[8 * 144];
__device__ uint4 g_mod2[288];
__device__ uint4 g_q[128 * 4 * 8 * 256];
constexpr int Z_ACC = 0;
constexpr int Z_KEY = 16 * 2 * 72 * 4 * 32;
constexpr int Z_N = 2368;
__device__ uint4 g_zero[128 * Z_N];
constexpr int F_HX = 0;
constexpr int F_YP = 128 * 2 * 144;
constexpr int F_N = 288 + 288;
__device__ uint4 g_ones[128 * F_N];
#define g_acc reinterpret_cast<float4*>(g_zero)
__device__ unsigned int g_cnt[136 * 32];
__device__ unsigned int g_err;
#define HAS_ERR
enum { C_SIDE = 1, C_Q = 8 };

#define STAMP(i)
#define KSTAMP(i)
#define GSTAMP(i)
#define SETERR(v)
#define PSTAMP(t, i)

__device__ __forceinline__ int get_lane() {
  int l;
  asm volatile("mov.u32 %0, %%laneid;" : "=r"(l));
  __builtin_assume(l >= 0 && l < 32);
  return l;
}
__device__ __forceinline__ uint32_t smem_u32(const void* p) { return (uint32_t)__cvta_generic_to_shared(p); }
__device__ __forceinline__ void mbar_init(uint32_t a, uint32_t cnt) { asm volatile("mbarrier.init.shared::cta.b64 [%0], %1;" ::"r"(a), "r"(cnt)); }
__device__ __forceinline__ void mbar_expect_tx(uint32_t a, uint32_t bytes) { asm volatile("mbarrier.arrive.expect_tx.shared::cta.b64 _, [%0], %1;" ::"r"(a), "r"(bytes) : "memory"); }
__device__ __forceinline__ void mbar_arrive(uint32_t a) { asm volatile("mbarrier.arrive.shared::cta.b64 _, [%0];" ::"r"(a) : "memory"); }
__device__ __forceinline__ void mbar_arrive_cl(uint32_t a_cluster) { asm volatile("mbarrier.arrive.shared::cluster.b64 _, [%0];" ::"r"(a_cluster) : "memory"); }
__device__ __forceinline__ void mbar_wait(uint32_t a, uint32_t parity) {
  asm volatile(
      "{\n.reg .pred p;\n.reg .u32 n;\nmov.u32 n, 0;\n"
      "WAIT_LOOP:\n"
      "mbarrier.try_wait.parity.shared::cta.b64 p, [%0], %1;\n"
      "@p bra WAIT_DONE;\n"
      "add.u32 n, n, 1;\n"
      "setp.lt.u32 p, n, 65536;\n"
      "@p bra WAIT_LOOP;\n"
      "WAIT_DONE:\n}\n" ::"r"(a), "r"(parity), "l"(&g_err) : "memory");
}
__device__ __forceinline__ void cnt_wait(int idx, unsigned target) {
  for (uint32_t n = 0;; n++) {
    unsigned v;
    asm volatile("ld.relaxed.gpu.global.u32 %0, [%1];" : "=r"(v) : "l"(&g_cnt[idx * 32]) : "memory");
    if (v >= target) break;
    if (n > (1u << 15)) { SETERR(2); break; }
  }
}
__device__ __forceinline__ void cnt_arrive(int idx) {
  asm volatile("red.relaxed.gpu.global.add.u32 [%0], 1;" ::"l"(&g_cnt[idx * 32]) : "memory");
}
__device__ __forceinline__ uint4 poll4(const uint4* p) {
  uint4 v;
  uint32_t n = 0;
  while (true) {
    asm volatile("ld.relaxed.gpu.global.v4.u32 {%0,%1,%2,%3}, [%4];" : "=r"(v.x), "=r"(v.y), "=r"(v.z), "=r"(v.w) : "l"(p) : "memory");
    if (v.x && v.y && v.z && v.w) break;
    if (++n > (1u << 15)) { SETERR(4); break; }
  }
  return v;
}
__device__ __forceinline__ void poll8(const uint4* p, const uint4* q, uint4& v, uint4& w) {
  uint32_t n = 0;
  while (true) {
    asm volatile("ld.relaxed.gpu.global.v4.u32 {%0,%1,%2,%3}, [%4];" : "=r"(v.x), "=r"(v.y), "=r"(v.z), "=r"(v.w) : "l"(p) : "memory");
    asm volatile("ld.relaxed.gpu.global.v4.u32 {%0,%1,%2,%3}, [%4];" : "=r"(w.x), "=r"(w.y), "=r"(w.z), "=r"(w.w) : "l"(q) : "memory");
    if (v.x && v.y && v.z && v.w && w.x && w.y && w.z && w.w) break;
    if (++n > (1u << 15)) { SETERR(4); break; }
  }
}
__device__ __forceinline__ uint4 ldr4(const void* p) {
  uint4 v;
  asm volatile("ld.relaxed.gpu.global.v4.u32 {%0,%1,%2,%3}, [%4];" : "=r"(v.x), "=r"(v.y), "=r"(v.z), "=r"(v.w) : "l"(p) : "memory");
  return v;
}
__device__ __forceinline__ uint2 ldr2(const void* p) {
  uint2 v;
  asm volatile("ld.relaxed.gpu.global.v2.u32 {%0,%1}, [%2];" : "=r"(v.x), "=r"(v.y) : "l"(p) : "memory");
  return v;
}
__device__ __forceinline__ void str1(void* p, uint32_t v) { asm volatile("st.relaxed.gpu.global.u32 [%0], %1;" ::"l"(p), "r"(v) : "memory"); }
__device__ __forceinline__ bool unset(uint4 v) { return v.x == ~0u || v.y == ~0u || v.z == ~0u || v.w == ~0u; }
__device__ __forceinline__ uint32_t hmul2(uint32_t a, uint32_t b) { uint32_t r; asm("mul.rn.bf16x2 %0, %1, %2;" : "=r"(r) : "r"(a), "r"(b)); return r; }
__device__ __forceinline__ uint32_t hadd2(uint32_t a, uint32_t b) { uint32_t r; asm("add.rn.bf16x2 %0, %1, %2;" : "=r"(r) : "r"(a), "r"(b)); return r; }
__device__ __forceinline__ uint32_t hfma2(uint32_t a, uint32_t b, uint32_t c) { uint32_t r; asm("fma.rn.bf16x2 %0, %1, %2, %3;" : "=r"(r) : "r"(a), "r"(b), "r"(c)); return r; }
__device__ __forceinline__ void mma16816(float (&c)[4], uint32_t a0, uint32_t a1, uint32_t a2, uint32_t a3, uint32_t b0, uint32_t b1) {
  asm volatile("mma.sync.aligned.m16n8k16.row.col.f32.bf16.bf16.f32 {%0,%1,%2,%3}, {%4,%5,%6,%7}, {%8,%9}, {%0,%1,%2,%3};"
               : "+f"(c[0]), "+f"(c[1]), "+f"(c[2]), "+f"(c[3]) : "r"(a0), "r"(a1), "r"(a2), "r"(a3), "r"(b0), "r"(b1));
}
__device__ __forceinline__ void mma1688(float (&c)[4], uint32_t a0, uint32_t a1, uint32_t b0) {
  asm volatile("mma.sync.aligned.m16n8k8.row.col.f32.bf16.bf16.f32 {%0,%1,%2,%3}, {%4,%5}, {%6}, {%0,%1,%2,%3};"
               : "+f"(c[0]), "+f"(c[1]), "+f"(c[2]), "+f"(c[3]) : "r"(a0), "r"(a1), "r"(b0));
}
__device__ __forceinline__ void ldsm4t(uint32_t (&r)[4], uint32_t a) {
  asm volatile("ldmatrix.sync.aligned.m8n8.x4.trans.shared.b16 {%0,%1,%2,%3}, [%4];" : "=r"(r[0]), "=r"(r[1]), "=r"(r[2]), "=r"(r[3]) : "r"(a) : "memory");
}
__device__ __forceinline__ void ldsm4(uint32_t (&r)[4], uint32_t a) {
  asm volatile("ldmatrix.sync.aligned.m8n8.x4.shared.b16 {%0,%1,%2,%3}, [%4];" : "=r"(r[0]), "=r"(r[1]), "=r"(r[2]), "=r"(r[3]) : "r"(a) : "memory");
}
__device__ __forceinline__ void ldsm2t(uint32_t (&r)[2], uint32_t a) {
  asm volatile("ldmatrix.sync.aligned.m8n8.x2.trans.shared.b16 {%0,%1}, [%2];" : "=r"(r[0]), "=r"(r[1]) : "r"(a) : "memory");
}
__device__ __forceinline__ float warp_sum(float v) {
#pragma unroll
  for (int o = 16; o; o >>= 1) v += __shfl_xor_sync(~0u, v, o);
  return v;
}
__device__ __forceinline__ void tma_load_2d(uint32_t dst, const CUtensorMap* map, uint32_t mbar, int c0, int c1) {
  asm volatile("cp.async.bulk.tensor.2d.shared::cluster.global.mbarrier::complete_tx::bytes [%0], [%1, {%3, %4}], [%2];"
               ::"r"(dst), "l"(map), "r"(mbar), "r"(c0), "r"(c1) : "memory");
}
__device__ __forceinline__ void tma_load_2d_mc(uint32_t dst, const CUtensorMap* map, uint32_t mbar, int c0, int c1) {
  asm volatile("cp.async.bulk.tensor.2d.shared::cluster.global.mbarrier::complete_tx::bytes.multicast::cluster [%0], [%1, {%3, %4}], [%2], %5;"
               ::"r"(dst), "l"(map), "r"(mbar), "r"(c0), "r"(c1), "h"((uint16_t)3) : "memory");
}
__device__ __forceinline__ uint64_t pol_first() {
  uint64_t p;
  asm("createpolicy.fractional.L2::evict_first.b64 %0, 1.0;" : "=l"(p));
  return p;
}
__device__ __forceinline__ void tma_load_2d_h(uint32_t dst, const CUtensorMap* map, uint32_t mbar, int c0, int c1, uint64_t pol) {
  asm volatile("cp.async.bulk.tensor.2d.shared::cluster.global.mbarrier::complete_tx::bytes.L2::cache_hint [%0], [%1, {%3, %4}], [%2], %5;"
               ::"r"(dst), "l"(map), "r"(mbar), "r"(c0), "r"(c1), "l"(pol) : "memory");
}
__device__ __forceinline__ void tma_load_2d_mc_h(uint32_t dst, const CUtensorMap* map, uint32_t mbar, int c0, int c1, uint64_t pol) {
  asm volatile("cp.async.bulk.tensor.2d.shared::cluster.global.mbarrier::complete_tx::bytes.multicast::cluster.L2::cache_hint [%0], [%1, {%3, %4}], [%2], %5, %6;"
               ::"r"(dst), "l"(map), "r"(mbar), "r"(c0), "r"(c1), "h"((uint16_t)3), "l"(pol) : "memory");
}
__device__ __forceinline__ void tma_prefetch_2d(const CUtensorMap* map, int c0, int c1) {
  asm volatile("cp.async.bulk.prefetch.tensor.2d.L2.global.tile [%0, {%1, %2}];" ::"l"(map), "r"(c0), "r"(c1) : "memory");
}
__device__ __forceinline__ void bulk_prefetch(const void* p, uint32_t bytes) {
  asm volatile("cp.async.bulk.prefetch.L2.global [%0], %1;" ::"l"(p), "r"(bytes) : "memory");
}
__device__ __forceinline__ void bulk_load(uint32_t dst, const void* src, uint32_t bytes, uint32_t mbar) {
  asm volatile("cp.async.bulk.shared::cluster.global.mbarrier::complete_tx::bytes [%0], [%1], %2, [%3];"
               ::"r"(dst), "l"(src), "r"(bytes), "r"(mbar) : "memory");
}
__device__ __forceinline__ void wgmma_fence() { asm volatile("wgmma.fence.sync.aligned;" ::: "memory"); }
__device__ __forceinline__ void wgmma_commit() { asm volatile("wgmma.commit_group.sync.aligned;" ::: "memory"); }
template <int N> __device__ __forceinline__ void wgmma_wait() { asm volatile("wgmma.wait_group.sync.aligned %0;" ::"n"(N) : "memory"); }
__device__ __forceinline__ void fence_async() { asm volatile("fence.proxy.async.shared::cta;" ::: "memory"); }
__device__ __forceinline__ void bar_sync(int id, int n) { asm volatile("bar.sync %0, %1;" ::"r"(id), "r"(n) : "memory"); }
__device__ __forceinline__ void bar_arrive(int id, int n) { asm volatile("bar.arrive %0, %1;" ::"r"(id), "r"(n) : "memory"); }

constexpr uint32_t SM_BASE = 1024;
__host__ __device__ constexpr uint32_t mk_desc(uint32_t addr, uint32_t lbo_bytes) { return ((addr & 0x3FFFF) >> 4) | ((lbo_bytes >> 4) << 16); }

#define R32(d) \
  "+f"(d[0]), "+f"(d[1]), "+f"(d[2]), "+f"(d[3]), "+f"(d[4]), "+f"(d[5]), "+f"(d[6]), "+f"(d[7]), \
  "+f"(d[8]), "+f"(d[9]), "+f"(d[10]), "+f"(d[11]), "+f"(d[12]), "+f"(d[13]), "+f"(d[14]), "+f"(d[15]), \
  "+f"(d[16]), "+f"(d[17]), "+f"(d[18]), "+f"(d[19]), "+f"(d[20]), "+f"(d[21]), "+f"(d[22]), "+f"(d[23]), \
  "+f"(d[24]), "+f"(d[25]), "+f"(d[26]), "+f"(d[27]), "+f"(d[28]), "+f"(d[29]), "+f"(d[30]), "+f"(d[31])
#define R64(d) R32(d), \
  "+f"(d[32]), "+f"(d[33]), "+f"(d[34]), "+f"(d[35]), "+f"(d[36]), "+f"(d[37]), "+f"(d[38]), "+f"(d[39]), \
  "+f"(d[40]), "+f"(d[41]), "+f"(d[42]), "+f"(d[43]), "+f"(d[44]), "+f"(d[45]), "+f"(d[46]), "+f"(d[47]), \
  "+f"(d[48]), "+f"(d[49]), "+f"(d[50]), "+f"(d[51]), "+f"(d[52]), "+f"(d[53]), "+f"(d[54]), "+f"(d[55]), \
  "+f"(d[56]), "+f"(d[57]), "+f"(d[58]), "+f"(d[59]), "+f"(d[60]), "+f"(d[61]), "+f"(d[62]), "+f"(d[63])
#define S32 \
  "{%0,%1,%2,%3,%4,%5,%6,%7,%8,%9,%10,%11,%12,%13,%14,%15,%16,%17,%18,%19,%20,%21,%22,%23,%24,%25,%26,%27,%28,%29,%30,%31}"
#define S64 \
  "{%0,%1,%2,%3,%4,%5,%6,%7,%8,%9,%10,%11,%12,%13,%14,%15,%16,%17,%18,%19,%20,%21,%22,%23,%24,%25,%26,%27,%28,%29,%30,%31," \
  "%32,%33,%34,%35,%36,%37,%38,%39,%40,%41,%42,%43,%44,%45,%46,%47,%48,%49,%50,%51,%52,%53,%54,%55,%56,%57,%58,%59,%60,%61,%62,%63}"

template <int TB>
__device__ __forceinline__ void wgmma128_rs(float (&d)[64], uint32_t a0, uint32_t a1, uint32_t a2, uint32_t a3, uint32_t db, int scale_d) {
  asm volatile("{\n.reg .pred p;\n.reg .b64 q;\nsetp.ne.b32 p, %69, 0;\nmov.b64 q, {%68, 0x40000040};\n"
               "wgmma.mma_async.sync.aligned.m64n128k16.f32.bf16.bf16 " S64 ", {%64,%65,%66,%67}, q, p, 1, 1, %70;\n}\n"
               : R64(d) : "r"(a0), "r"(a1), "r"(a2), "r"(a3), "r"(db), "r"(scale_d), "n"(TB));
}
__device__ __forceinline__ void wgmma64_rs(float (&d)[32], uint32_t a0, uint32_t a1, uint32_t a2, uint32_t a3, uint32_t db, int scale_d) {
  asm volatile("{\n.reg .pred p;\n.reg .b64 q;\nsetp.ne.b32 p, %37, 0;\nmov.b64 q, {%36, 0x40000040};\n"
               "wgmma.mma_async.sync.aligned.m64n64k16.f32.bf16.bf16 " S32 ", {%32,%33,%34,%35}, q, p, 1, 1, 1;\n}\n"
               : R32(d) : "r"(a0), "r"(a1), "r"(a2), "r"(a3), "r"(db), "r"(scale_d));
}
__device__ __forceinline__ uint32_t pack_bf16(float a, float b) {
  uint32_t r;
  asm("cvt.rn.bf16x2.f32 %0, %1, %2;" : "=r"(r) : "f"(b), "f"(a));
  return r;
}
__device__ __forceinline__ float ex2(float x) { float y; asm("ex2.approx.ftz.f32 %0, %1;" : "=f"(y) : "f"(x)); return y; }
__device__ __forceinline__ float bfr(float x) { return __bfloat162float(__float2bfloat16(x)); }
__device__ __forceinline__ float bf_lo(uint32_t u) { return __uint_as_float(u << 16); }
__device__ __forceinline__ float bf_hi(uint32_t u) { return __uint_as_float(u & 0xffff0000u); }
__device__ __forceinline__ uint4 lds128(uint32_t a) {
  uint4 v;
  asm volatile("ld.shared.v4.b32 {%0,%1,%2,%3}, [%4];" : "=r"(v.x), "=r"(v.y), "=r"(v.z), "=r"(v.w) : "r"(a) : "memory");
  return v;
}
__device__ __forceinline__ void sts128(uint32_t a, uint4 v) {
  asm volatile("st.shared.v4.b32 [%0], {%1,%2,%3,%4};" ::"r"(a), "r"(v.x), "r"(v.y), "r"(v.z), "r"(v.w) : "memory");
}
__device__ __forceinline__ void red_add_v4(float4* p, float a, float b, float c, float d) {
  asm volatile("red.global.add.v4.f32 [%0], {%1,%2,%3,%4};" ::"l"(p), "f"(a), "f"(b), "f"(c), "f"(d) : "memory");
}
__device__ __forceinline__ float rcp(float x) { float y; asm("rcp.approx.ftz.f32 %0, %1;" : "=f"(y) : "f"(x)); return y; }
__device__ __forceinline__ float sqrt_a(float x) { float y; asm("sqrt.approx.ftz.f32 %0, %1;" : "=f"(y) : "f"(x)); return y; }
__device__ __forceinline__ float silu_bf(float v) { return bfr(v * rcp(1.f + __expf(-v))); }

constexpr int SM_STASH = 131072;
constexpr int QG = 73728;
constexpr int SM_STG = 210944;
constexpr int SM_XCH = 98304;
constexpr int SM_MISC = 229376;
constexpr int SM_TOTAL = 232448;
constexpr int B_FULLQ = 0, B_G1 = 24, B_G2 = 32, B_G3 = 40, B_FULLA = 64, B_FULLO = 96, B_FFN = 160, B_RD = 168, B_MD = 176, B_X = 272,
              B_EMPTYQ = 280, B_EMPTYO = 344, B_ST = 392,
              B_EMPTYA = 400, B_M = 432, B_XF = 144;
constexpr int SM_MOD = SM_MISC + 448;
constexpr int SM_FILL = SM_MISC + 512;
constexpr int SM_M2 = SM_MISC + 2560;
constexpr int SM_RED = SM_MISC + 2752;
constexpr int SM_ZERO = SM_MISC + 3040;
constexpr int SM_WG = 137216, SM_WU = 183296;
constexpr int SM_X2 = 46080;
constexpr int SM_T = 65536;
constexpr int SM_OUT = SM_MISC - 32768;
constexpr int SM_MD = SM_STASH;

struct Params {
  const bf16 *x, *k, *c, *w_mod, *w_r, *wo, *v, *wq, *wg, *wu, *wd;
  bf16* out;
};

__global__ void __launch_bounds__(384, 1)
k_mega(const __grid_constant__ CUtensorMap mX, const __grid_constant__ CUtensorMap mWq,
       const __grid_constant__ CUtensorMap mK, const __grid_constant__ CUtensorMap mV,
       const __grid_constant__ CUtensorMap mWo, const __grid_constant__ CUtensorMap mWg,
       const __grid_constant__ CUtensorMap mWu, const __grid_constant__ CUtensorMap mWd, const Params prm) {
  extern __shared__ __align__(1024) uint8_t smem_raw[];
  const uint32_t sb = smem_u32(smem_raw);
  if ((sb & 0x3FFFF) != SM_BASE) __trap();
  const uint32_t sBar = sb + SM_MISC;
  const int tid = threadIdx.x;
  const int lane = get_lane();
  PSTAMP(0, 84);
  const int warp = __shfl_sync(~0u, tid >> 5, 0);
  const int b = blockIdx.x, rank = b & 1, qt = (b >> 1) & 15, kg = b >> 5, hg = kg * 2 + rank;
  const int hcol = (kg * 8 + rank) * DH;
  auto wq_prefetch = [&](int mask) {
    const bf16* wp = prm.wq + (size_t)(qt * 36 + ((tid - 128) >> 3)) * (HQ * DH) + hcol + ((tid & 6) * 2 + (tid & 1)) * 64;
    if ((mask >> (tid & 7)) & 1) {
      asm volatile("prefetch.global.L2 [%0];" ::"l"(wp));
      if (warp == 4) asm volatile("prefetch.global.L2 [%0];" ::"l"(wp + 32 * (HQ * DH)));
    }
  };
  if (warp >= 4) wq_prefetch(WQPF0);
  if (lane == 0 && warp >= 4) {
    if (MPF && warp < 10 && b < 96) bulk_prefetch(prm.w_mod + (size_t)(b * 6 + warp - 4) * (6 * DM), 2 * DM * 2);
    const int c0 = warp < 9 ? 1 : 8, c1 = warp < 11 ? c0 : 16, c2 = warp < 11 ? c0 : 3;
#pragma unroll
    for (int j = 0; j < 7; j++) mbar_init(sBar + (warp - 4) * 56 + j * 8, (warp == 6 && (j & 6) == 4) ? 2 : j == 0 ? c0 : j < 5 ? c1 : c2);
    *reinterpret_cast<uint32_t*>(smem_raw + SM_ZERO) = 0;
    asm volatile("fence.mbarrier_init.release.cluster;" ::: "memory");
  }
  __syncwarp();
  asm volatile("barrier.cluster.arrive.relaxed.aligned;" ::: "memory");
#define CL_WAIT() asm volatile("barrier.cluster.wait.acquire.aligned;" ::: "memory")
  const bool do_mod1 = warp >= 1 && warp < 4 && b < 72;
  if (warp < 4) {
    asm volatile("setmaxnreg.dec.sync.aligned.u32 40;");
    if (warp == 0) {
      PSTAMP(0, 85);
      CL_WAIT();
      PSTAMP(0, 86);
      if (lane == 0) {
        mbar_expect_tx(sBar + B_X, 9 * 16384);
#pragma unroll
        for (int i = 0; i < 5; i++)
          if (i < 4 || rank == 0) tma_load_2d_mc(sb + (2 * i + rank) * 16384, &mX, sBar + B_X, (2 * i + rank) * 64, qt * 128);
      }
    }
    PSTAMP(0, 87);
    if (do_mod1) {
      const int st = tid - 32;
      const uint32_t stg = sb + SM_STG + st * 16;
      {
        const bf16* wp = prm.w_mod + (size_t)(st >> 1) * (6 * DM) + b * 16 + (st & 1) * 8;
#pragma unroll
        for (int i = 0; i < 12; i++)
          asm volatile("cp.async.cg.shared.global [%0], [%1], 16;" ::"r"(stg + i * 1536), "l"(wp + (size_t)i * 48 * (6 * DM)) : "memory");
      }
      float* const sc = reinterpret_cast<float*>(smem_raw + SM_MOD);
#pragma unroll
      for (int i = 0; i < 3; i++) {
        const uint32_t v = __ldg(reinterpret_cast<const uint32_t*>(prm.c) + st + i * 96);
        *reinterpret_cast<float2*>(sc + (st + i * 96) * 2) = make_float2(silu_bf(bf_lo(v)), silu_bf(bf_hi(v)));
      }
      bar_sync(6, 96);
      PSTAMP(32, 88);
      asm volatile("cp.async.wait_all;" ::: "memory");
      PSTAMP(32, 93);
      float a[8];
#pragma unroll
      for (int i = 0; i < 8; i++) a[i] = 0.f;
#pragma unroll 3
      for (int i = 0; i < 12; i++) {
        const float sv = sc[(st >> 1) + 48 * i];
        const uint4 v = lds128(stg + i * 1536);
        a[0] += sv * bf_lo(v.x); a[1] += sv * bf_hi(v.x); a[2] += sv * bf_lo(v.y); a[3] += sv * bf_hi(v.y);
        a[4] += sv * bf_lo(v.z); a[5] += sv * bf_hi(v.z); a[6] += sv * bf_lo(v.w); a[7] += sv * bf_hi(v.w);
      }
      const bool u2 = lane & 2, u4 = lane & 4, u8 = lane & 8;
#pragma unroll
      for (int i = 0; i < 4; i++) { float snd = u2 ? a[i] : a[i + 4]; float kp = u2 ? a[i + 4] : a[i]; a[i] = kp + __shfl_xor_sync(~0u, snd, 2); }
#pragma unroll
      for (int i = 0; i < 2; i++) { float snd = u4 ? a[i] : a[i + 2]; float kp = u4 ? a[i + 2] : a[i]; a[i] = kp + __shfl_xor_sync(~0u, snd, 4); }
      { float snd = u8 ? a[0] : a[1]; float kp = u8 ? a[1] : a[0]; a[0] = kp + __shfl_xor_sync(~0u, snd, 8); }
      a[0] += __shfl_xor_sync(~0u, a[0], 16);
      float* const red = reinterpret_cast<float*>(smem_raw + SM_RED);
      if (lane < 16) red[(warp - 1) * 16 + (lane & 1) * 8 + (u2 ? 4 : 0) + (u4 ? 2 : 0) + (u8 ? 1 : 0)] = a[0];
      PSTAMP(32, 94);
      bar_sync(6, 96);
      PSTAMP(32, 95);
      if (st < 64) {
        const float* rp = red + (lane & 7) * 2;
        const float2 x = *reinterpret_cast<const float2*>(rp), y = *reinterpret_cast<const float2*>(rp + 16), z = *reinterpret_cast<const float2*>(rp + 32);
        uint32_t w = pack_bf16(x.x + y.x + z.x, x.y + y.y + z.y);
        if (b >= 36) w = hadd2(w, 0x3f803f80u);
        asm volatile("st.relaxed.gpu.global.u32 [%0], %1;" ::"l"(reinterpret_cast<uint32_t*>(g_mod1) + (st >> 3) * 576 + b * 8 + (lane & 7)), "r"(~w) : "memory");
      }
    }
    __syncwarp();
    PSTAMP(32, 89);
    if (warp > 0) {
      CL_WAIT();
      fence_async();
      if (tid < 104) {
        uint4 v, w;
        mbar_wait(sBar + B_X, 0);
        poll8(g_mod1 + (b & 7) * 144 + tid - 32, g_mod1 + (b & 7) * 144 + tid + 40, v, w);
        sts128(sb + SM_MOD + (tid - 32) * 32, make_uint4(~v.x, ~w.x, ~v.y, ~w.y));
        sts128(sb + SM_MOD + (tid - 32) * 32 + 16, make_uint4(~v.z, ~w.z, ~v.w, ~w.w));
      }
      __syncwarp();
      PSTAMP(32, 92);
      bar_arrive(3, 224);
      bar_arrive(4, 224);
      if (lane == 0) asm volatile("mbarrier.arrive.shared::cta.b64 _, [%0];" ::"r"(sBar + B_M) : "memory");
    }
    auto ffn_box = [&](int fb) {
      const int m = fb >= 12;
      tma_load_2d(sb + SM_WG + fb * 3840, m ? &mWu : &mWg, sBar + B_FFN, (b * 36) & ~7, (fb - m * 12) * 48);
    };
    if (tid == 0) {
      const uint64_t pol = pol_first();
      auto kv_load = [&](int t) {
        const int s = t & 3;
        mbar_wait(sBar + B_EMPTYA + s * 8, (t >> 2) & 1);
        mbar_expect_tx(sBar + B_FULLA + s * 8, 32768);
        if (EF & 1) tma_load_2d_mc_h(sb + s * 32768 + rank * 16384, (t & 1) ? &mV : &mK, sBar + B_FULLA + s * 8, rank * 64, kg * 4 * SK + (t >> 1) * 128, pol);
        else tma_load_2d_mc(sb + s * 32768 + rank * 16384, (t & 1) ? &mV : &mK, sBar + B_FULLA + s * 8, rank * 64, kg * 4 * SK + (t >> 1) * 128);
      };
#pragma unroll 1
      for (int i = 0, g = 1; i < 32; i++) {
        const int hh = (i >> 2) + 2;
        if (i == QTH) mbar_wait(sBar + B_M, 0);
        if (!(i & 3)) {
          mbar_wait(sBar + B_EMPTYQ + g * 8, i >= 12 && i < 24);
          mbar_expect_tx(sBar + B_FULLQ + g * 8, QG);
        }
        if (EF & 2) tma_load_2d_h(sb + g * QG + (i & 3) * 18432, &mWq, sBar + B_FULLQ + g * 8, hcol + (hh & 6) * 128 + (hh & 1) * 64, (i & 3) * 144, pol);
        else tma_load_2d(sb + g * QG + (i & 3) * 18432, &mWq, sBar + B_FULLQ + g * 8, hcol + (hh & 6) * 128 + (hh & 1) * 64, (i & 3) * 144);
        if ((i & 3) == 3 && ++g == 3) g = 0;
      }
#pragma unroll 1
      for (int u = 0; u < 128; u++) kv_load(u < 5 || u == 127 ? u : (u & 1) ? u + 1 : u - 1);
      mbar_wait(sBar + B_X, 1);
      {
        int ch = kg * 2, g = 0, par = 1, fb = 0;
        mbar_expect_tx(sBar + B_FFN, (NOFFN & 1 ? 0 : 9 * 5120) + (NOFFN & 2 ? 15 * 3840 : 2 * DM * 80));
#pragma unroll 1
        for (int i = 0; i < 39; i++) {
          if (i < 6) mbar_wait(sBar + B_EMPTYA + (g >> 1) * 8, 0);
          else mbar_wait(sBar + B_EMPTYO + g * 8, par);
          if (i < 36) {
            mbar_expect_tx(sBar + B_FULLO + g * 8, 16384);
            if (EF & 8) tma_load_2d_h(sb + g * 16384, &mWo, sBar + B_FULLO + g * 8, ch * 64, hcol + (i & 3) * 256, pol);
            else tma_load_2d(sb + g * 16384, &mWo, sBar + B_FULLO + g * 8, ch * 64, hcol + (i & 3) * 256);
            if ((i & 3) == 3 && ++ch == 9) ch = 0;
            if (i == 7) mbar_wait(sBar + B_ST, 0);
            if (i >= FFN0) {
#pragma unroll 1
              for (const int fe = i == 35 ? FFNE : min(FFNE, (i - FFN0 + 1) * FFNR / FFND); fb < fe; fb++) ffn_box(fb);
            }
          } else {
            if ((FLATE & 1) && i == 36) mbar_wait(sBar + B_G1, 0);
#pragma unroll 1
            for (int f = g * 3; f < g * 3 + 3 && !(NOFFN & 1); f++) tma_load_2d(sb + f * 5120, &mWd, sBar + B_FFN, f * 64, b * 36);
          }
          if (++g == 6) { g = 0; par ^= 1; }
        }
      }
    } else if (warp == 3) {
#pragma unroll 1
      for (int i = 0, g = 1; i < 8; i++) {
        mbar_wait(sBar + B_FULLQ + g * 8, i >= 3 && i < 6);
        if (++g == 3) g = 0;
        KSTAMP(170 + i * 2); bar_sync(1, 288); KSTAMP(171 + i * 2);
      }
#pragma unroll 1
      for (int u = 0; u < 128; u++) {
        const int t = (u == 0 || u == 127) ? u : (u & 1) ? u + 1 : u - 1;
        mbar_wait(sBar + B_FULLA + (t & 3) * 8, (t >> 2) & 1);
        if (!(t & 1) || t == 127) { KSTAMP((t + 1) & ~1); bar_sync(1, 288); KSTAMP(((t + 1) & ~1) + 1); }
        else { KSTAMP(190 + (t >> 1)); bar_sync(10, 160); }
      }
      int g = 0, par = 0;
      if (lane < 2) mbar_expect_tx(sBar + B_XF + lane * 8, 16384);
#pragma unroll 1
      for (int i = 0; i < 36; i++) {
        mbar_wait(sBar + B_FULLO + g * 8, par);
        if (++g == 6) { g = 0; par ^= 1; }
        if ((i & 3) == 3 && i > 3 && i < 35) {
          const uint32_t xf = sBar + B_XF + ((i - 4) & 4) * 2;
          KSTAMP(260 + (i >> 2));
          mbar_wait(xf, ((i - 4) >> 3) & 1);
          __syncwarp();
          if (lane == 0) mbar_expect_tx(xf, 16384);
        }
        if (i & 1) { KSTAMP(129 + i); bar_sync(1, 288); KSTAMP(130 + i); }
      }
    } else if (warp > 0) {
      const int st = tid - 32;
      mbar_wait(sBar + B_FULLQ + 8, 0);
      mbar_wait(sBar + B_FULLQ + 8, 1);
      const bf16* const kvp = (rank ? prm.v : prm.k) + ((size_t)kg * 4 * SK + qt * 128) * DH;
      if (st == 0) bulk_prefetch(kvp, 32768);
      mbar_wait(sBar + B_FULLA, 0);
      mbar_wait(sBar + B_FULLA, 1);
      if (warp == 1) {
#pragma unroll 1
        for (int grp = b < 72 ? b : 288; grp < 288; grp += 72) {
          float a[8];
#pragma unroll
          for (int i = 0; i < 8; i++) a[i] = 0.f;
#pragma unroll 2
          for (int r = lane; r < DM; r += 32) {
            uint4 v;
            if (EF & 16) asm("ld.global.nc.L2::cache_hint.v4.u32 {%0,%1,%2,%3}, [%4], %5;" : "=r"(v.x), "=r"(v.y), "=r"(v.z), "=r"(v.w) : "l"(prm.w_mod + (size_t)r * (6 * DM) + 2 * DM + grp * 8), "l"(pol_first()));
            else v = __ldg(reinterpret_cast<const uint4*>(prm.w_mod + (size_t)r * (6 * DM) + 2 * DM + grp * 8));
            float s = silu_bf(__bfloat162float(prm.c[r]));
            a[0] += s * bf_lo(v.x); a[1] += s * bf_hi(v.x); a[2] += s * bf_lo(v.y); a[3] += s * bf_hi(v.y);
            a[4] += s * bf_lo(v.z); a[5] += s * bf_hi(v.z); a[6] += s * bf_lo(v.w); a[7] += s * bf_hi(v.w);
          }
#pragma unroll
          for (int i = 0; i < 8; i++) a[i] = warp_sum(a[i]);
          if (lane == 0) {
            const int kind = grp / 72;
#pragma unroll
            for (int i = 0; i < 4; i++) {
              uint32_t w = pack_bf16(a[2 * i], a[2 * i + 1]);
              if (kind == 2) w = hadd2(w, 0x3f803f80u);
              reinterpret_cast<uint32_t*>(smem_raw + SM_M2)[i * 4 + kind] = w;
            }
            if (kind == 3) {
              fence_async();
              asm volatile("cp.async.bulk.global.shared::cta.bulk_group [%0], [%1], 64;" ::"l"(g_mod2 + b * 4), "r"(sb + SM_M2) : "memory");
              asm volatile("cp.async.bulk.commit_group;\ncp.async.bulk.wait_group 0;" ::: "memory");
              if (SIDEF & 1) asm volatile("fence.acq_rel.gpu;" ::: "memory");
              cnt_arrive(C_SIDE);
            }
          }
        }
        __syncwarp();
        {
          if (lane == 0) asm volatile("mbarrier.arrive.shared::cta.b64 _, [%0];" ::"r"(sBar + B_XF) : "memory");
          int ch = kg * 2;
#pragma unroll 1
          for (int k = 0; k < 16; k++) {
            bar_sync(8 + (k & 1), 160);
            if (lane == 0) {
              fence_async();
#pragma unroll
              for (int w = 0; w < 4; w++)
                asm volatile("cp.reduce.async.bulk.global.shared::cta.bulk_group.add.f32 [%0], [%1], 2048;" ::"l"(g_acc + (qt * 8 + (k & 1) * 4 + w) * 2304 + ch * 256 + rank * 128),
                             "r"(sb + SM_OUT + (k & 3) * 8192 + w * 2048) : "memory");
              if (k & 1) {
                asm volatile("cp.async.bulk.commit_group;\ncp.async.bulk.wait_group.read 1;" ::: "memory");
                asm volatile("mbarrier.arrive.shared::cta.b64 _, [%0];" ::"r"(sBar + B_XF + ((k & 2) ? 0 : 8)) : "memory");
                if (++ch == 9) ch = 0;
              }
            }
            __syncwarp();
          }
        }
        PSTAMP(32, 56);
        if (lane == 0) {
          asm volatile("cp.async.bulk.wait_group.read 0;" ::: "memory");
          asm volatile("mbarrier.arrive.shared::cta.b64 _, [%0];" ::"r"(sBar + B_RD) : "memory");
          asm volatile("cp.async.bulk.wait_group 0;" ::: "memory");
          PSTAMP(32, 58);
          REL_FENCE();
        }
        __syncwarp();
        const int lane = get_lane();
        if (lane < 8) asm volatile("red.relaxed.gpu.global.add.u32 [%0], 1;" ::"l"(&g_cnt[(C_Q + qt * 8 + lane) * 32]) : "memory");
        PSTAMP(32, 57);
        {
          bool first = true;
#pragma unroll 1
          for (uint32_t n = 0;; n++) {
            uint2 v;
            v = ldr2(&g_cnt[(C_Q + qt * 8 + hg) * 32]);
            const bool out = n > (1u << 15);
            if (out) SETERR(2);
            if (first && (v.x >= 8 || out)) { PSTAMP(32, 55); if (lane == 0) mbar_arrive(sBar + B_G1); first = false; }
            if (!first && (v.y >= 8 || out)) break;
          }
        }
        PSTAMP(32, 59);
        if (lane == 0) mbar_arrive(sBar + B_G2);
        uint32_t k1 = 0, k2 = 0;
        uint4 hv[4];
        uint2 hw = make_uint2(0u, 0u);
        auto h_load = [&]() {
          const int r1 = ~k1 & (SQ - 1), r2 = ~k2 & (SQ - 1);
          const int r = lane < 16 ? r1 : r2;
          const int c = ((r >> 5) & 3) * 32 + (r >> 7) * 2 + ((r >> 4) & 1);
          const uint4* p = g_ones + F_HX + (c * 288 + (lane >= 16 && (r1 >> 4) == (r2 >> 4) ? 144 : 0) + (lane & 15));
#pragma unroll
          for (int i = 0; i < 4; i++) hv[i] = ldr4(p + i * 16);
          hw = ldr2(reinterpret_cast<const uint2*>(p + 64) - (lane & 15));
        };
#pragma unroll
        for (int i = 0; i < 4; i++) hv[i] = make_uint4(0u, 0u, 0u, 0u);
        const uint4* kp = g_zero + Z_KEY + (b & 31) * 64 + lane * 2;
        auto merge = [](uint32_t& m1, uint32_t& m2, uint32_t n1, uint32_t n2) { m2 = max(min(m1, n1), max(m2, n2)); m1 = max(m1, n1); };
#pragma unroll 1
        for (uint32_t n = 0;; n++) {
          uint4 a, c;
          asm volatile("ld.relaxed.gpu.global.v4.u32 {%0,%1,%2,%3}, [%8];\nld.relaxed.gpu.global.v4.u32 {%4,%5,%6,%7}, [%8+16];"
                       : "=r"(a.x), "=r"(a.y), "=r"(a.z), "=r"(a.w), "=r"(c.x), "=r"(c.y), "=r"(c.z), "=r"(c.w) : "l"(kp) : "memory");
          const bool all = __all_sync(~0u, a.y && a.w && c.y && c.w);
          merge(a.x, a.y, a.z, a.w);
          merge(a.x, a.y, c.x, c.y);
          merge(a.x, a.y, c.z, c.w);
          const uint32_t m1 = __reduce_max_sync(~0u, a.x);
          const uint32_t m2 = __reduce_max_sync(~0u, a.x == m1 ? a.y : a.x);
          bool bad = m1 != k1 || m2 != k2 || hw.x == ~0u || hw.y == ~0u;
#pragma unroll
          for (int i = 0; i < 4; i++) bad |= unset(hv[i]);
          bad = __any_sync(~0u, bad);
          if (all && !bad) break;
          if (n > (1u << 15)) { SETERR(4); break; }
          if (bad) { k1 = m1; k2 = m2; h_load(); }
        }
        PSTAMP(32, 60);
        {
          const uint32_t ha = sb + SM_T + 4096 + (lane >> 4) * 1152 + (lane & 15) * 16;
#pragma unroll
          for (int i = 0; i < 4; i++) sts128(ha + i * 256, hv[i]);
          asm volatile("st.shared.v2.b32 [%0], {%1,%2};" ::"r"(ha + 1024 - (lane & 15) * 8), "r"(hw.x), "r"(hw.y) : "memory");
        }
        if (lane == 0) asm volatile("st.shared.v2.b32 [%0], {%1,%2};" ::"r"(sb + SM_T + 128), "r"(k1), "r"(k2) : "memory");
        __syncwarp();
        if (lane == 0) mbar_arrive(sBar + B_G3);
        PSTAMP(32, 61);
      } else {
#pragma unroll
        for (int i = 0; i < 4; i++) sts128(sb + SM_FILL + i * 512 + lane * 16, i < 2 ? make_uint4(0u, 0u, 0u, 0u) : make_uint4(~0u, ~0u, ~0u, ~0u));
        fence_async();
        __syncwarp();
#pragma unroll 1
        for (int p = 2; p < FILLP; p++) {
          mbar_wait(sBar + B_FULLA, p & 1);
          if (lane == 0) {
            if ((p & 7) == 3 && p < 24) bulk_prefetch(kvp + (size_t)((p >> 3) + 1) * SK * DH, 32768);
            if ((p & 7) == QPF && p < 24) bulk_prefetch(g_q + ((size_t)b * 4 + (p >> 3) + 1) * 2048, 32768);
            if (p == FILLP - 1) bulk_prefetch(prm.x + (size_t)(qt * 128 + hg * 16) * DM, 16 * DM * 2);
            if (p == WOP) bulk_prefetch(prm.wo + ((size_t)kg * 1024 + (b & 31) * 32) * DM, 32 * DM * 2);
            if (p >= PF0 && p < PF0 + 9) {
              const int i = p - PF0, m = i / 3;
              bulk_prefetch((m == 0 ? prm.wg : m == 1 ? prm.wu : prm.wd) + (size_t)(b * 3 + i - m * 3) * (DM * 12), DM * 24);
            }
          }
          __syncwarp();
          if (p >= FILL0 && lane < FILLN) {
            const int i = (p - FILL0) * FILLN + lane;
            if (i < (Z_N + F_N) / 64)
              asm volatile("cp.async.bulk.global.shared::cta.bulk_group [%0], [%1], 1024;" ::"l"(i < F_N / 64 ? g_ones + b * F_N + i * 64 : g_zero + b * Z_N - F_N + i * 64),
                           "r"(sb + SM_FILL + (i < F_N / 64 ? 1024 : 0)) : "memory");
          }
        }
        asm volatile("cp.async.bulk.commit_group;\ncp.async.bulk.wait_group 0;" ::: "memory");
        if (SIDEF & 2) asm volatile("fence.acq_rel.gpu;" ::: "memory");
        __syncwarp();
        PSTAMP(64, 51);
        if (lane == 0) {
          cnt_arrive(C_SIDE);
          PSTAMP(64, 52);
          cnt_wait(C_SIDE, 128 + 72);
          PSTAMP(64, 53);
          asm volatile("mbarrier.arrive.shared::cta.b64 _, [%0];" ::"r"(sBar + B_X) : "memory");
        }
        __syncwarp();
        if (lane == 0) {
          asm volatile("prefetch.tensormap [%0];\nprefetch.tensormap [%1];\nprefetch.tensormap [%2];\nprefetch.tensormap [%3];" ::"l"(&mWo), "l"(&mWg), "l"(&mWu), "l"(&mWd) : "memory");
          mbar_wait(sBar + B_ST, 0);
          mbar_expect_tx(sBar + B_MD, 5760);
          bulk_load(sb + SM_MD, g_mod2, 4608, sBar + B_MD);
          bulk_load(sb + SM_MD + 4608, prm.w_r, 1152, sBar + B_MD);
#pragma unroll 1
          for (int r = 0; r < 6; r++) mbar_wait(sBar + B_EMPTYO + 24, r & 1);
          mbar_expect_tx(sBar + B_FULLO + 24, 16 * 1152);
#pragma unroll 1
          for (int r = 0; r < 16; r++) bulk_load(sb + SM_X2 + r * 1168, prm.x + (size_t)(qt * 128 + hg * 16 + r) * DM, 1152, sBar + B_FULLO + 24);
          mbar_wait(sBar + B_RD, 0);
          if (FLATE & 2) mbar_wait(sBar + B_G1, 0);
#pragma unroll 1
          for (int fb = FFNE; fb < 24 && !(NOFFN & 2); fb++) ffn_box(fb);
        }
        __syncwarp();
        const uint32_t* const tsu = reinterpret_cast<const uint32_t*>(smem_raw + SM_T);
        const int row = qt * 128 + hg * 16 + lane;
        auto out_row = [&]() {
          asm volatile("cp.async.bulk.global.shared::cta.bulk_group [%0], [%1], 1152;" ::"l"(prm.out + (size_t)row * DM), "r"(sb + SM_X2 + lane * 1168) : "memory");
        };
        bar_sync(11, 288);
        fence_async();
        const bool top = (*(volatile const uint32_t*)(tsu + 34) >> lane) & 1;
        if (lane < 16 && !top) out_row();
        mbar_wait(sBar + B_G3, 0);
        if (top && row != (int)(~*(volatile const uint32_t*)(tsu + 32) & (SQ - 1)) && row != (int)(~*(volatile const uint32_t*)(tsu + 33) & (SQ - 1))) out_row();
        asm volatile("cp.async.bulk.commit_group;\ncp.async.bulk.wait_group.read 0;" ::: "memory");
      }
    }
  } else {
    const int cw = (warp >> 2) - 1;
    const int w8 = warp - 4;
    const int ct = tid - 128;
    const int lane = get_lane(), g = lane >> 2, t4 = lane & 3;
    uint32_t relBar;
    asm volatile("mapa.shared::cluster.u32 %0, %1, %2;" : "=r"(relBar) : "r"(sBar), "r"(rank ^ (lane & 1)));
    auto release = [&](int off) {
      if (lane < 2) mbar_arrive_cl(relBar + off);
    };
    auto release1 = [&](int off) {
      if (lane == 0) mbar_arrive_cl(relBar + off);
    };
    auto turn_begin = [&]() {
      asm volatile("{\n.reg .pred p;\nsetp.eq.b32 p, %0, 0;\n@p bar.sync 1, 288;\n@!p bar.sync 2, 256;\n}\n" ::"r"(cw) : "memory");
      wgmma_fence();
    };
    auto turn_end = [&]() { asm volatile("{\n.reg .pred p;\nsetp.eq.b32 p, %0, 0;\n@p bar.arrive 2, 256;\n@!p bar.arrive 1, 288;\n}\n" ::"r"(cw) : "memory"); };
    STAMP(0); GSTAMP(90);
    CL_WAIT();
    asm volatile("setmaxnreg.inc.sync.aligned.u32 232;");
    float S[64], O[64];
    uint32_t P[32], Qf[32];
    constexpr uint32_t dB_k = mk_desc(SM_BASE, 16);
    constexpr uint32_t dB_n16 = mk_desc(SM_BASE, 16384);
    uint4* const qpark = g_q + (size_t)b * (4 * 8 * 256) + ct;
    {
      uint32_t A[144];
      const uint32_t la = sb + (w8 * 16 + (lane & 15)) * 128 + (((lane >> 4) ^ (lane & 7)) << 4);
      mbar_wait(sBar + B_X, 0);
      wq_prefetch(WQPF1);
      STAMP(1);
#pragma unroll
      for (int k = 0; k < 36; k++) {
        uint32_t a[4];
        ldsm4(a, (la ^ ((k & 3) << 5)) + (k >> 2) * 16384);
        A[k * 4] = a[0]; A[k * 4 + 1] = a[1]; A[k * 4 + 2] = a[2]; A[k * 4 + 3] = a[3];
      }
      const uint32_t one = 0x3f803f80u;
      float c[4][4];
#pragma unroll
      for (int i = 0; i < 16; i++) c[i >> 2][i & 3] = 0.f;
#pragma unroll
      for (int k = 0; k < 36; k++) mma16816(c[k & 3], A[k * 4], A[k * 4 + 1], A[k * 4 + 2], A[k * 4 + 3], one, one);
      if (lane < 3) mbar_arrive_cl(sBar + B_EMPTYQ + lane * 8);
      const float mA = ((c[0][0] + c[1][0]) + (c[2][0] + c[3][0])) * (1.f / DM), mB = ((c[0][2] + c[1][2]) + (c[2][2] + c[3][2])) * (1.f / DM);
      if (cw == 1) bar_sync(7, 256);
      uint32_t zero;
      asm volatile("ld.shared.b32 %0, [%1];" : "=r"(zero) : "r"(sb + SM_ZERO) : "memory");
      const uint32_t nA = pack_bf16(-mA, -mA) | zero, nB = pack_bf16(-mB, -mB) | zero;
      const float eA = mA + bf_lo(nA), eB = mB + bf_lo(nB);
#pragma unroll
      for (int i = 0; i < 16; i++) c[i >> 2][i & 3] = 0.f;
#pragma unroll
      for (int k = 0; k < 36; k++) {
        A[k * 4] = hadd2(A[k * 4], nA); A[k * 4 + 1] = hadd2(A[k * 4 + 1], nB); A[k * 4 + 2] = hadd2(A[k * 4 + 2], nA); A[k * 4 + 3] = hadd2(A[k * 4 + 3], nB);
        mma16816(c[k & 3], hmul2(A[k * 4], A[k * 4]), hmul2(A[k * 4 + 1], A[k * 4 + 1]), hmul2(A[k * 4 + 2], A[k * 4 + 2]), hmul2(A[k * 4 + 3], A[k * 4 + 3]), one, one);
      }
      const float vA = (c[0][0] + c[1][0]) + (c[2][0] + c[3][0]), vB = (c[0][2] + c[1][2]) + (c[2][2] + c[3][2]);
      const float rA = rsqrtf(fmaxf(vA * (1.f / DM) - eA * eA, 0.f) + 1e-5f), rB = rsqrtf(fmaxf(vB * (1.f / DM) - eB * eB, 0.f) + 1e-5f);
      const uint32_t hA = pack_bf16(rA, rA), hB = pack_bf16(rB, rB);
      const uint32_t lA = pack_bf16(rA - bf_lo(hA), rA - bf_lo(hA)), lB = pack_bf16(rB - bf_lo(hB), rB - bf_lo(hB));
      const uint32_t oA = pack_bf16(-eA * rA, -eA * rA), oB = pack_bf16(-eB * rB, -eB * rB);
#pragma unroll
      for (int i = 0; i < 144; i++) A[i] = hfma2(A[i], (i & 1) ? hB : hA, hfma2(A[i], (i & 1) ? lB : lA, (i & 1) ? oB : oA));
      asm volatile("st.shared.b32 [%0], %1;" ::"r"(sb + SM_ZERO + 4), "r"(A[143] ^ A[100]) : "memory");
      if (cw == 0) bar_arrive(7, 256);
      STAMP(2);
      bar_sync(3 + cw, 224);
      wq_prefetch(WQPF2);
      STAMP(3);
#pragma unroll
      for (int k = 0; k < 72; k++) {
        const uint2 m = *reinterpret_cast<const uint2*>(smem_raw + SM_MOD + (k * 4 + t4) * 8);
        A[k * 2] = hfma2(A[k * 2], m.y, m.x); A[k * 2 + 1] = hfma2(A[k * 2 + 1], m.y, m.x);
      }
      STAMP(4);
      float qa[32];
      if (cw == 0) bar_arrive(1, 288);
#pragma unroll 1
      for (int hh = 2, gr = 1;; hh++) {
#pragma unroll
        for (int p = 0; p < 4; p++) {
          if (p == 0) turn_begin();
          const uint32_t db = dB_k + gr * (QG >> 4) + p * 1152;
#pragma unroll
          for (int kk = 0; kk < 9; kk++)
            wgmma64_rs(qa, A[p * 36 + kk * 4], A[p * 36 + kk * 4 + 1], A[p * 36 + kk * 4 + 2], A[p * 36 + kk * 4 + 3], db + kk * 128, (p | kk) != 0);
        }
        wgmma_commit();
        turn_end();
        wgmma_wait<0>();
        if (hh < 7) release1(B_EMPTYQ + gr * 8);
        else if (hh < 9) { release(B_EMPTYA + gr * 16); release(B_EMPTYA + gr * 16 + 8); }
        if (++gr == 3) gr = 0;
#pragma unroll
        for (int j = 0; j < 4; j++)
          qpark[((hh & 7) * 4 + j) * 256] = make_uint4(pack_bf16(qa[8 * j], qa[8 * j + 1]), pack_bf16(qa[8 * j + 2], qa[8 * j + 3]),
                                                       pack_bf16(qa[8 * j + 4], qa[8 * j + 5]), pack_bf16(qa[8 * j + 6], qa[8 * j + 7]));
        if (hh == 9) break;
      }
#pragma unroll
      for (int j = 0; j < 4; j++) {
        const uint4 v = __ldcg(qpark + j * 256);
        Qf[4 * j] = v.x; Qf[4 * j + 1] = v.y; Qf[4 * j + 2] = v.z; Qf[4 * j + 3] = v.w;
      }
#pragma unroll
      for (int j = 0; j < 16; j++) Qf[16 + j] = pack_bf16(qa[2 * j], qa[2 * j + 1]);
    }
    STAMP(5);
    const float sc = 0.08838834764831845f * 1.4426950408889634f;
    float mb0 = 0.f, mb1 = 0.f, l0 = 0.f, l1 = 0.f;
    float i0, i1;
    auto o_scale = [&]() {
      float a0 = l0, a1 = l1;
      a0 += __shfl_xor_sync(~0u, a0, 1); a0 += __shfl_xor_sync(~0u, a0, 2);
      a1 += __shfl_xor_sync(~0u, a1, 1); a1 += __shfl_xor_sync(~0u, a1, 2);
      i0 = rcp(a0); i1 = rcp(a1);
    };
    auto o_frag = [&](int i) {
      return make_uint4(pack_bf16(O[i * 8] * i0, O[i * 8 + 1] * i0), pack_bf16(O[i * 8 + 2] * i1, O[i * 8 + 3] * i1),
                        pack_bf16(O[i * 8 + 4] * i0, O[i * 8 + 5] * i0), pack_bf16(O[i * 8 + 6] * i1, O[i * 8 + 7] * i1));
    };
    auto row_max = [&](float& x0, float& x1) {
      float y0 = fmaxf(S[0], S[1]), y1 = fmaxf(S[2], S[3]), z0 = fmaxf(S[4], S[5]), z1 = fmaxf(S[6], S[7]);
#pragma unroll
      for (int j = 2; j < 16; j += 2) {
        y0 = fmaxf(y0, fmaxf(S[j * 4], S[j * 4 + 1])); y1 = fmaxf(y1, fmaxf(S[j * 4 + 2], S[j * 4 + 3]));
        z0 = fmaxf(z0, fmaxf(S[j * 4 + 4], S[j * 4 + 5])); z1 = fmaxf(z1, fmaxf(S[j * 4 + 6], S[j * 4 + 7]));
      }
      x0 = fmaxf(y0, z0); x1 = fmaxf(y1, z1);
      x0 = fmaxf(x0, __shfl_xor_sync(~0u, x0, 1)); x1 = fmaxf(x1, __shfl_xor_sync(~0u, x1, 1));
      x0 = fmaxf(x0, __shfl_xor_sync(~0u, x0, 2)); x1 = fmaxf(x1, __shfl_xor_sync(~0u, x1, 2));
    };
    float s0, s1;
    auto exps = [&](int j0, int j1) {
#pragma unroll
      for (int j = j0; j < j1; j++) {
        S[j * 4] = ex2(fmaf(S[j * 4], sc, -mb0)); S[j * 4 + 1] = ex2(fmaf(S[j * 4 + 1], sc, -mb0));
        S[j * 4 + 2] = ex2(fmaf(S[j * 4 + 2], sc, -mb1)); S[j * 4 + 3] = ex2(fmaf(S[j * 4 + 3], sc, -mb1));
        s0 += S[j * 4] + S[j * 4 + 1]; s1 += S[j * 4 + 2] + S[j * 4 + 3];
      }
    };
    auto cvtP = [&]() {
#pragma unroll
      for (int i = 0; i < 32; i++) P[i] = pack_bf16(S[2 * i], S[2 * i + 1]);
    };
    auto issue_qk = [&](uint32_t db) {
#pragma unroll
      for (int kk = 0; kk < 8; kk++)
        wgmma128_rs<0>(S, Qf[kk * 4], Qf[kk * 4 + 1], Qf[kk * 4 + 2], Qf[kk * 4 + 3], db + (kk >> 2) * 1024 + (kk & 3) * 2, kk != 0);
    };
    auto issue_pv = [&](uint32_t db, int first) {
#pragma unroll
      for (int kk = 0; kk < 8; kk++) {
        if (kk == TE_POS) turn_end();
        wgmma128_rs<1>(O, P[kk * 4], P[kk * 4 + 1], P[kk * 4 + 2], P[kk * 4 + 3], db + kk * 128, kk ? 1 : !first);
      }
      wgmma_commit();
      if (TE_POS == 8) turn_end();
    };
    auto sched_fence = [&]() {
      asm volatile("st.shared.v2.f32 [%0], {%1,%2};" ::"r"(sb + SM_RED), "f"(s0), "f"(s1) : "memory");
    };
    {
      STAMP(6);
      turn_begin();
      issue_qk(dB_k);
      wgmma_commit();
      turn_end();
      wgmma_wait<0>();
      release(B_EMPTYA);
      s0 = 0.f; s1 = 0.f;
      float x0, x1;
      row_max(x0, x1);
      mb0 = x0 * sc; mb1 = x1 * sc;
      exps(0, 16);
      cvtP();
      l0 = s0; l1 = s1;
    }
    const uint4* qn = qpark + 8 * 256;
    asm volatile("" : "+l"(qn));
    uint32_t kd = dB_k + 4096;
#pragma unroll 1
    for (int t = 1; t < 64; t++, kd ^= 4096) {
      const int j = t & 15, h = t >> 4;
      const int ks = (t & 1) * 2, vs = 3 - ks;
      turn_begin();
      issue_qk(kd);
      wgmma_commit();
      if (cw == 0) bar_sync(10, 160);
      issue_pv(kd ^ (dB_k ^ (dB_n16 + 6144)), j == 1);
      wgmma_wait<1>();
      release(B_EMPTYA + ks * 8);
      if (j == 15 && h < 3) {
#pragma unroll
        for (int i = 0; i < 8; i++) {
          uint4 v;
          if (EF & 4) asm volatile("ld.global.cg.L2::cache_hint.v4.u32 {%0,%1,%2,%3}, [%4], %5;" : "=r"(v.x), "=r"(v.y), "=r"(v.z), "=r"(v.w) : "l"(qn + i * 256), "l"(pol_first()));
          else v = __ldcg(qn + i * 256);
          Qf[4 * i] = v.x; Qf[4 * i + 1] = v.y; Qf[4 * i + 2] = v.z; Qf[4 * i + 3] = v.w;
        }
        qn += 8 * 256;
      }
      s0 = 0.f; s1 = 0.f;
      exps(0, 8);
      sched_fence();
      wgmma_wait<0>();
      release(B_EMPTYA + vs * 8);
      float lo = 0.f;
      if (__builtin_expect(j == 0, 0)) {
        o_scale();
#pragma unroll
        for (int i = 0; i < 8; i++) sts128(sb + SM_STASH + (h - 1) * 32768 + i * 4096 + ct * 16, o_frag(i));
        l0 = 0.f; l1 = 0.f;
        lo = LAZY_LOW;
      }
      bool bad = __any_sync(~0u, !(s0 <= LAZY_LIMIT && s1 <= LAZY_LIMIT));
      if (__builtin_expect(!bad, 1)) {
        exps(8, 16);
        cvtP();
        bad = __any_sync(~0u, !(s0 <= LAZY_LIMIT && s1 <= LAZY_LIMIT && s0 >= lo && s1 >= lo));
      }
      if (__builtin_expect(bad, 0)) {
        const uint32_t* kp = reinterpret_cast<const uint32_t*>(prm.k + ((size_t)kg * 4 * SK + t * 128 + g) * DH) + t4;
        const uint4* qp = qpark + h * (8 * 256);
        float4 tmp[16];
        uint4 qf[8];
#pragma unroll
        for (int kk = 0; kk < 8; kk++) qf[kk] = __ldcg(qp + kk * 256);
#pragma unroll 1
        for (int jn = 0; jn < 16; jn++) {
          float c[4] = {0.f, 0.f, 0.f, 0.f};
#pragma unroll
          for (int kk = 0; kk < 8; kk++) mma16816(c, qf[kk].x, qf[kk].y, qf[kk].z, qf[kk].w, __ldg(kp + jn * 512 + kk * 8), __ldg(kp + jn * 512 + kk * 8 + 4));
          tmp[jn] = make_float4(c[0], c[1], c[2], c[3]);
        }
#pragma unroll
        for (int jn = 0; jn < 16; jn++) { const float4 c = tmp[jn]; S[jn * 4] = c.x; S[jn * 4 + 1] = c.y; S[jn * 4 + 2] = c.z; S[jn * 4 + 3] = c.w; }
        float x0, x1;
        row_max(x0, x1);
        const float n0 = j ? fmaxf(mb0, x0 * sc) : x0 * sc, n1 = j ? fmaxf(mb1, x1 * sc) : x1 * sc;
        const float f0 = j ? ex2(mb0 - n0) : 0.f, f1 = j ? ex2(mb1 - n1) : 0.f;
        mb0 = n0; mb1 = n1;
        l0 *= f0; l1 *= f1;
#pragma unroll
        for (int i = 0; i < 16; i++) { O[i * 4] *= f0; O[i * 4 + 1] *= f0; O[i * 4 + 2] *= f1; O[i * 4 + 3] *= f1; }
        s0 = 0.f; s1 = 0.f;
        exps(0, 16);
        cvtP();
      }
      l0 += s0; l1 += s1;
    }
    STAMP(70);
    turn_begin();
    issue_pv(dB_n16 + 6144, 0);
    {
      const int lane = get_lane();
      uint32_t A[128];
#pragma unroll
      for (int i = 0; i < 16; i++) {
        const uint4 v = lds128(sb + SM_STASH + i * 4096 + ct * 16);
        A[i * 4] = v.x; A[i * 4 + 1] = v.y; A[i * 4 + 2] = v.z; A[i * 4 + 3] = v.w;
      }
      o_scale();
      wgmma_wait<0>();
      release(B_EMPTYA + 24);
#pragma unroll
      for (int i = 16; i < 24; i++) {
        const uint4 v = lds128(sb + SM_STASH + i * 4096 + ct * 16);
        A[i * 4] = v.x; A[i * 4 + 1] = v.y; A[i * 4 + 2] = v.z; A[i * 4 + 3] = v.w;
      }
#pragma unroll
      for (int i = 0; i < 8; i++) {
        const uint4 v = o_frag(i);
        A[96 + i * 4] = v.x; A[96 + i * 4 + 1] = v.y; A[96 + i * 4 + 2] = v.z; A[96 + i * 4 + 3] = v.w;
      }
      if (__any_sync(~0u, A[95] != 0x12345678u || A[64] != 0x9abcdef0u || lane == 0)) release1(B_ST);
      STAMP(71);
      const uint32_t xb = sb + SM_XCH + w8 * 2048 + lane * 16;
      const uint32_t peer = __shfl_sync(~0u, relBar, 1) - sBar;
      float c0[32], c1[32];
      int gr = 0;
      auto send = [&](const float* v, int xp) {
#pragma unroll
        for (int j = 0; j < 4; j++)
          asm volatile("st.async.shared::cluster.mbarrier::complete_tx::bytes.v4.f32 [%0], {%1,%2,%3,%4}, [%5];" ::"r"(xb + peer + xp * 16384 + j * 512),
                       "f"(v[j * 4]), "f"(v[j * 4 + 1]), "f"(v[j * 4 + 2]), "f"(v[j * 4 + 3]), "r"(sBar + B_XF + xp * 8 + peer) : "memory");
      };
      auto recv = [&](const float* v, int xp) {
        uint4 u[4];
#pragma unroll
        for (int j = 0; j < 4; j++) u[j] = lds128(xb + xp * 16384 + j * 512);
#pragma unroll
        for (int j = 0; j < 4; j++) {
          const float x = v[j * 4] + __uint_as_float(u[j].x), y = v[j * 4 + 1] + __uint_as_float(u[j].y), z = v[j * 4 + 2] + __uint_as_float(u[j].z), w = v[j * 4 + 3] + __uint_as_float(u[j].w);
          sts128(xb + (SM_OUT - SM_XCH) + xp * 16384 + j * 512, make_uint4(__float_as_uint(x), __float_as_uint(y), __float_as_uint(z), __float_as_uint(w)));
        }
      };
      auto chunk = [&](float (&acc)[32], float (&prev)[32], bool has_prev, bool last, int xp) {
#pragma unroll
        for (int hd = 0; hd < 4; hd++) {
          if (!(hd & 1)) turn_begin();
          const uint32_t db = dB_k + (gr + (hd & 1)) * 1024;
#pragma unroll
          for (int kk = 0; kk < 8; kk++)
            wgmma64_rs(acc, A[hd * 32 + kk * 4], A[hd * 32 + kk * 4 + 1], A[hd * 32 + kk * 4 + 2], A[hd * 32 + kk * 4 + 3], db + kk * 128, (hd | kk) != 0);
          wgmma_commit();
          if (hd & 1) {
            if (hd == 1 || !last || cw == 0) turn_end();
            if (hd == 1 ? last : has_prev && !last) {
              if (hd == 1) mbar_wait(sBar + B_XF + 8, 1);
              if (rank) recv(prev + 16, xp ^ 1); else recv(prev, xp ^ 1);
              bar_arrive(8 + cw, 160);
            }
            wgmma_wait<1>();
            release1(B_EMPTYO + gr * 8);
            wgmma_wait<0>();
            release1(B_EMPTYO + gr * 8 + 8);
            if ((gr += 2) == 6) gr = 0;
          }
        }
        if (!last) {
          if (!has_prev) mbar_wait(sBar + B_EMPTYA + 24, 0);
          if (rank) send(acc, xp); else send(acc + 16, xp);
        }
      };
#pragma unroll 1
      for (int cp = 0;; cp++) {
        chunk(c0, c1, cp != 0, cp == 4, 0);
        if (cp == 4) break;
        chunk(c1, c0, true, false, 1);
      }
      STAMP(72);
#pragma unroll
      for (int jb = 0; jb < 8; jb++)
        sts128(xb + (jb >> 2) * 16384 + (jb & 3) * 512, make_uint4(__float_as_uint(c0[jb * 4]), __float_as_uint(c0[jb * 4 + 1]), __float_as_uint(c0[jb * 4 + 2]), __float_as_uint(c0[jb * 4 + 3])));
      __syncwarp();
      if (lane == 0) {
        fence_async();
        float4* const dst = g_acc + (qt * 8 + w8) * 2304 + (kg ? kg * 2 - 1 : 8) * 256;
        asm volatile("cp.reduce.async.bulk.global.shared::cta.bulk_group.add.f32 [%0], [%1], 2048;" ::"l"(dst), "r"(xb) : "memory");
        asm volatile("cp.reduce.async.bulk.global.shared::cta.bulk_group.add.f32 [%0], [%1], 2048;" ::"l"(dst + 128), "r"(xb + 16384) : "memory");
        asm volatile("cp.async.bulk.commit_group;" ::: "memory");
      }
      __syncwarp();
    }
    STAMP(73);
    {
    const int lane = get_lane(), g = lane >> 2, t4 = lane & 3;
    uint32_t* const tsu = reinterpret_cast<uint32_t*>(smem_raw + SM_T);
    float* const tsf = reinterpret_cast<float*>(smem_raw + SM_T);
    const int row0 = qt * 128 + hg * 16;
    {
      uint32_t xa[9], xb[9];
      uint4 md[9];
      float wa[18], sumA = 0.f, sumB = 0.f;
      const float4* ap = g_acc + (qt * 8 + hg) * 2304 + w8 * 32 + lane;
      float4 av[9];
      auto ld_acc = [&](int i) { const uint4 u = ldr4(ap + i * 256); av[i] = make_float4(__uint_as_float(u.x), __uint_as_float(u.y), __uint_as_float(u.z), __uint_as_float(u.w)); };
      mbar_wait(sBar + B_MD, 0);
#pragma unroll
      for (int i = 0; i < 9; i++) {
        const uint4 m = lds128(sb + SM_MD + (lane + i * 32) * 16);
        const uint32_t w = *reinterpret_cast<const uint32_t*>(smem_raw + SM_MD + 4608 + (lane + i * 32) * 4);
        sumA = fmaf(bf_lo(m.z), bf_lo(w), fmaf(bf_hi(m.z), bf_hi(w), sumA));
        sumB = fmaf(bf_lo(m.y), bf_lo(w), fmaf(bf_hi(m.y), bf_hi(w), sumB));
      }
#pragma unroll
      for (int i = 0; i < 9; i++) {
        md[i] = lds128(sb + SM_MD + (i * 32 + w8 * 4 + t4) * 16);
        const uint32_t w = *reinterpret_cast<const uint32_t*>(smem_raw + SM_MD + 4608 + (i * 32 + w8 * 4 + t4) * 4);
        wa[2 * i] = bf_lo(md[i].z) * bf_lo(w); wa[2 * i + 1] = bf_hi(md[i].z) * bf_hi(w);
      }
      sumA = warp_sum(sumA); sumB = warp_sum(sumB);
      if (lane == 0) {
        asm volatile("cp.async.bulk.wait_group 0;" ::: "memory");
        REL_FENCE();
        asm volatile("red.relaxed.gpu.global.add.u32 [%0], 1;" ::"l"(&g_cnt[(C_Q + qt * 8 + w8) * 32 + 1]) : "memory");
      }
      __syncwarp();
      STAMP(50);
      mbar_wait(sBar + B_G1, 0);
      STAMP(74);
      ld_acc(6); ld_acc(0); ld_acc(2); ld_acc(4); ld_acc(7);
      mbar_wait(sBar + B_FULLO + 24, 0);
      uint32_t* const tr = reinterpret_cast<uint32_t*>(smem_raw + SM_X2) + g * 292 + w8 * 4 + t4;
#pragma unroll
      for (int i = 0; i < 9; i++) { xa[i] = tr[i * 32]; xb[i] = tr[8 * 292 + i * 32]; }
      mbar_wait(sBar + B_G2, 0);
      STAMP(48);
      ld_acc(8); ld_acc(1); ld_acc(3); ld_acc(5);
      auto x2 = [&](int i) {
        xa[i] = hadd2(xa[i], hmul2(md[i].x, pack_bf16(av[i].x, av[i].y)));
        xb[i] = hadd2(xb[i], hmul2(md[i].x, pack_bf16(av[i].z, av[i].w)));
      };
      float pA, pB, st[6] = {0.f, 0.f, 0.f, 0.f, 0.f, 0.f};
      auto stat = [&](int i) {
        const float v0 = bf_lo(xa[i]), v1 = bf_hi(xa[i]), v2 = bf_lo(xb[i]), v3 = bf_hi(xb[i]);
        const float d0 = v0 - pA, d1 = v1 - pA, d2 = v2 - pB, d3 = v3 - pB;
        st[0] += d0 + d1; st[3] += d2 + d3;
        st[1] = fmaf(d0, d0, fmaf(d1, d1, st[1])); st[4] = fmaf(d2, d2, fmaf(d3, d3, st[4]));
        st[2] = fmaf(v0, wa[2 * i], fmaf(v1, wa[2 * i + 1], st[2])); st[5] = fmaf(v2, wa[2 * i], fmaf(v3, wa[2 * i + 1], st[5]));
      };
      x2(6);
      const uint32_t piv = __shfl_sync(~0u, __byte_perm(xa[6], xb[6], 0x5410), lane & 28);
      pA = bf_lo(piv); pB = bf_hi(piv);
      stat(6);
#pragma unroll
      for (int i = 0; i < 4; i++) { x2((2 * i + 7) % 9); stat((2 * i + 7) % 9); }
      asm volatile("st.shared.f32 [%0], %1;" ::"r"(sb + SM_RED + lane * 4), "f"(st[1] + st[4] + st[2] + st[5]) : "memory");
      STAMP(77);
#pragma unroll
      for (int i = 0; i < 4; i++) { x2((2 * i + 8) % 9); stat((2 * i + 8) % 9); }
      STAMP(40);
      const bool odd = lane & 1;
#pragma unroll
      for (int i = 0; i < 3; i++) { const float snd = odd ? st[i] : st[i + 3], kp = odd ? st[i + 3] : st[i]; st[i] = kp + __shfl_xor_sync(~0u, snd, 1); }
#pragma unroll
      for (int i = 0; i < 3; i++) st[i] += __shfl_xor_sync(~0u, st[i], 2);
      float4* const ps = reinterpret_cast<float4*>(smem_raw + SM_FILL);
      if (t4 < 2) ps[w8 * 16 + t4 * 8 + g] = make_float4(fmaf(st[0], 1.f / 72, odd ? pB : pA), fmaf(st[0] * st[0], -1.f / 72, st[1]), st[2], 0.f);
      bar_sync(5, 256);
      STAMP(44);
      float4 q[4];
#pragma unroll
      for (int i = 0; i < 4; i++) q[i] = ps[i * 32 + lane];
      float mean = (q[0].x + q[1].x) + (q[2].x + q[3].x), dot = (q[0].z + q[1].z) + (q[2].z + q[3].z);
      mean += __shfl_xor_sync(~0u, mean, 16);
      dot += __shfl_xor_sync(~0u, dot, 16);
      mean *= 0.125f;
      float m2 = (q[0].y + q[1].y) + (q[2].y + q[3].y);
#pragma unroll
      for (int i = 0; i < 4; i++) { const float d = q[i].x - mean; m2 = fmaf(d * 72.f, d, m2); }
      m2 += __shfl_xor_sync(~0u, m2, 16);
      const float rs = rcp(bfr(sqrt_a(bfr(bfr(fmaxf(m2 * (1.f / DM), 0.f)) + 1e-5f))));
      const uint32_t nm = pack_bf16(-mean, -mean);
      uint32_t u = pack_bf16(0.f, fmaf(rs, fmaf(bf_lo(nm), sumA, dot), sumB));
      u = ((u & 0x7fff0000u) > 0x7f800000u) ? 0u : (u ^ ((u >> 31) ? 0xffff0000u : 0x80000000u));
      u |= 0xffffu - (row0 + (lane & 15));
      const uint32_t m1 = __reduce_max_sync(~0u, u), m2k = __reduce_max_sync(~0u, u == m1 ? 0u : u);
      if (w8 == 7) asm volatile("st.relaxed.gpu.global.v2.u32 [%0], {%1,%2};" ::"l"(reinterpret_cast<uint2*>(g_zero + Z_KEY) + lane * 128 + b), "r"(m1), "r"(m2k) : "memory");
      STAMP(41);
      const int r1 = ~m1 & 15, r2 = ~m2k & 15;
      const float rA = __shfl_sync(~0u, rs, g), rB = __shfl_sync(~0u, rs, g + 8);
      const uint32_t nmA = __shfl_sync(~0u, nm, g), nmB = __shfl_sync(~0u, nm, g + 8);
      uint32_t ha[9], hb[9];
#pragma unroll
      for (int i = 0; i < 9; i++) {
        const uint32_t da = hadd2(xa[i], nmA), db = hadd2(xb[i], nmB);
        ha[i] = hadd2(hmul2(pack_bf16(bf_lo(da) * rA, bf_hi(da) * rA), md[i].z), md[i].y);
        hb[i] = hadd2(hmul2(pack_bf16(bf_lo(db) * rB, bf_hi(db) * rB), md[i].z), md[i].y);
      }
      uint32_t* const hx = reinterpret_cast<uint32_t*>(g_ones + F_HX + b * 288) + w8 * 4 + t4;
      const bool topA = g == r1 || g == r2, topB = g + 8 == r1 || g + 8 == r2;
      const int slot = topA ? g == r2 : g + 8 == r2;
      if (topA || topB) {
#pragma unroll
        for (int i = 0; i < 9; i++) str1(hx + slot * 576 + i * 32, topA ? ha[i] : hb[i]);
      }
      if (topA && topB) {
#pragma unroll
        for (int i = 0; i < 9; i++) str1(hx + (slot ^ 1) * 576 + i * 32, hb[i]);
#pragma unroll
        for (int i = 0; i < 9; i++) str1(hx + (slot ^ 1) * 576 + 288 + i * 32, xb[i]);
      }
      if (topA || topB) {
#pragma unroll
        for (int i = 0; i < 9; i++) str1(hx + slot * 576 + 288 + i * 32, topA ? xa[i] : xb[i]);
      }
#pragma unroll
      for (int i = 0; i < 9; i++) {
        tr[i * 32] = hadd2(xa[i], hmul2(md[i].w, ha[i]));
        tr[8 * 292 + i * 32] = hadd2(xb[i], hmul2(md[i].w, hb[i]));
      }
      if (tid == 128) tsu[34] = (1u << r1) | (1u << r2);
      bar_arrive(11, 288);
    }
    STAMP(75);
    const int kq = w8 >> 1;
    const int ng = w8 < 2 ? 3 : 2;
    uint32_t bg[9][10], bd[12][5];
    mbar_wait(sBar + B_FFN, 0);
    STAMP(42);
    {
      const uint32_t wa = sb + ((w8 & 1) ? SM_WU : SM_WG) + (kq * 144 + (lane & 6) * 2 + ((lane >> 2) & 2) + (lane & 1)) * 80 + (lane >> 4) * 16;
#pragma unroll
      for (int ks = 0; ks < 9; ks++) {
        uint32_t b0[4], b1[4], b2[2];
        ldsm4t(b0, wa + ks * 1280); ldsm4t(b1, wa + ks * 1280 + 32); ldsm2t(b2, wa + ks * 1280 + 64 - (lane >> 4) * 16);
#pragma unroll
        for (int i = 0; i < 4; i++) { bg[ks][i] = b0[i]; bg[ks][4 + i] = b1[i]; }
        bg[ks][8] = b2[0]; bg[ks][9] = b2[1];
      }
#pragma unroll
      for (int i = 0; i < 12; i++) {
        if (i < 8 || ng == 3) {
          const int bx = (w8 >> 1) + (i >> 2) * 4;
          const uint32_t a = sb + bx * 5120 + lane * 128 + (((((w8 & 1) * 4 + (i & 3)) ^ lane) & 7) << 4);
          uint32_t b0[4];
          ldsm4t(b0, a);
          asm volatile("ldmatrix.sync.aligned.m8n8.x1.trans.shared.b16 {%0}, [%1];" : "=r"(bd[i][4]) : "r"(a + 4096) : "memory");
#pragma unroll
          for (int j = 0; j < 4; j++) bd[i][j] = b0[j];
        }
      }
    }
    STAMP(43);
    mbar_wait(sBar + B_G3, 0);
    STAMP(76);
    {
      float c[2][5][4];
#pragma unroll
      for (int i = 0; i < 10; i++) c[i & 1][i >> 1][0] = c[i & 1][i >> 1][1] = c[i & 1][i >> 1][2] = c[i & 1][i >> 1][3] = 0.f;
      const uint2* hp = reinterpret_cast<const uint2*>(smem_raw + SM_T + 4096) + (g & 1) * 144 + kq * 36 + t4;
#pragma unroll
      for (int ks = 0; ks < 9; ks++) {
        const uint2 a = hp[ks * 4];
#pragma unroll
        for (int i = 0; i < 5; i++) mma16816(c[ks & 1][i], a.x, 0u, a.y, 0u, bg[ks][2 * i], bg[ks][2 * i + 1]);
      }
      float* const part = tsf + 64;
      if (g < 2) {
#pragma unroll
        for (int i = 0; i < 5; i++)
          *reinterpret_cast<float2*>(part + w8 * 80 + g * 40 + i * 8 + t4 * 2) = make_float2(c[0][i][0] + c[1][i][0], c[0][i][1] + c[1][i][1]);
      }
      STAMP(45);
      bar_sync(5, 256);
      STAMP(46);
      auto act2 = [&](int f) {
        const float2* pp = reinterpret_cast<const float2*>(part + (g & 1) * 40 + f + (b & 1) * 4);
        const float2 g0 = pp[0], g1 = pp[80], g2 = pp[160], g3 = pp[240], u0 = pp[40], u1 = pp[120], u2 = pp[200], u3 = pp[280];
        return pack_bf16(silu_bf(bfr((g0.x + g1.x) + (g2.x + g3.x))) * bfr((u0.x + u1.x) + (u2.x + u3.x)),
                         silu_bf(bfr((g0.y + g1.y) + (g2.y + g3.y))) * bfr((u0.y + u1.y) + (u2.y + u3.y)));
      };
      const uint32_t v0 = act2((g >> 1) * 8 + t4 * 2), v1 = act2(32 + (t4 & 1) * 2);
      uint32_t a6[5];
#pragma unroll
      for (int i = 0; i < 4; i++) a6[i] = __shfl_sync(~0u, v0, i * 8 + (lane & 7));
      a6[4] = t4 < 2 ? v1 : 0u;
      STAMP(47);
      float* const yp = reinterpret_cast<float*>(g_ones + F_YP) + ((w8 * 2 + (g & 1)) * 128 + b) * 32 + (g >> 1) * 8 + t4 * 2;
#pragma unroll
      for (int m = 0; m < 3; m++) {
        if (m < 2 || ng == 3) {
          float y[4][4];
#pragma unroll
          for (int i = 0; i < 4; i++) {
            y[i][0] = y[i][1] = y[i][2] = y[i][3] = 0.f;
            mma16816(y[i], a6[0], 0u, a6[1], 0u, bd[m * 4 + i][0], bd[m * 4 + i][1]);
          }
#pragma unroll
          for (int i = 0; i < 4; i++) mma16816(y[i], a6[2], 0u, a6[3], 0u, bd[m * 4 + i][2], bd[m * 4 + i][3]);
#pragma unroll
          for (int i = 0; i < 4; i++) mma1688(y[i], a6[4], 0u, bd[m * 4 + i][4]);
          const bool u1 = lane & 8, u2 = lane & 16;
          const float y0 = u2 ? (u1 ? y[3][0] : y[2][0]) : (u1 ? y[1][0] : y[0][0]), y1 = u2 ? (u1 ? y[3][1] : y[2][1]) : (u1 ? y[1][1] : y[0][1]);
          asm volatile("st.relaxed.gpu.global.v2.f32 [%0], {%1,%2};" ::"l"(yp + m * (16 * 4096)), "f"(y0), "f"(y1) : "memory");
        }
      }
    }
    STAMP(78);
    const uint32_t k1 = tsu[32], k2 = tsu[33];
    const int row1 = ~k1 & (SQ - 1), row2 = ~k2 & (SQ - 1);
    const int f = b + 128 * (7 - w8);
    if (f < 144) {
      const int tok = (f >> 2) & 1, col = ((f >> 3) * 4 + (f & 3)) * 8 + (lane & 1) * 4 + (lane & 2) + ((lane >> 2) & 1);
      const uint32_t key = tok ? k2 : k1;
      const int row = tok ? row2 : row1;
      const int c1 = ((row1 >> 5) & 3) * 32 + (row1 >> 7) * 2 + ((row1 >> 4) & 1), cr = ((row >> 5) & 3) * 32 + (row >> 7) * 2 + ((row >> 4) & 1);
      const uint16_t* xp = reinterpret_cast<const uint16_t*>(g_ones + F_HX + cr * 288 + (tok && c1 == cr ? 144 : 0) + 72) + col;
      const float gb = __uint_as_float((uint32_t)reinterpret_cast<const uint16_t*>(smem_raw + SM_MD)[(col >> 1) * 8 + 6 + (col & 1)] << 16);
      const float hv = __uint_as_float((uint32_t)reinterpret_cast<const uint16_t*>(smem_raw + SM_T + 4096)[tok * DM + col] << 16);
      const float r = __uint_as_float((key & 0xffff0000u) ^ ((key >> 31) ? 0x80000000u : 0xffff0000u));
      const float sg = bfr(rcp(1.f + __expf(-r)));
      const uint4* pp = g_ones + F_YP + (f >> 2) * 1024 + (f & 3) * 2 + (lane >> 1) * 8 + (lane & 1);
      uint4 pv[8];
      uint16_t xv;
      PSTAMP(352, 62);
#pragma unroll 1
      for (uint32_t n = 0;; n++) {
        asm volatile("ld.relaxed.gpu.global.u16 %0, [%1];" : "=h"(xv) : "l"(xp) : "memory");
#pragma unroll
        for (int i = 0; i < 8; i++) pv[i] = ldr4(pp + i * 128);
        bool bad = xv == 0xffff;
#pragma unroll
        for (int i = 0; i < 8; i++) bad |= unset(pv[i]);
        if (!bad) break;
        if (n > (1u << 15)) { SETERR(32); break; }
      }
      __syncwarp();
      PSTAMP(352, 63);
      float s[4];
#pragma unroll
      for (int j = 0; j < 4; j++) {
        auto w = [&](int i) { return __uint_as_float(j == 0 ? pv[i].x : j == 1 ? pv[i].y : j == 2 ? pv[i].z : pv[i].w); };
        s[j] = ((w(0) + w(1)) + (w(2) + w(3))) + ((w(4) + w(5)) + (w(6) + w(7)));
      }
      const bool u2 = lane & 2, u4 = lane & 4;
#pragma unroll
      for (int i = 0; i < 2; i++) { const float snd = u2 ? s[i] : s[i + 2], kp = u2 ? s[i + 2] : s[i]; s[i] = kp + __shfl_xor_sync(~0u, snd, 2); }
      { const float snd = u4 ? s[0] : s[1], kp = u4 ? s[1] : s[0]; s[0] = kp + __shfl_xor_sync(~0u, snd, 4); }
      s[0] += __shfl_xor_sync(~0u, s[0], 8);
      s[0] += __shfl_xor_sync(~0u, s[0], 16);
      const float hh = bfr(hv + bfr(bfr(s[0]) * sg));
      if (lane < 8) prm.out[(size_t)row * DM + col] = __float2bfloat16(__uint_as_float((uint32_t)xv << 16) + bfr(gb * hh));
      PSTAMP(352, 49);
    }
    if (w8 == 5 && lane < 9) g_mod1[b * 9 + lane] = make_uint4(0u, 0u, 0u, 0u);
    if (w8 == 5 && lane == 9) *reinterpret_cast<uint2*>(&g_cnt[(C_Q + b) * 32]) = make_uint2(0u, 0u);
    if (w8 == 5 && lane == 10 && b == 0) g_cnt[C_SIDE * 32] = 0;
    STAMP(79); GSTAMP(91);
    }
  }
}

typedef CUresult (*PFN_enc)(CUtensorMap*, CUtensorMapDataType, cuuint32_t, void*, const cuuint64_t*, const cuuint64_t*,
                            const cuuint32_t*, const cuuint32_t*, CUtensorMapInterleave, CUtensorMapSwizzle,
                            CUtensorMapL2promotion, CUtensorMapFloatOOBfill);
static PFN_enc g_enc = nullptr;
static CUtensorMap mk_map(const void* p, uint64_t cols, uint64_t rows, uint32_t bc, uint32_t br, bool swz = true) {
  CUtensorMap m;
  cuuint64_t dims[2] = {cols, rows};
  cuuint64_t strides[1] = {cols * 2};
  cuuint32_t box[2] = {bc, br}, es[2] = {1, 1};
  g_enc(&m, CU_TENSOR_MAP_DATA_TYPE_BFLOAT16, 2, const_cast<void*>(p), dims, strides, box, es, CU_TENSOR_MAP_INTERLEAVE_NONE,
        swz ? CU_TENSOR_MAP_SWIZZLE_128B : CU_TENSOR_MAP_SWIZZLE_NONE, swz ? CU_TENSOR_MAP_L2_PROMOTION_L2_128B : CU_TENSOR_MAP_L2_PROMOTION_NONE,
        CU_TENSOR_MAP_FLOAT_OOB_FILL_NONE);
  return m;
}

extern "C" void kernel_launch(void* const* d_in, const int* in_sizes, int n_in, void* d_out, int out_size) {
  if (!g_enc) {
    cudaDriverEntryPointQueryResult st;
    cudaGetDriverEntryPoint("cuTensorMapEncodeTiled", (void**)&g_enc, cudaEnableDefault, &st);
    cudaFuncSetAttribute(k_mega, cudaFuncAttributeMaxDynamicSharedMemorySize, SM_TOTAL);
  }
  CUtensorMap mX = mk_map(d_in[0], DM, SQ, 64, 128);
  CUtensorMap mWq = mk_map(d_in[3], HQ * DH, DM, 64, 144);
  CUtensorMap mK = mk_map(d_in[1], DH, HKV * SK, 64, 128);
  CUtensorMap mV = mk_map(d_in[2], DH, HKV * SK, 64, 128);
  CUtensorMap mWo = mk_map(d_in[4], DM, HQ * DH, 64, 128);
  CUtensorMap mWg = mk_map(d_in[7], FF, DM, 40, 48, false);
  CUtensorMap mWu = mk_map(d_in[8], FF, DM, 40, 48, false);
  CUtensorMap mWd = mk_map(d_in[9], DM, FF, 64, 40);
  Params prm;
  prm.x = (const bf16*)d_in[0]; prm.k = (const bf16*)d_in[1]; prm.v = (const bf16*)d_in[2]; prm.wo = (const bf16*)d_in[4]; prm.wq = (const bf16*)d_in[3];
  prm.w_r = (const bf16*)d_in[6]; prm.c = (const bf16*)d_in[10]; prm.w_mod = (const bf16*)d_in[11];
  prm.wg = (const bf16*)d_in[7]; prm.wu = (const bf16*)d_in[8]; prm.wd = (const bf16*)d_in[9];
  prm.out = (bf16*)d_out;
  cudaLaunchConfig_t cfg = {};
  cfg.gridDim = dim3(128); cfg.blockDim = dim3(384); cfg.dynamicSmemBytes = SM_TOTAL; cfg.stream = cudaStreamPerThread;
  cudaLaunchAttribute at[1];
  at[0].id = cudaLaunchAttributeClusterDimension;
  at[0].val.clusterDim.x = 2; at[0].val.clusterDim.y = 1; at[0].val.clusterDim.z = 1;
  cfg.attrs = at; cfg.numAttrs = 1;
  cudaLaunchKernelEx(&cfg, k_mega, mX, mWq, mK, mV, mWo, mWg, mWu, mWd, prm);
}
```

```cpp
#include <cuda_runtime.h>
#include <cuda_bf16.h>
#include <cuda.h>
#include <stdint.h>

typedef __nv_bfloat16 bf16;

constexpr int SQ = 2048, DM = 576, HQ = 32, HKV = 16, SK = 2048, DH = 128, FF = 4608;

#define XPF 0
#define WQPF0 0
#define WQPF1 0xff
#define FFNQ 2
#define WQPF2 0
#define QTH 7
#define MPF 1
#define FILLP 31
#define FILL0 25
#define FFN0 20
#define FILLN 8
#define FFNB 6
#define PF0 22
#define FFNR 1
#define FFND 1
#define KV0 16
#define KVS 2
#define QPF 6
#define EF 31
#define WOP 20
#define TLBW 0
#define NOFFN 0
#define FLATE 0
#define RELF 1
#define REL_FENCE() asm volatile("fence.acq_rel.gpu;" ::: "memory")
#define FILLMAX (F_N / 128)
#define XN 4
#define MODB 0
#define QPV 0
#define LATEG 3
#define RETL 1
#define HINTA 13
#define SIDEF 3
#define FFNE 15
#define TE_POS 8
#define LAZY_LIMIT 1.8446744e19f
#define LAZY_LOW 5.4210109e-20f
__device__ uint4 g_mod1[8 * 144];
__device__ uint4 g_mod2[288];
__device__ uint4 g_q[128 * 4 * 8 * 256];
constexpr int F_HX = 0;
constexpr int F_YP = 128 * 288;
constexpr int F_KEY = 128 * 576;
constexpr int F_PART = 128 * 640;
constexpr int F_N = 640 + 5120;
__device__ uint4 g_ones[128 * F_N];
__device__ unsigned int g_cnt[136 * 32];
__device__ unsigned int g_err;
#define HAS_ERR
enum { C_SIDE = 1, C_Q = 8 };

#define STAMP(i)
#define KSTAMP(i)
#define GSTAMP(i)
#define SETERR(v)
#define PSTAMP(t, i)

__device__ __forceinline__ int get_lane() {
  int l;
  asm volatile("mov.u32 %0, %%laneid;" : "=r"(l));
  __builtin_assume(l >= 0 && l < 32);
  return l;
}
__device__ __forceinline__ uint32_t smem_u32(const void* p) { return (uint32_t)__cvta_generic_to_shared(p); }
__device__ __forceinline__ void mbar_init(uint32_t a, uint32_t cnt) { asm volatile("mbarrier.init.shared::cta.b64 [%0], %1;" ::"r"(a), "r"(cnt)); }
__device__ __forceinline__ void mbar_expect_tx(uint32_t a, uint32_t bytes) { asm volatile("mbarrier.arrive.expect_tx.shared::cta.b64 _, [%0], %1;" ::"r"(a), "r"(bytes) : "memory"); }
__device__ __forceinline__ void mbar_arrive(uint32_t a) { asm volatile("mbarrier.arrive.shared::cta.b64 _, [%0];" ::"r"(a) : "memory"); }
__device__ __forceinline__ void mbar_arrive_cl(uint32_t a_cluster) { asm volatile("mbarrier.arrive.shared::cluster.b64 _, [%0];" ::"r"(a_cluster) : "memory"); }
__device__ __forceinline__ void mbar_wait(uint32_t a, uint32_t parity) {
  asm volatile(
      "{\n.reg .pred p;\n.reg .u32 n;\nmov.u32 n, 0;\n"
      "WAIT_LOOP:\n"
      "mbarrier.try_wait.parity.shared::cta.b64 p, [%0], %1;\n"
      "@p bra WAIT_DONE;\n"
      "add.u32 n, n, 1;\n"
      "setp.lt.u32 p, n, 65536;\n"
      "@p bra WAIT_LOOP;\n"
      "WAIT_DONE:\n}\n" ::"r"(a), "r"(parity), "l"(&g_err) : "memory");
}
__device__ __forceinline__ void cnt_wait(int idx, unsigned target) {
  for (uint32_t n = 0;; n++) {
    unsigned v;
    asm volatile("ld.relaxed.gpu.global.u32 %0, [%1];" : "=r"(v) : "l"(&g_cnt[idx * 32]) : "memory");
    if (v >= target) break;
    if (n > (1u << 15)) { SETERR(2); break; }
  }
}
__device__ __forceinline__ void cnt_wait1(int word, unsigned target) {
  for (uint32_t n = 0;; n++) {
    unsigned v;
    asm volatile("ld.relaxed.gpu.global.u32 %0, [%1];" : "=r"(v) : "l"(&g_cnt[word]) : "memory");
    if (v >= target) break;
    if (n > (1u << 15)) { SETERR(2); break; }
  }
}
__device__ __forceinline__ void cnt_arrive(int idx) {
  asm volatile("red.relaxed.gpu.global.add.u32 [%0], 1;" ::"l"(&g_cnt[idx * 32]) : "memory");
}
__device__ __forceinline__ uint4 poll4(const uint4* p) {
  uint4 v;
  uint32_t n = 0;
  while (true) {
    asm volatile("ld.relaxed.gpu.global.v4.u32 {%0,%1,%2,%3}, [%4];" : "=r"(v.x), "=r"(v.y), "=r"(v.z), "=r"(v.w) : "l"(p) : "memory");
    if (v.x && v.y && v.z && v.w) break;
    if (++n > (1u << 15)) { SETERR(4); break; }
  }
  return v;
}
__device__ __forceinline__ void poll8(const uint4* p, const uint4* q, uint4& v, uint4& w) {
  uint32_t n = 0;
  while (true) {
    asm volatile("ld.relaxed.gpu.global.v4.u32 {%0,%1,%2,%3}, [%4];" : "=r"(v.x), "=r"(v.y), "=r"(v.z), "=r"(v.w) : "l"(p) : "memory");
    asm volatile("ld.relaxed.gpu.global.v4.u32 {%0,%1,%2,%3}, [%4];" : "=r"(w.x), "=r"(w.y), "=r"(w.z), "=r"(w.w) : "l"(q) : "memory");
    if (v.x && v.y && v.z && v.w && w.x && w.y && w.z && w.w) break;
    if (++n > (1u << 15)) { SETERR(4); break; }
  }
}
__device__ __forceinline__ uint4 ldr4(const void* p) {
  uint4 v;
  asm volatile("ld.relaxed.gpu.global.v4.u32 {%0,%1,%2,%3}, [%4];" : "=r"(v.x), "=r"(v.y), "=r"(v.z), "=r"(v.w) : "l"(p) : "memory");
  return v;
}
__device__ __forceinline__ uint2 ldr2(const void* p) {
  uint2 v;
  asm volatile("ld.relaxed.gpu.global.v2.u32 {%0,%1}, [%2];" : "=r"(v.x), "=r"(v.y) : "l"(p) : "memory");
  return v;
}
__device__ __forceinline__ uint32_t ldr1(const void* p) {
  uint32_t v;
  asm volatile("ld.relaxed.gpu.global.u32 %0, [%1];" : "=r"(v) : "l"(p) : "memory");
  return v;
}
__device__ __forceinline__ void str1(void* p, uint32_t v) { asm volatile("st.relaxed.gpu.global.u32 [%0], %1;" ::"l"(p), "r"(v) : "memory"); }
__device__ __forceinline__ bool unset(uint4 v) { return v.x == ~0u || v.y == ~0u || v.z == ~0u || v.w == ~0u; }
__device__ __forceinline__ uint32_t hmul2(uint32_t a, uint32_t b) { uint32_t r; asm("mul.rn.bf16x2 %0, %1, %2;" : "=r"(r) : "r"(a), "r"(b)); return r; }
__device__ __forceinline__ uint32_t hadd2(uint32_t a, uint32_t b) { uint32_t r; asm("add.rn.bf16x2 %0, %1, %2;" : "=r"(r) : "r"(a), "r"(b)); return r; }
__device__ __forceinline__ uint32_t hfma2(uint32_t a, uint32_t b, uint32_t c) { uint32_t r; asm("fma.rn.bf16x2 %0, %1, %2, %3;" : "=r"(r) : "r"(a), "r"(b), "r"(c)); return r; }
__device__ __forceinline__ void mma16816(float (&c)[4], uint32_t a0, uint32_t a1, uint32_t a2, uint32_t a3, uint32_t b0, uint32_t b1) {
  asm volatile("mma.sync.aligned.m16n8k16.row.col.f32.bf16.bf16.f32 {%0,%1,%2,%3}, {%4,%5,%6,%7}, {%8,%9}, {%0,%1,%2,%3};"
               : "+f"(c[0]), "+f"(c[1]), "+f"(c[2]), "+f"(c[3]) : "r"(a0), "r"(a1), "r"(a2), "r"(a3), "r"(b0), "r"(b1));
}
__device__ __forceinline__ void mma1688(float (&c)[4], uint32_t a0, uint32_t a1, uint32_t b0) {
  asm volatile("mma.sync.aligned.m16n8k8.row.col.f32.bf16.bf16.f32 {%0,%1,%2,%3}, {%4,%5}, {%6}, {%0,%1,%2,%3};"
               : "+f"(c[0]), "+f"(c[1]), "+f"(c[2]), "+f"(c[3]) : "r"(a0), "r"(a1), "r"(b0));
}
__device__ __forceinline__ void ldsm4t(uint32_t (&r)[4], uint32_t a) {
  asm volatile("ldmatrix.sync.aligned.m8n8.x4.trans.shared.b16 {%0,%1,%2,%3}, [%4];" : "=r"(r[0]), "=r"(r[1]), "=r"(r[2]), "=r"(r[3]) : "r"(a) : "memory");
}
__device__ __forceinline__ void ldsm4(uint32_t (&r)[4], uint32_t a) {
  asm volatile("ldmatrix.sync.aligned.m8n8.x4.shared.b16 {%0,%1,%2,%3}, [%4];" : "=r"(r[0]), "=r"(r[1]), "=r"(r[2]), "=r"(r[3]) : "r"(a) : "memory");
}
__device__ __forceinline__ void ldsm2t(uint32_t (&r)[2], uint32_t a) {
  asm volatile("ldmatrix.sync.aligned.m8n8.x2.trans.shared.b16 {%0,%1}, [%2];" : "=r"(r[0]), "=r"(r[1]) : "r"(a) : "memory");
}
__device__ __forceinline__ float warp_sum(float v) {
#pragma unroll
  for (int o = 16; o; o >>= 1) v += __shfl_xor_sync(~0u, v, o);
  return v;
}
__device__ __forceinline__ void tma_load_2d(uint32_t dst, const CUtensorMap* map, uint32_t mbar, int c0, int c1) {
  asm volatile("cp.async.bulk.tensor.2d.shared::cluster.global.mbarrier::complete_tx::bytes [%0], [%1, {%3, %4}], [%2];"
               ::"r"(dst), "l"(map), "r"(mbar), "r"(c0), "r"(c1) : "memory");
}
__device__ __forceinline__ void tma_load_2d_mc(uint32_t dst, const CUtensorMap* map, uint32_t mbar, int c0, int c1) {
  asm volatile("cp.async.bulk.tensor.2d.shared::cluster.global.mbarrier::complete_tx::bytes.multicast::cluster [%0], [%1, {%3, %4}], [%2], %5;"
               ::"r"(dst), "l"(map), "r"(mbar), "r"(c0), "r"(c1), "h"((uint16_t)3) : "memory");
}
__device__ __forceinline__ uint64_t pol_first() {
  uint64_t p;
  asm("createpolicy.fractional.L2::evict_first.b64 %0, 1.0;" : "=l"(p));
  return p;
}
__device__ __forceinline__ void tma_load_2d_h(uint32_t dst, const CUtensorMap* map, uint32_t mbar, int c0, int c1, uint64_t pol) {
  asm volatile("cp.async.bulk.tensor.2d.shared::cluster.global.mbarrier::complete_tx::bytes.L2::cache_hint [%0], [%1, {%3, %4}], [%2], %5;"
               ::"r"(dst), "l"(map), "r"(mbar), "r"(c0), "r"(c1), "l"(pol) : "memory");
}
__device__ __forceinline__ void tma_load_2d_mc_h(uint32_t dst, const CUtensorMap* map, uint32_t mbar, int c0, int c1, uint64_t pol) {
  asm volatile("cp.async.bulk.tensor.2d.shared::cluster.global.mbarrier::complete_tx::bytes.multicast::cluster.L2::cache_hint [%0], [%1, {%3, %4}], [%2], %5, %6;"
               ::"r"(dst), "l"(map), "r"(mbar), "r"(c0), "r"(c1), "h"((uint16_t)3), "l"(pol) : "memory");
}
__device__ __forceinline__ void tma_prefetch_2d(const CUtensorMap* map, int c0, int c1) {
  asm volatile("cp.async.bulk.prefetch.tensor.2d.L2.global.tile [%0, {%1, %2}];" ::"l"(map), "r"(c0), "r"(c1) : "memory");
}
__device__ __forceinline__ void bulk_prefetch(const void* p, uint32_t bytes) {
  asm volatile("cp.async.bulk.prefetch.L2.global [%0], %1;" ::"l"(p), "r"(bytes) : "memory");
}
__device__ __forceinline__ void bulk_load(uint32_t dst, const void* src, uint32_t bytes, uint32_t mbar) {
  asm volatile("cp.async.bulk.shared::cluster.global.mbarrier::complete_tx::bytes [%0], [%1], %2, [%3];"
               ::"r"(dst), "l"(src), "r"(bytes), "r"(mbar) : "memory");
}
__device__ __forceinline__ void wgmma_fence() { asm volatile("wgmma.fence.sync.aligned;" ::: "memory"); }
__device__ __forceinline__ void wgmma_commit() { asm volatile("wgmma.commit_group.sync.aligned;" ::: "memory"); }
template <int N> __device__ __forceinline__ void wgmma_wait() { asm volatile("wgmma.wait_group.sync.aligned %0;" ::"n"(N) : "memory"); }
__device__ __forceinline__ void fence_async() { asm volatile("fence.proxy.async.shared::cta;" ::: "memory"); }
__device__ __forceinline__ void bar_sync(int id, int n) { asm volatile("bar.sync %0, %1;" ::"r"(id), "r"(n) : "memory"); }
__device__ __forceinline__ void bar_arrive(int id, int n) { asm volatile("bar.arrive %0, %1;" ::"r"(id), "r"(n) : "memory"); }

constexpr uint32_t SM_BASE = 1024;
__host__ __device__ constexpr uint32_t mk_desc(uint32_t addr, uint32_t lbo_bytes) { return ((addr & 0x3FFFF) >> 4) | ((lbo_bytes >> 4) << 16); }

#define R32(d) \
  "+f"(d[0]), "+f"(d[1]), "+f"(d[2]), "+f"(d[3]), "+f"(d[4]), "+f"(d[5]), "+f"(d[6]), "+f"(d[7]), \
  "+f"(d[8]), "+f"(d[9]), "+f"(d[10]), "+f"(d[11]), "+f"(d[12]), "+f"(d[13]), "+f"(d[14]), "+f"(d[15]), \
  "+f"(d[16]), "+f"(d[17]), "+f"(d[18]), "+f"(d[19]), "+f"(d[20]), "+f"(d[21]), "+f"(d[22]), "+f"(d[23]), \
  "+f"(d[24]), "+f"(d[25]), "+f"(d[26]), "+f"(d[27]), "+f"(d[28]), "+f"(d[29]), "+f"(d[30]), "+f"(d[31])
#define R64(d) R32(d), \
  "+f"(d[32]), "+f"(d[33]), "+f"(d[34]), "+f"(d[35]), "+f"(d[36]), "+f"(d[37]), "+f"(d[38]), "+f"(d[39]), \
  "+f"(d[40]), "+f"(d[41]), "+f"(d[42]), "+f"(d[43]), "+f"(d[44]), "+f"(d[45]), "+f"(d[46]), "+f"(d[47]), \
  "+f"(d[48]), "+f"(d[49]), "+f"(d[50]), "+f"(d[51]), "+f"(d[52]), "+f"(d[53]), "+f"(d[54]), "+f"(d[55]), \
  "+f"(d[56]), "+f"(d[57]), "+f"(d[58]), "+f"(d[59]), "+f"(d[60]), "+f"(d[61]), "+f"(d[62]), "+f"(d[63])
#define S32 \
  "{%0,%1,%2,%3,%4,%5,%6,%7,%8,%9,%10,%11,%12,%13,%14,%15,%16,%17,%18,%19,%20,%21,%22,%23,%24,%25,%26,%27,%28,%29,%30,%31}"
#define S64 \
  "{%0,%1,%2,%3,%4,%5,%6,%7,%8,%9,%10,%11,%12,%13,%14,%15,%16,%17,%18,%19,%20,%21,%22,%23,%24,%25,%26,%27,%28,%29,%30,%31," \
  "%32,%33,%34,%35,%36,%37,%38,%39,%40,%41,%42,%43,%44,%45,%46,%47,%48,%49,%50,%51,%52,%53,%54,%55,%56,%57,%58,%59,%60,%61,%62,%63}"

template <int TB>
__device__ __forceinline__ void wgmma128_rs(float (&d)[64], uint32_t a0, uint32_t a1, uint32_t a2, uint32_t a3, uint32_t db, int scale_d) {
  asm volatile("{\n.reg .pred p;\n.reg .b64 q;\nsetp.ne.b32 p, %69, 0;\nmov.b64 q, {%68, 0x40000040};\n"
               "wgmma.mma_async.sync.aligned.m64n128k16.f32.bf16.bf16 " S64 ", {%64,%65,%66,%67}, q, p, 1, 1, %70;\n}\n"
               : R64(d) : "r"(a0), "r"(a1), "r"(a2), "r"(a3), "r"(db), "r"(scale_d), "n"(TB));
}
__device__ __forceinline__ void wgmma64_rs(float (&d)[32], uint32_t a0, uint32_t a1, uint32_t a2, uint32_t a3, uint32_t db, int scale_d) {
  asm volatile("{\n.reg .pred p;\n.reg .b64 q;\nsetp.ne.b32 p, %37, 0;\nmov.b64 q, {%36, 0x40000040};\n"
               "wgmma.mma_async.sync.aligned.m64n64k16.f32.bf16.bf16 " S32 ", {%32,%33,%34,%35}, q, p, 1, 1, 1;\n}\n"
               : R32(d) : "r"(a0), "r"(a1), "r"(a2), "r"(a3), "r"(db), "r"(scale_d));
}
__device__ __forceinline__ uint32_t pack_bf16(float a, float b) {
  uint32_t r;
  asm("cvt.rn.bf16x2.f32 %0, %1, %2;" : "=r"(r) : "f"(b), "f"(a));
  return r;
}
__device__ __forceinline__ float ex2(float x) { float y; asm("ex2.approx.ftz.f32 %0, %1;" : "=f"(y) : "f"(x)); return y; }
__device__ __forceinline__ float bfr(float x) { return __bfloat162float(__float2bfloat16(x)); }
__device__ __forceinline__ float bf_lo(uint32_t u) { return __uint_as_float(u << 16); }
__device__ __forceinline__ float bf_hi(uint32_t u) { return __uint_as_float(u & 0xffff0000u); }
__device__ __forceinline__ uint4 lds128(uint32_t a) {
  uint4 v;
  asm volatile("ld.shared.v4.b32 {%0,%1,%2,%3}, [%4];" : "=r"(v.x), "=r"(v.y), "=r"(v.z), "=r"(v.w) : "r"(a) : "memory");
  return v;
}
__device__ __forceinline__ void sts128(uint32_t a, uint4 v) {
  asm volatile("st.shared.v4.b32 [%0], {%1,%2,%3,%4};" ::"r"(a), "r"(v.x), "r"(v.y), "r"(v.z), "r"(v.w) : "memory");
}
__device__ __forceinline__ void red_add_v4(float4* p, float a, float b, float c, float d) {
  asm volatile("red.global.add.v4.f32 [%0], {%1,%2,%3,%4};" ::"l"(p), "f"(a), "f"(b), "f"(c), "f"(d) : "memory");
}
__device__ __forceinline__ float rcp(float x) { float y; asm("rcp.approx.ftz.f32 %0, %1;" : "=f"(y) : "f"(x)); return y; }
__device__ __forceinline__ float sqrt_a(float x) { float y; asm("sqrt.approx.ftz.f32 %0, %1;" : "=f"(y) : "f"(x)); return y; }
__device__ __forceinline__ float silu_bf(float v) { return bfr(v * rcp(1.f + __expf(-v))); }

constexpr int SM_STASH = 131072;
constexpr int QG = 73728;
constexpr int SM_STG = 210944;
constexpr int SM_XCH = 196608;
constexpr int SM_PB = 65536;
constexpr int SM_MISC = 229376;
constexpr int SM_TOTAL = 232448;
constexpr int B_FULLQ = 0, B_G1 = 24, B_G2 = 32, B_G3 = 40, B_FULLA = 64, B_XR = 96, B_FULLO = 184, B_FFN = 160, B_RD = 168, B_MD = 176, B_X = 272,
              B_EMPTYQ = 280, B_EMPTYO = 328, B_ST = 392,
              B_EMPTYA = 400, B_M = 432, B_XF = 144;
constexpr int SM_MOD = SM_MISC + 448;
constexpr int SM_FILL = SM_MISC + 512;
constexpr int SM_M2 = SM_MISC + 2560;
constexpr int SM_RED = SM_MISC + 2752;
constexpr int SM_ZERO = SM_MISC + 3040;
constexpr int SM_WG = 137216, SM_WU = 183296;
constexpr int SM_X2 = 0;
constexpr int SM_WD = 19456;
constexpr int SM_T = 122880;
constexpr int SM_OUT = SM_MISC - 16384;
constexpr int SM_MD = SM_STASH;

struct Params {
  const bf16 *x, *k, *c, *w_mod, *w_r, *wo, *v, *wq, *wg, *wu, *wd;
  bf16* out;
};

__global__ void __launch_bounds__(384, 1)
k_mega(const __grid_constant__ CUtensorMap mX, const __grid_constant__ CUtensorMap mWq,
       const __grid_constant__ CUtensorMap mK, const __grid_constant__ CUtensorMap mV,
       const __grid_constant__ CUtensorMap mWo, const __grid_constant__ CUtensorMap mWg,
       const __grid_constant__ CUtensorMap mWu, const __grid_constant__ CUtensorMap mWd, const Params prm) {
  extern __shared__ __align__(1024) uint8_t smem_raw[];
  const uint32_t sb = smem_u32(smem_raw);
  if ((sb & 0x3FFFF) != SM_BASE) __trap();
  const uint32_t sBar = sb + SM_MISC;
  const int tid = threadIdx.x;
  const int lane = get_lane();
  PSTAMP(0, 84);
  const int warp = __shfl_sync(~0u, tid >> 5, 0);
  const int b = blockIdx.x, rank = b & 1, qt = (b >> 1) & 15, kg = b >> 5, hg = kg * 2 + rank;
  const int hcol = (kg * 8 + rank) * DH;
  auto wq_prefetch = [&](int mask) {
    const bf16* wp = prm.wq + (size_t)(qt * 36 + ((tid - 128) >> 3)) * (HQ * DH) + hcol + ((tid & 6) * 2 + (tid & 1)) * 64;
    if ((mask >> (tid & 7)) & 1) {
      asm volatile("prefetch.global.L2 [%0];" ::"l"(wp));
      if (warp == 4) asm volatile("prefetch.global.L2 [%0];" ::"l"(wp + 32 * (HQ * DH)));
    }
  };
  if (warp >= 4) wq_prefetch(WQPF0);
  if (lane == 0 && warp >= 4) {
    if (MPF && warp < 10 && b < 96) bulk_prefetch(prm.w_mod + (size_t)(b * 6 + warp - 4) * (6 * DM), 2 * DM * 2);
    const int c0 = warp < 9 ? 1 : 8, c1 = warp < 11 ? c0 : 16, c2 = warp < 11 ? c0 : 3;
#pragma unroll
    for (int j = 0; j < 7; j++) mbar_init(sBar + (warp - 4) * 56 + j * 8, (warp == 6 && (j & 6) == 4) ? 2 : j == 0 ? c0 : j < 5 ? c1 : c2);
    *reinterpret_cast<uint32_t*>(smem_raw + SM_ZERO) = 0;
    asm volatile("fence.mbarrier_init.release.cluster;" ::: "memory");
  }
  __syncwarp();
  asm volatile("barrier.cluster.arrive.relaxed.aligned;" ::: "memory");
#define CL_WAIT() asm volatile("barrier.cluster.wait.acquire.aligned;" ::: "memory")
  const bool do_mod1 = warp >= 1 && warp < 4 && b < 72;
  if (warp < 4) {
    asm volatile("setmaxnreg.dec.sync.aligned.u32 40;");
    if (warp == 0) {
      PSTAMP(0, 85);
      CL_WAIT();
      PSTAMP(0, 86);
      if (lane == 0) {
        mbar_expect_tx(sBar + B_X, 9 * 16384);
#pragma unroll
        for (int i = 0; i < 5; i++)
          if (i < 4 || rank == 0) tma_load_2d_mc(sb + (2 * i + rank) * 16384, &mX, sBar + B_X, (2 * i + rank) * 64, qt * 128);
      }
    }
    PSTAMP(0, 87);
    if (do_mod1) {
      const int st = tid - 32;
      const uint32_t stg = sb + SM_STG + st * 16;
      {
        const bf16* wp = prm.w_mod + (size_t)(st >> 1) * (6 * DM) + b * 16 + (st & 1) * 8;
#pragma unroll
        for (int i = 0; i < 12; i++)
          asm volatile("cp.async.cg.shared.global [%0], [%1], 16;" ::"r"(stg + i * 1536), "l"(wp + (size_t)i * 48 * (6 * DM)) : "memory");
      }
      float* const sc = reinterpret_cast<float*>(smem_raw + SM_MOD);
#pragma unroll
      for (int i = 0; i < 3; i++) {
        const uint32_t v = __ldg(reinterpret_cast<const uint32_t*>(prm.c) + st + i * 96);
        *reinterpret_cast<float2*>(sc + (st + i * 96) * 2) = make_float2(silu_bf(bf_lo(v)), silu_bf(bf_hi(v)));
      }
      bar_sync(6, 96);
      PSTAMP(32, 88);
      asm volatile("cp.async.wait_all;" ::: "memory");
      PSTAMP(32, 93);
      float a[8];
#pragma unroll
      for (int i = 0; i < 8; i++) a[i] = 0.f;
#pragma unroll 3
      for (int i = 0; i < 12; i++) {
        const float sv = sc[(st >> 1) + 48 * i];
        const uint4 v = lds128(stg + i * 1536);
        a[0] += sv * bf_lo(v.x); a[1] += sv * bf_hi(v.x); a[2] += sv * bf_lo(v.y); a[3] += sv * bf_hi(v.y);
        a[4] += sv * bf_lo(v.z); a[5] += sv * bf_hi(v.z); a[6] += sv * bf_lo(v.w); a[7] += sv * bf_hi(v.w);
      }
      const bool u2 = lane & 2, u4 = lane & 4, u8 = lane & 8;
#pragma unroll
      for (int i = 0; i < 4; i++) { float snd = u2 ? a[i] : a[i + 4]; float kp = u2 ? a[i + 4] : a[i]; a[i] = kp + __shfl_xor_sync(~0u, snd, 2); }
#pragma unroll
      for (int i = 0; i < 2; i++) { float snd = u4 ? a[i] : a[i + 2]; float kp = u4 ? a[i + 2] : a[i]; a[i] = kp + __shfl_xor_sync(~0u, snd, 4); }
      { float snd = u8 ? a[0] : a[1]; float kp = u8 ? a[1] : a[0]; a[0] = kp + __shfl_xor_sync(~0u, snd, 8); }
      a[0] += __shfl_xor_sync(~0u, a[0], 16);
      float* const red = reinterpret_cast<float*>(smem_raw + SM_RED);
      if (lane < 16) red[(warp - 1) * 16 + (lane & 1) * 8 + (u2 ? 4 : 0) + (u4 ? 2 : 0) + (u8 ? 1 : 0)] = a[0];
      PSTAMP(32, 94);
      bar_sync(6, 96);
      PSTAMP(32, 95);
      if (st < 64) {
        const float* rp = red + (lane & 7) * 2;
        const float2 x = *reinterpret_cast<const float2*>(rp), y = *reinterpret_cast<const float2*>(rp + 16), z = *reinterpret_cast<const float2*>(rp + 32);
        uint32_t w = pack_bf16(x.x + y.x + z.x, x.y + y.y + z.y);
        if (b >= 36) w = hadd2(w, 0x3f803f80u);
        asm volatile("st.relaxed.gpu.global.u32 [%0], %1;" ::"l"(reinterpret_cast<uint32_t*>(g_mod1) + (st >> 3) * 576 + b * 8 + (lane & 7)), "r"(~w) : "memory");
      }
    }
    __syncwarp();
    PSTAMP(32, 89);
    if (warp > 0) {
      CL_WAIT();
      fence_async();
      if (tid < 104) {
        uint4 v, w;
        mbar_wait(sBar + B_X, 0);
        poll8(g_mod1 + (b & 7) * 144 + tid - 32, g_mod1 + (b & 7) * 144 + tid + 40, v, w);
        sts128(sb + SM_MOD + (tid - 32) * 32, make_uint4(~v.x, ~w.x, ~v.y, ~w.y));
        sts128(sb + SM_MOD + (tid - 32) * 32 + 16, make_uint4(~v.z, ~w.z, ~v.w, ~w.w));
      }
      __syncwarp();
      PSTAMP(32, 92);
      bar_arrive(3, 224);
      bar_arrive(4, 224);
      if (lane == 0) asm volatile("mbarrier.arrive.shared::cta.b64 _, [%0];" ::"r"(sBar + B_M) : "memory");
    }
    auto ffn_box = [&](int fb) {
      const int m = fb >= 12;
      tma_load_2d(sb + SM_WG + fb * 3840, m ? &mWu : &mWg, sBar + B_FFN, (b * 36) & ~7, (fb - m * 12) * 48);
    };
    if (tid == 0) {
      const uint64_t pol = pol_first();
      auto kv_load = [&](int t) {
        const int s = t & 3;
        mbar_wait(sBar + B_EMPTYA + s * 8, (t >> 2) & 1);
        mbar_expect_tx(sBar + B_FULLA + s * 8, 32768);
        if (EF & 1) tma_load_2d_mc_h(sb + s * 32768 + rank * 16384, (t & 1) ? &mV : &mK, sBar + B_FULLA + s * 8, rank * 64, kg * 4 * SK + (t >> 1) * 128, pol);
        else tma_load_2d_mc(sb + s * 32768 + rank * 16384, (t & 1) ? &mV : &mK, sBar + B_FULLA + s * 8, rank * 64, kg * 4 * SK + (t >> 1) * 128);
      };
#pragma unroll 1
      for (int i = 0, g = 1; i < 32; i++) {
        const int hh = (i >> 2) + 2;
        if (i == QTH) mbar_wait(sBar + B_M, 0);
        if (!(i & 3)) {
          mbar_wait(sBar + B_EMPTYQ + g * 8, i >= 12 && i < 24);
          mbar_expect_tx(sBar + B_FULLQ + g * 8, QG);
        }
        if (EF & 2) tma_load_2d_h(sb + g * QG + (i & 3) * 18432, &mWq, sBar + B_FULLQ + g * 8, hcol + (hh & 6) * 128 + (hh & 1) * 64, (i & 3) * 144, pol);
        else tma_load_2d(sb + g * QG + (i & 3) * 18432, &mWq, sBar + B_FULLQ + g * 8, hcol + (hh & 6) * 128 + (hh & 1) * 64, (i & 3) * 144);
        if ((i & 3) == 3 && ++g == 3) g = 0;
      }
#pragma unroll 1
      for (int u = 0; u < 128; u++) kv_load(u < 5 || u == 127 ? u : (u & 1) ? u + 1 : u - 1);
      mbar_wait(sBar + B_X, 1);
      {
        int ch = kg * 2, g = 0, par = 1, fb = 0;
        mbar_expect_tx(sBar + B_FFN, 9 * 5120 + 2 * DM * 80);
#pragma unroll 1
        for (int i = 0; i < 36; i++) {
          if (i < 8) mbar_wait(sBar + B_EMPTYA + (g >> 1) * 8, 0);
          else mbar_wait(sBar + B_EMPTYO + g * 8, par);
          mbar_expect_tx(sBar + B_FULLO + g * 8, 16384);
          if (EF & 8) tma_load_2d_h(sb + g * 16384, &mWo, sBar + B_FULLO + g * 8, ch * 64, hcol + (i & 3) * 256, pol);
          else tma_load_2d(sb + g * 16384, &mWo, sBar + B_FULLO + g * 8, ch * 64, hcol + (i & 3) * 256);
          if ((i & 3) == 3 && ++ch == 9) ch = 0;
          if (i == 7) mbar_wait(sBar + B_ST, 0);
          if (i >= FFN0) {
#pragma unroll 1
            for (const int fe = i == 35 ? FFNE : min(FFNE, (i - FFN0 + 1) * FFNR / FFND); fb < fe; fb++) ffn_box(fb);
          }
          if (++g == 8) { g = 0; par ^= 1; }
        }
        mbar_wait(sBar + B_EMPTYO + 8, 0);
        mbar_expect_tx(sBar + B_XR, 16 * 1152);
#pragma unroll 1
        for (int r = 0; r < 16; r++) bulk_load(sb + SM_X2 + r * 1168, prm.x + (size_t)(qt * 128 + hg * 16 + r) * DM, 1152, sBar + B_XR);
        mbar_wait(sBar + B_RD, 0);
        if (LATEG & 1) mbar_wait(sBar + B_G1, 0);
#pragma unroll 1
        for (; fb < 24; fb++) ffn_box(fb);
        mbar_wait(sBar + B_EMPTYO + 24, 0);
        if (LATEG & 2) mbar_wait(sBar + B_G1, 0);
#pragma unroll 1
        for (int f = 0; f < 9; f++) tma_load_2d(sb + SM_WD + f * 5120, &mWd, sBar + B_FFN, f * 64, b * 36);
      }
    } else if (warp == 3) {
#pragma unroll 1
      for (int i = 0, g = 1; i < 8; i++) {
        mbar_wait(sBar + B_FULLQ + g * 8, i >= 3 && i < 6);
        if (++g == 3) g = 0;
        KSTAMP(170 + i * 2); bar_sync(1, 288); KSTAMP(171 + i * 2);
      }
      long long nxt = 0;
#pragma unroll 1
      for (int u = 0; u < 128; u++) {
        const int t = (u == 0 || u == 127) ? u : (u & 1) ? u + 1 : u - 1;
        mbar_wait(sBar + B_FULLA + (t & 3) * 8, (t >> 2) & 1);
        if (!(t & 1) || t == 127) { KSTAMP((t + 1) & ~1);
          bar_sync(1, 288); KSTAMP(((t + 1) & ~1) + 1); }
        else { KSTAMP(190 + (t >> 1)); bar_sync(10, 160); }
      }
      int g = 0, par = 0;
      if (lane < 2) mbar_expect_tx(sBar + B_XF + lane * 8, 8192);
#pragma unroll 1
      for (int i = 0; i < 36; i++) {
        mbar_wait(sBar + B_FULLO + g * 8, par);
        if (++g == 8) { g = 0; par ^= 1; }
        if ((i & 3) == 3 && i > 3 && i < 35) {
          const uint32_t xf = sBar + B_XF + ((i - 4) & 4) * 2;
          KSTAMP(260 + (i >> 2));
          mbar_wait(xf, ((i - 4) >> 3) & 1);
          __syncwarp();
          if (lane == 0) mbar_expect_tx(xf, 8192);
        }
        if (i & 1) { KSTAMP(129 + i); bar_sync(1, 288); KSTAMP(130 + i); }
      }
    } else if (warp > 0) {
      const int st = tid - 32;
      mbar_wait(sBar + B_FULLQ + 8, 0);
      mbar_wait(sBar + B_FULLQ + 8, 1);
      const bf16* const kvp = (rank ? prm.v : prm.k) + ((size_t)kg * 4 * SK + qt * 128) * DH;
      if (st == 0) bulk_prefetch(kvp, 32768);
      mbar_wait(sBar + B_FULLA, 0);
      mbar_wait(sBar + B_FULLA, 1);
      if (warp == 1) {
#pragma unroll 1
        for (int grp = b < 72 ? b : 288; grp < 288; grp += 72) {
          float a[8];
#pragma unroll
          for (int i = 0; i < 8; i++) a[i] = 0.f;
#pragma unroll 2
          for (int r = lane; r < DM; r += 32) {
            uint4 v;
            if (EF & 16) asm("ld.global.nc.L2::cache_hint.v4.u32 {%0,%1,%2,%3}, [%4], %5;" : "=r"(v.x), "=r"(v.y), "=r"(v.z), "=r"(v.w) : "l"(prm.w_mod + (size_t)r * (6 * DM) + 2 * DM + grp * 8), "l"(pol_first()));
            else v = __ldg(reinterpret_cast<const uint4*>(prm.w_mod + (size_t)r * (6 * DM) + 2 * DM + grp * 8));
            float s = silu_bf(__bfloat162float(prm.c[r]));
            a[0] += s * bf_lo(v.x); a[1] += s * bf_hi(v.x); a[2] += s * bf_lo(v.y); a[3] += s * bf_hi(v.y);
            a[4] += s * bf_lo(v.z); a[5] += s * bf_hi(v.z); a[6] += s * bf_lo(v.w); a[7] += s * bf_hi(v.w);
          }
#pragma unroll
          for (int i = 0; i < 8; i++) a[i] = warp_sum(a[i]);
          if (lane == 0) {
            const int kind = grp / 72;
#pragma unroll
            for (int i = 0; i < 4; i++) {
              uint32_t w = pack_bf16(a[2 * i], a[2 * i + 1]);
              if (kind == 2) w = hadd2(w, 0x3f803f80u);
              reinterpret_cast<uint32_t*>(smem_raw + SM_M2)[i * 4 + kind] = w;
            }
            if (kind == 3) {
              fence_async();
              asm volatile("cp.async.bulk.global.shared::cta.bulk_group [%0], [%1], 64;" ::"l"(g_mod2 + b * 4), "r"(sb + SM_M2) : "memory");
              asm volatile("cp.async.bulk.commit_group;\ncp.async.bulk.wait_group 0;" ::: "memory");
              if (SIDEF & 1) asm volatile("fence.acq_rel.gpu;" ::: "memory");
              cnt_arrive(C_SIDE);
            }
          }
        }
        __syncwarp();
        {
          if (lane == 0) asm volatile("mbarrier.arrive.shared::cta.b64 _, [%0];" ::"r"(sBar + B_XF) : "memory");
#pragma unroll 1
          for (int k = 0; k < 16; k++) {
            bar_sync(8 + (k & 1), 160);
            if (lane == 0) {
              fence_async();
              const int t = (k >> 1) + (kg & 1) * 2, slot = k >= 14 ? 28 + kg : (kg >> 1) * 14 + (t < 7 ? t : t - 7) * 2 + (kg & 1);
#pragma unroll
              for (int w = 0; w < 4; w++)
                asm volatile("cp.async.bulk.global.shared::cta.bulk_group [%0], [%1], 1024;" ::"l"(g_ones + F_PART + (qt * 8 + (k & 1) * 4 + w) * 5120 + slot * 128 + rank * 64),
                             "r"(sb + SM_OUT + (k & 3) * 4096 + w * 1024) : "memory");
              if (k & 1) {
                asm volatile("cp.async.bulk.commit_group;\ncp.async.bulk.wait_group.read 1;" ::: "memory");
                asm volatile("mbarrier.arrive.shared::cta.b64 _, [%0];" ::"r"(sBar + B_XF + ((k & 2) ? 0 : 8)) : "memory");
              }
            }
            __syncwarp();
            if (k >= HINTA && (k & 1) && lane < 8) asm volatile("red.relaxed.gpu.global.add.u32 [%0], 1;" ::"l"(&g_cnt[(C_Q + qt * 8 + lane) * 32 + (k == 15)]) : "memory");
          }
        }
        PSTAMP(32, 56);
        if (lane == 0) {
          asm volatile("cp.async.bulk.wait_group.read 0;" ::: "memory");
          asm volatile("mbarrier.arrive.shared::cta.b64 _, [%0];" ::"r"(sBar + B_RD) : "memory");
        }
        __syncwarp();
        const int lane = get_lane();
        PSTAMP(32, 57);
        cnt_wait1((C_Q + qt * 8 + hg) * 32 + 1, 8);
        PSTAMP(32, 59);
        if (lane == 0) mbar_arrive(sBar + B_G2);
        uint32_t k1 = ~0u, k2 = ~0u;
        uint4 hv[4];
        uint2 hw = make_uint2(0u, 0u);
        auto h_load = [&]() {
          const int r1 = k1 & (SQ - 1), r2 = k2 & (SQ - 1);
          const int r = lane < 16 ? r1 : r2;
          const int c = ((r >> 5) & 3) * 32 + (r >> 7) * 2 + ((r >> 4) & 1);
          const uint4* p = g_ones + F_HX + (c * 288 + (lane >= 16 && (r1 >> 4) == (r2 >> 4) ? 144 : 0) + (lane & 15));
#pragma unroll
          for (int i = 0; i < 4; i++) hv[i] = ldr4(p + i * 16);
          hw = ldr2(reinterpret_cast<const uint2*>(p + 64) - (lane & 15));
        };
#pragma unroll
        for (int i = 0; i < 4; i++) hv[i] = make_uint4(0u, 0u, 0u, 0u);
        const uint4* kp = g_ones + F_KEY + (b & 31) * 64 + lane * 2;
        auto merge = [](uint32_t& m1, uint32_t& m2, uint32_t n1, uint32_t n2) { m2 = min(max(m1, n1), min(m2, n2)); m1 = min(m1, n1); };
#pragma unroll 1
        for (uint32_t n = 0;; n++) {
          uint4 a, c;
          asm volatile("ld.relaxed.gpu.global.v4.u32 {%0,%1,%2,%3}, [%8];\nld.relaxed.gpu.global.v4.u32 {%4,%5,%6,%7}, [%8+16];"
                       : "=r"(a.x), "=r"(a.y), "=r"(a.z), "=r"(a.w), "=r"(c.x), "=r"(c.y), "=r"(c.z), "=r"(c.w) : "l"(kp) : "memory");
          const bool all = !__any_sync(~0u, unset(a) || unset(c));
          merge(a.x, a.y, a.z, a.w);
          merge(a.x, a.y, c.x, c.y);
          merge(a.x, a.y, c.z, c.w);
          const uint32_t m1 = __reduce_min_sync(~0u, a.x);
          const uint32_t m2 = __reduce_min_sync(~0u, a.x == m1 ? a.y : a.x);
          bool bad = m1 != k1 || m2 != k2 || hw.x == ~0u || hw.y == ~0u;
#pragma unroll
          for (int i = 0; i < 4; i++) bad |= unset(hv[i]);
          bad = __any_sync(~0u, bad);
          if (all && !bad) break;
          if (n > (1u << 15)) { SETERR(4); break; }
          if (bad) { k1 = m1; k2 = m2; h_load(); }
        }
        PSTAMP(32, 60);
        {
          const uint32_t ha = sb + SM_T + 4096 + (lane >> 4) * 1152 + (lane & 15) * 16;
#pragma unroll
          for (int i = 0; i < 4; i++) sts128(ha + i * 256, hv[i]);
          asm volatile("st.shared.v2.b32 [%0], {%1,%2};" ::"r"(ha + 1024 - (lane & 15) * 8), "r"(hw.x), "r"(hw.y) : "memory");
        }
        if (lane == 0) asm volatile("st.shared.v2.b32 [%0], {%1,%2};" ::"r"(sb + SM_T + 128), "r"(~k1), "r"(~k2) : "memory");
        __syncwarp();
        if (lane == 0) mbar_arrive(sBar + B_G3);
        PSTAMP(32, 61);
      } else {
#pragma unroll
        for (int i = 0; i < 4; i++) sts128(sb + SM_FILL + i * 512 + lane * 16, make_uint4(~0u, ~0u, ~0u, ~0u));
        fence_async();
        __syncwarp();
#pragma unroll 1
        for (int p = 2; p < FILLP; p++) {
          mbar_wait(sBar + B_FULLA, p & 1);
          if (lane == 0) {
            if ((p & 7) == 3 && p < 24) bulk_prefetch(kvp + (size_t)((p >> 3) + 1) * SK * DH, 32768);
            if ((p & 7) == QPF && p < 24) bulk_prefetch(g_q + ((size_t)b * 4 + (p >> 3) + 1) * 2048, 32768);
            if (p == FILLP - 1) bulk_prefetch(prm.x + (size_t)(qt * 128 + hg * 16) * DM, 16 * DM * 2);
            if (p == WOP) bulk_prefetch(prm.wo + ((size_t)kg * 1024 + (b & 31) * 32) * DM, 32 * DM * 2);
            if (p >= PF0 && p < PF0 + 9) {
              const int i = p - PF0, m = i / 3;
              bulk_prefetch((m == 0 ? prm.wg : m == 1 ? prm.wu : prm.wd) + (size_t)(b * 3 + i - m * 3) * (DM * 12), DM * 24);
            }
          }
          __syncwarp();
          if (p >= FILL0 && lane < FILLN) {
            const int i = (p - FILL0) * FILLN + lane;
            if (i < FILLMAX) {
              uint4* const fp = g_ones + (i < 5 ? b * 640 : F_PART - 640 + b * 5120) + i * 128;
              if (EF & 32) asm volatile("cp.async.bulk.global.shared::cta.bulk_group.L2::cache_hint [%0], [%1], 2048, %2;" ::"l"(fp), "r"(sb + SM_FILL), "l"(pol_first()) : "memory");
              else asm volatile("cp.async.bulk.global.shared::cta.bulk_group [%0], [%1], 2048;" ::"l"(fp), "r"(sb + SM_FILL) : "memory");
            }
          }
        }
        asm volatile("cp.async.bulk.commit_group;\ncp.async.bulk.wait_group 0;" ::: "memory");
        if (SIDEF & 2) asm volatile("fence.acq_rel.gpu;" ::: "memory");
        __syncwarp();
        PSTAMP(64, 51);
        if (lane == 0) {
          cnt_arrive(C_SIDE);
          PSTAMP(64, 52);
          cnt_wait(C_SIDE, 128 + 72);
          PSTAMP(64, 53);
          asm volatile("mbarrier.arrive.shared::cta.b64 _, [%0];" ::"r"(sBar + B_X) : "memory");
        }
        __syncwarp();
        if (lane == 0) {
          asm volatile("prefetch.tensormap [%0];\nprefetch.tensormap [%1];\nprefetch.tensormap [%2];\nprefetch.tensormap [%3];" ::"l"(&mWo), "l"(&mWg), "l"(&mWu), "l"(&mWd) : "memory");
          mbar_wait(sBar + B_ST, 0);
          mbar_expect_tx(sBar + B_MD, 5760);
          bulk_load(sb + SM_MD, g_mod2, 4608, sBar + B_MD);
          bulk_load(sb + SM_MD + 4608, prm.w_r, 1152, sBar + B_MD);
        }
        __syncwarp();
        {
          mbar_wait(sBar + B_MD, 0);
          float sA = 0.f, sB = 0.f;
#pragma unroll 1
          for (int i = lane; i < 288; i += 32) {
            const uint4 m = lds128(sb + SM_MD + i * 16);
            const uint32_t w = *reinterpret_cast<const uint32_t*>(smem_raw + SM_MD + 4608 + i * 4);
            const float a0 = bf_lo(m.z) * bf_lo(w), a1 = bf_hi(m.z) * bf_hi(w);
            const uint32_t hi = pack_bf16(a0, a1);
            *reinterpret_cast<uint2*>(smem_raw + SM_MOD + i * 8) = make_uint2(pack_bf16(a0 - bf_lo(hi), a1 - bf_hi(hi)), hi);
            sA += a0 + a1;
            sB = fmaf(bf_lo(m.y), bf_lo(w), fmaf(bf_hi(m.y), bf_hi(w), sB));
          }
          sA = warp_sum(sA); sB = warp_sum(sB);
          *reinterpret_cast<float2*>(smem_raw + SM_ZERO + 16) = make_float2(sA, sB);
          __syncwarp();
        }
        if (lane == 0) {
#pragma unroll 1
          for (int r = 0; r < 4; r++) mbar_wait(sBar + B_EMPTYO + 40, r & 1);
          cnt_wait1((C_Q + qt * 8 + hg) * 32, 8);
          PSTAMP(64, 55);
          const uint4* const pp = g_ones + F_PART + (qt * 8 + hg) * 5120;
          mbar_expect_tx(sBar + B_G1, 28 * 2048);
          bulk_load(sb + SM_PB, pp, 32768, sBar + B_G1);
          mbar_wait(sBar + B_EMPTYO + 56, 1);
          bulk_load(sb + SM_PB + 32768, pp + 2048, 24576, sBar + B_G1);
        }
        __syncwarp();
        const uint32_t* const tsu = reinterpret_cast<const uint32_t*>(smem_raw + SM_T);
        const int row = qt * 128 + hg * 16 + lane;
        auto out_row = [&]() {
          asm volatile("cp.async.bulk.global.shared::cta.bulk_group [%0], [%1], 1152;" ::"l"(prm.out + (size_t)row * DM), "r"(sb + SM_X2 + lane * 1168) : "memory");
        };
        bar_sync(11, 288);
        fence_async();
        const bool top = (*(volatile const uint32_t*)(tsu + 34) >> lane) & 1;
        if (lane < 16 && !top) out_row();
        mbar_wait(sBar + B_G3, 0);
        if (top && row != (int)(~*(volatile const uint32_t*)(tsu + 32) & (SQ - 1)) && row != (int)(~*(volatile const uint32_t*)(tsu + 33) & (SQ - 1))) out_row();
        asm volatile("cp.async.bulk.commit_group;\ncp.async.bulk.wait_group.read 0;" ::: "memory");
      }
    }
  } else {
    const int cw = (warp >> 2) - 1;
    const int w8 = warp - 4;
    const int ct = tid - 128;
    const int lane = get_lane(), g = lane >> 2, t4 = lane & 3;
    uint32_t relBar;
    asm volatile("mapa.shared::cluster.u32 %0, %1, %2;" : "=r"(relBar) : "r"(sBar), "r"(rank ^ (lane & 1)));
    auto release = [&](int off) {
      if (lane < 2) mbar_arrive_cl(relBar + off);
    };
    auto release1 = [&](int off) {
      if (lane == 0) mbar_arrive_cl(relBar + off);
    };
    auto turn_begin = [&]() {
      asm volatile("{\n.reg .pred p;\nsetp.eq.b32 p, %0, 0;\n@p bar.sync 1, 288;\n@!p bar.sync 2, 256;\n}\n" ::"r"(cw) : "memory");
      wgmma_fence();
    };
    auto turn_end = [&]() { asm volatile("{\n.reg .pred p;\nsetp.eq.b32 p, %0, 0;\n@p bar.arrive 2, 256;\n@!p bar.arrive 1, 288;\n}\n" ::"r"(cw) : "memory"); };
    STAMP(0); GSTAMP(90);
    CL_WAIT();
    asm volatile("setmaxnreg.inc.sync.aligned.u32 232;");
    float S[64], O[64];
    uint32_t P[32], Qf[32];
    constexpr uint32_t dB_k = mk_desc(SM_BASE, 16);
    constexpr uint32_t dB_n16 = mk_desc(SM_BASE, 16384);
    uint4* const qpark = g_q + (size_t)b * (4 * 8 * 256) + ct;
    {
      uint32_t A[144];
      const uint32_t la = sb + (w8 * 16 + ((lane & 15) ^ (rank * 8))) * 128 + (((lane >> 4) ^ (lane & 7)) << 4);
      mbar_wait(sBar + B_X, 0);
      wq_prefetch(WQPF1);
      STAMP(1);
#pragma unroll
      for (int k = 0; k < 36; k++) {
        uint32_t a[4];
        ldsm4(a, (la ^ ((k & 3) << 5)) + (k >> 2) * 16384);
        A[k * 4] = a[0]; A[k * 4 + 1] = a[1]; A[k * 4 + 2] = a[2]; A[k * 4 + 3] = a[3];
      }
      const uint32_t one = 0x3f803f80u;
      float c[4][4];
#pragma unroll
      for (int i = 0; i < 16; i++) c[i >> 2][i & 3] = 0.f;
#pragma unroll
      for (int k = 0; k < 36; k++) mma16816(c[k & 3], A[k * 4], A[k * 4 + 1], A[k * 4 + 2], A[k * 4 + 3], one, one);
      if (lane < 3) mbar_arrive_cl(sBar + B_EMPTYQ + lane * 8);
      const float mA = ((c[0][0] + c[1][0]) + (c[2][0] + c[3][0])) * (1.f / DM), mB = ((c[0][2] + c[1][2]) + (c[2][2] + c[3][2])) * (1.f / DM);
      if (cw == 1) bar_sync(7, 256);
      uint32_t zero;
      asm volatile("ld.shared.b32 %0, [%1];" : "=r"(zero) : "r"(sb + SM_ZERO) : "memory");
      const uint32_t nA = pack_bf16(-mA, -mA) | zero, nB = pack_bf16(-mB, -mB) | zero;
      const float eA = mA + bf_lo(nA), eB = mB + bf_lo(nB);
#pragma unroll
      for (int i = 0; i < 16; i++) c[i >> 2][i & 3] = 0.f;
#pragma unroll
      for (int k = 0; k < 36; k++) {
        A[k * 4] = hadd2(A[k * 4], nA); A[k * 4 + 1] = hadd2(A[k * 4 + 1], nB); A[k * 4 + 2] = hadd2(A[k * 4 + 2], nA); A[k * 4 + 3] = hadd2(A[k * 4 + 3], nB);
        mma16816(c[k & 3], hmul2(A[k * 4], A[k * 4]), hmul2(A[k * 4 + 1], A[k * 4 + 1]), hmul2(A[k * 4 + 2], A[k * 4 + 2]), hmul2(A[k * 4 + 3], A[k * 4 + 3]), one, one);
      }
      const float vA = (c[0][0] + c[1][0]) + (c[2][0] + c[3][0]), vB = (c[0][2] + c[1][2]) + (c[2][2] + c[3][2]);
      const float rA = rsqrtf(fmaxf(vA * (1.f / DM) - eA * eA, 0.f) + 1e-5f), rB = rsqrtf(fmaxf(vB * (1.f / DM) - eB * eB, 0.f) + 1e-5f);
      const uint32_t hA = pack_bf16(rA, rA), hB = pack_bf16(rB, rB);
      const uint32_t lA = pack_bf16(rA - bf_lo(hA), rA - bf_lo(hA)), lB = pack_bf16(rB - bf_lo(hB), rB - bf_lo(hB));
      const uint32_t oA = pack_bf16(-eA * rA, -eA * rA), oB = pack_bf16(-eB * rB, -eB * rB);
#pragma unroll
      for (int i = 0; i < 144; i++) A[i] = hfma2(A[i], (i & 1) ? hB : hA, hfma2(A[i], (i & 1) ? lB : lA, (i & 1) ? oB : oA));
      asm volatile("st.shared.b32 [%0], %1;" ::"r"(sb + SM_ZERO + 4), "r"(A[143] ^ A[100]) : "memory");
      if (cw == 0) bar_arrive(7, 256);
      STAMP(2);
      bar_sync(3 + cw, 224);
      wq_prefetch(WQPF2);
      STAMP(3);
#pragma unroll
      for (int k = 0; k < 72; k++) {
        const uint2 m = *reinterpret_cast<const uint2*>(smem_raw + SM_MOD + (k * 4 + t4) * 8);
        A[k * 2] = hfma2(A[k * 2], m.y, m.x); A[k * 2 + 1] = hfma2(A[k * 2 + 1], m.y, m.x);
      }
      STAMP(4); GSTAMP(64);
      float qa[32];
      if (cw == 0) bar_arrive(1, 288);
#pragma unroll 1
      for (int hh = 2, gr = 1;; hh++) {
#pragma unroll
        for (int p = 0; p < 4; p++) {
          if (p == 0) turn_begin();
          const uint32_t db = dB_k + gr * (QG >> 4) + p * 1152;
#pragma unroll
          for (int kk = 0; kk < 9; kk++)
            wgmma64_rs(qa, A[p * 36 + kk * 4], A[p * 36 + kk * 4 + 1], A[p * 36 + kk * 4 + 2], A[p * 36 + kk * 4 + 3], db + kk * 128, (p | kk) != 0);
        }
        wgmma_commit();
        turn_end();
        wgmma_wait<0>();
        if (hh < 7) release1(B_EMPTYQ + gr * 8);
        else if (hh < 9) { release(B_EMPTYA + gr * 16); release(B_EMPTYA + gr * 16 + 8); }
        if (++gr == 3) gr = 0;
#pragma unroll
        for (int j = 0; j < 4; j++)
          qpark[((hh & 7) * 4 + j) * 256] = make_uint4(pack_bf16(qa[8 * j], qa[8 * j + 1]), pack_bf16(qa[8 * j + 2], qa[8 * j + 3]),
                                                       pack_bf16(qa[8 * j + 4], qa[8 * j + 5]), pack_bf16(qa[8 * j + 6], qa[8 * j + 7]));
        if (hh == 9) break;
      }
#pragma unroll
      for (int j = 0; j < 4; j++) {
        const uint4 v = __ldcg(qpark + j * 256);
        Qf[4 * j] = v.x; Qf[4 * j + 1] = v.y; Qf[4 * j + 2] = v.z; Qf[4 * j + 3] = v.w;
      }
#pragma unroll
      for (int j = 0; j < 16; j++) Qf[16 + j] = pack_bf16(qa[2 * j], qa[2 * j + 1]);
    }
    STAMP(5); GSTAMP(65);
    const float sc = 0.08838834764831845f * 1.4426950408889634f;
    float mb0 = 0.f, mb1 = 0.f, l0 = 0.f, l1 = 0.f;
    float i0 = 0.f, i1 = 0.f;
    auto o_scale = [&]() {
      float a0 = l0, a1 = l1;
      a0 += __shfl_xor_sync(~0u, a0, 1); a0 += __shfl_xor_sync(~0u, a0, 2);
      a1 += __shfl_xor_sync(~0u, a1, 1); a1 += __shfl_xor_sync(~0u, a1, 2);
      i0 = rcp(a0); i1 = rcp(a1);
    };
    auto o_frag = [&](int i) {
      return make_uint4(pack_bf16(O[i * 8] * i0, O[i * 8 + 1] * i0), pack_bf16(O[i * 8 + 2] * i1, O[i * 8 + 3] * i1),
                        pack_bf16(O[i * 8 + 4] * i0, O[i * 8 + 5] * i0), pack_bf16(O[i * 8 + 6] * i1, O[i * 8 + 7] * i1));
    };
    auto row_max = [&](float& x0, float& x1) {
      float y0 = fmaxf(S[0], S[1]), y1 = fmaxf(S[2], S[3]), z0 = fmaxf(S[4], S[5]), z1 = fmaxf(S[6], S[7]);
#pragma unroll
      for (int j = 2; j < 16; j += 2) {
        y0 = fmaxf(y0, fmaxf(S[j * 4], S[j * 4 + 1])); y1 = fmaxf(y1, fmaxf(S[j * 4 + 2], S[j * 4 + 3]));
        z0 = fmaxf(z0, fmaxf(S[j * 4 + 4], S[j * 4 + 5])); z1 = fmaxf(z1, fmaxf(S[j * 4 + 6], S[j * 4 + 7]));
      }
      x0 = fmaxf(y0, z0); x1 = fmaxf(y1, z1);
      x0 = fmaxf(x0, __shfl_xor_sync(~0u, x0, 1)); x1 = fmaxf(x1, __shfl_xor_sync(~0u, x1, 1));
      x0 = fmaxf(x0, __shfl_xor_sync(~0u, x0, 2)); x1 = fmaxf(x1, __shfl_xor_sync(~0u, x1, 2));
    };
    float s0, s1;
    auto exps = [&](int j0, int j1) {
#pragma unroll
      for (int j = j0; j < j1; j++) {
        S[j * 4] = ex2(fmaf(S[j * 4], sc, -mb0)); S[j * 4 + 1] = ex2(fmaf(S[j * 4 + 1], sc, -mb0));
        S[j * 4 + 2] = ex2(fmaf(S[j * 4 + 2], sc, -mb1)); S[j * 4 + 3] = ex2(fmaf(S[j * 4 + 3], sc, -mb1));
        s0 += S[j * 4] + S[j * 4 + 1]; s1 += S[j * 4 + 2] + S[j * 4 + 3];
      }
    };
    auto cvtP = [&]() {
#pragma unroll
      for (int i = 0; i < 32; i++) P[i] = pack_bf16(S[2 * i], S[2 * i + 1]);
    };
    auto issue_qk = [&](uint32_t db) {
#pragma unroll
      for (int kk = 0; kk < 8; kk++)
        wgmma128_rs<0>(S, Qf[kk * 4], Qf[kk * 4 + 1], Qf[kk * 4 + 2], Qf[kk * 4 + 3], db + (kk >> 2) * 1024 + (kk & 3) * 2, kk != 0);
    };
    auto issue_pv = [&](uint32_t db, int first) {
#pragma unroll
      for (int kk = 0; kk < 8; kk++) {
        if (kk == TE_POS) turn_end();
        wgmma128_rs<1>(O, P[kk * 4], P[kk * 4 + 1], P[kk * 4 + 2], P[kk * 4 + 3], db + kk * 128, kk ? 1 : !first);
      }
      wgmma_commit();
      if (TE_POS == 8) turn_end();
    };
    auto sched_fence = [&]() {
      asm volatile("st.shared.v2.f32 [%0], {%1,%2};" ::"r"(sb + SM_RED), "f"(s0), "f"(s1) : "memory");
    };
    {
      STAMP(6);
      turn_begin();
      issue_qk(dB_k);
      wgmma_commit();
      turn_end();
      wgmma_wait<0>();
      release(B_EMPTYA);
      s0 = 0.f; s1 = 0.f;
      float x0, x1;
      row_max(x0, x1);
      mb0 = x0 * sc; mb1 = x1 * sc;
      exps(0, 16);
      cvtP();
      l0 = s0; l1 = s1;
    }
    const uint4* qn = qpark + 8 * 256;
    asm volatile("" : "+l"(qn));
    uint32_t kd = dB_k + 4096;
#pragma unroll 1
    for (int t = 1; t < 64; t++, kd ^= 4096) {
      const int j = t & 15, h = t >> 4;
      const int ks = (t & 1) * 2, vs = 3 - ks;
      turn_begin();
      issue_qk(kd);
      wgmma_commit();
      if (__builtin_expect(j == 1 && h, 0)) {
#pragma unroll
        for (int i = 0; i < 8; i++) sts128(sb + SM_STASH + (h - 1) * 32768 + i * 4096 + ct * 16, o_frag(i));
        wgmma_fence();
      }
      if (cw == 0) bar_sync(10, 160);
      issue_pv(kd ^ (dB_k ^ (dB_n16 + 6144)), j == 1);
      wgmma_wait<1>();
      release(B_EMPTYA + ks * 8);
      if (j == 15 && h < 3) {
#pragma unroll
        for (int i = 0; i < 8; i++) {
          uint4 v;
          if (EF & 4) asm volatile("ld.global.cg.L2::cache_hint.v4.u32 {%0,%1,%2,%3}, [%4], %5;" : "=r"(v.x), "=r"(v.y), "=r"(v.z), "=r"(v.w) : "l"(qn + i * 256), "l"(pol_first()));
          else v = __ldcg(qn + i * 256);
          Qf[4 * i] = v.x; Qf[4 * i + 1] = v.y; Qf[4 * i + 2] = v.z; Qf[4 * i + 3] = v.w;
        }
        qn += 8 * 256;
      }
      s0 = 0.f; s1 = 0.f;
      exps(0, 8);
      sched_fence();
      wgmma_wait<0>();
      release(B_EMPTYA + vs * 8);
      float lo = 0.f;
      if (__builtin_expect(j == 0, 0)) {
        o_scale();
        l0 = 0.f; l1 = 0.f;
        lo = LAZY_LOW;
      }
      bool bad = __any_sync(~0u, !(s0 <= LAZY_LIMIT && s1 <= LAZY_LIMIT));
      if (__builtin_expect(!bad, 1)) {
        exps(8, 16);
        cvtP();
        bad = __any_sync(~0u, !(s0 <= LAZY_LIMIT && s1 <= LAZY_LIMIT && s0 >= lo && s1 >= lo));
      }
      if (__builtin_expect(bad, 0)) {
        const uint32_t* kp = reinterpret_cast<const uint32_t*>(prm.k + ((size_t)kg * 4 * SK + t * 128 + g) * DH) + t4;
        const uint4* qp = qpark + h * (8 * 256);
        float4 tmp[16];
        uint4 qf[8];
#pragma unroll
        for (int kk = 0; kk < 8; kk++) qf[kk] = __ldcg(qp + kk * 256);
#pragma unroll 1
        for (int jn = 0; jn < 16; jn++) {
          float c[4] = {0.f, 0.f, 0.f, 0.f};
#pragma unroll
          for (int kk = 0; kk < 8; kk++) mma16816(c, qf[kk].x, qf[kk].y, qf[kk].z, qf[kk].w, __ldg(kp + jn * 512 + kk * 8), __ldg(kp + jn * 512 + kk * 8 + 4));
          tmp[jn] = make_float4(c[0], c[1], c[2], c[3]);
        }
#pragma unroll
        for (int jn = 0; jn < 16; jn++) { const float4 c = tmp[jn]; S[jn * 4] = c.x; S[jn * 4 + 1] = c.y; S[jn * 4 + 2] = c.z; S[jn * 4 + 3] = c.w; }
        float x0, x1;
        row_max(x0, x1);
        const float n0 = j ? fmaxf(mb0, x0 * sc) : x0 * sc, n1 = j ? fmaxf(mb1, x1 * sc) : x1 * sc;
        const float f0 = j ? ex2(mb0 - n0) : 1.f, f1 = j ? ex2(mb1 - n1) : 1.f;
        mb0 = n0; mb1 = n1;
        l0 *= f0; l1 *= f1;
#pragma unroll
        for (int i = 0; i < 16; i++) { O[i * 4] *= f0; O[i * 4 + 1] *= f0; O[i * 4 + 2] *= f1; O[i * 4 + 3] *= f1; }
        s0 = 0.f; s1 = 0.f;
        exps(0, 16);
        cvtP();
      }
      l0 += s0; l1 += s1;
    }
    STAMP(70); GSTAMP(66);
    turn_begin();
    issue_pv(dB_n16 + 6144, 0);
    {
      const int lane = get_lane();
      uint32_t A[128];
#pragma unroll
      for (int i = 0; i < 16; i++) {
        const uint4 v = lds128(sb + SM_STASH + i * 4096 + ct * 16);
        A[i * 4] = v.x; A[i * 4 + 1] = v.y; A[i * 4 + 2] = v.z; A[i * 4 + 3] = v.w;
      }
      o_scale();
      wgmma_wait<0>();
#pragma unroll
      for (int i = 16; i < 24; i++) {
        const uint4 v = lds128(sb + SM_STASH + i * 4096 + ct * 16);
        A[i * 4] = v.x; A[i * 4 + 1] = v.y; A[i * 4 + 2] = v.z; A[i * 4 + 3] = v.w;
      }
#pragma unroll
      for (int i = 0; i < 8; i++) {
        const uint4 v = o_frag(i);
        A[96 + i * 4] = v.x; A[96 + i * 4 + 1] = v.y; A[96 + i * 4 + 2] = v.z; A[96 + i * 4 + 3] = v.w;
      }
      if (__any_sync(~0u, A[95] != 0x12345678u || A[64] != 0x9abcdef0u || lane == 0)) {
        release(B_EMPTYA + 24);
        release1(B_ST);
      }
      STAMP(71);
      uint32_t xb = w8 * 1024 + lane * 16;
      const uint32_t peer = __shfl_sync(~0u, relBar, 1) - sBar;
      float c0[32], kp[16];
      int gr = 0;
      auto recv = [&]() {
        uint4 u[2];
#pragma unroll
        for (int j = 0; j < 2; j++) u[j] = lds128(sb + SM_XCH + xb + j * 512);
#pragma unroll
        for (int j = 0; j < 2; j++)
          asm volatile("stmatrix.sync.aligned.m8n8.x4.shared.b16 [%0], {%1,%2,%3,%4};" ::"r"(sb + SM_OUT + xb + j * 512),
                       "r"(pack_bf16(kp[j * 8] + bf_lo(u[j].x), kp[j * 8 + 1] + bf_hi(u[j].x))), "r"(pack_bf16(kp[j * 8 + 2] + bf_lo(u[j].y), kp[j * 8 + 3] + bf_hi(u[j].y))),
                       "r"(pack_bf16(kp[j * 8 + 4] + bf_lo(u[j].z), kp[j * 8 + 5] + bf_hi(u[j].z))), "r"(pack_bf16(kp[j * 8 + 6] + bf_lo(u[j].w), kp[j * 8 + 7] + bf_hi(u[j].w))) : "memory");
        bar_arrive(8 + cw, 160);
        xb ^= 8192;
      };
#pragma unroll 1
      for (int c = 0;; c++) {
#pragma unroll
        for (int hd = 0; hd < 4; hd++) {
          if (!(hd & 1)) turn_begin();
          const uint32_t db = dB_k + (gr + (hd & 1)) * 1024;
#pragma unroll
          for (int kk = 0; kk < 8; kk++)
            wgmma64_rs(c0, A[hd * 32 + kk * 4], A[hd * 32 + kk * 4 + 1], A[hd * 32 + kk * 4 + 2], A[hd * 32 + kk * 4 + 3], db + kk * 128, (hd | kk) != 0);
          wgmma_commit();
          if (hd & 1) {
            if (hd == 1 || c < 8 || cw == 0) turn_end();
            if (hd == 1 ? c == 8 : (c & 7) != 0) {
              if (hd == 1) mbar_wait(sBar + B_XF + 8, 1);
              recv();
            }
            wgmma_wait<1>();
            release1(B_EMPTYO + gr * 8);
            wgmma_wait<0>();
            release1(B_EMPTYO + gr * 8 + 8);
            gr = (gr + 2) & 7;
          }
        }
        if (c == 8) break;
        if (c == 0) mbar_wait(sBar + B_EMPTYA + 24, 0);
#pragma unroll
        for (int j = 0; j < 2; j++)
          asm volatile("st.async.shared::cluster.mbarrier::complete_tx::bytes.v4.b32 [%0], {%1,%2,%3,%4}, [%5];" ::"r"(sb + SM_XCH + xb + peer + j * 512),
                       "r"(pack_bf16(c0[j * 16 + 2], c0[j * 16 + 3])), "r"(pack_bf16(c0[j * 16 + 6], c0[j * 16 + 7])), "r"(pack_bf16(c0[j * 16 + 10], c0[j * 16 + 11])),
                       "r"(pack_bf16(c0[j * 16 + 14], c0[j * 16 + 15])), "r"(sBar + B_XF + (c & 1) * 8 + peer) : "memory");
#pragma unroll
        for (int j = 0; j < 16; j++) kp[j] = c0[(j >> 1) * 4 + (j & 1)];
      }
      STAMP(72); GSTAMP(67);
      uint2* const dst = reinterpret_cast<uint2*>(g_ones + F_PART) + ((qt * 8 + w8) * 40 + 32 + rank * 4 + kg) * 256 + lane;
#pragma unroll
      for (int jb = 0; jb < 8; jb++)
        asm volatile("st.relaxed.gpu.global.v2.u32 [%0], {%1,%2};" ::"l"(dst + jb * 32), "r"(pack_bf16(c0[jb * 4], c0[jb * 4 + 1])), "r"(pack_bf16(c0[jb * 4 + 2], c0[jb * 4 + 3])) : "memory");
    }
    STAMP(73);
    {
    const int lane = get_lane(), g = lane >> 2, t4 = lane & 3;
    uint32_t* const tsu = reinterpret_cast<uint32_t*>(smem_raw + SM_T);
    float* const tsf = reinterpret_cast<float*>(smem_raw + SM_T);
    const int row0 = qt * 128 + hg * 16;
    {
      uint32_t xa[9], xb[9], wb[9];
      uint4 md[9];
      const uint32_t* ap = reinterpret_cast<const uint32_t*>(g_ones + F_PART) + (qt * 8 + hg) * 20480 + w8 * 32 + lane;
      const uint32_t pb = sb + (lane >> 3) * 1024 + w8 * 128 + (lane & 7) * 16;
      float av[9][4];
      uint2 pv[12];
      const uint32_t ident = (g >> 1) == t4 ? 0x3f80u << ((g & 1) * 16) : 0u;
      auto ld_late = [&]() {
        bool bad = false;
#pragma unroll
        for (int s = 0; s < 12; s++)
          if (pv[s].x == ~0u || pv[s].y == ~0u) {
            bad = true;
            if (s < 4) { pv[s].x = ldr1(ap + (28 + s) * 512); pv[s].y = ldr1(ap + (28 + s) * 512 + 256); }
            else pv[s] = ldr2(ap + (28 + s) * 512 + w8 * 32 + lane);
          }
        return bad;
      };
#pragma unroll
      for (int s = 0; s < 12; s++) pv[s] = make_uint2(~0u, ~0u);
      uint32_t* const tr = reinterpret_cast<uint32_t*>(smem_raw + SM_X2) + g * 292 + w8 * 4 + t4;
      float sx[4] = {0.f, 0.f, 0.f, 0.f}, qa[4] = {0.f, 0.f, 0.f, 0.f}, qb[4] = {0.f, 0.f, 0.f, 0.f};
      auto stat = [&](int i) {
        xa[i] = hfma2(md[i].x, pack_bf16(av[i][0], av[i][1]), xa[i]);
        xb[i] = hfma2(md[i].x, pack_bf16(av[i][2], av[i][3]), xb[i]);
        mma1688(sx, xa[i], xb[i], wb[i]);
        mma1688(qa, xa[i], xb[i], xa[i]);
        mma1688(qb, xa[i], xb[i], xb[i]);
      };
#pragma unroll 1
      for (uint32_t n = 0;; n++) {
        uint32_t go = 1;
        if (n == 0) asm volatile("{\n.reg .pred p;\nmbarrier.test_wait.parity.shared::cta.b64 p, [%1], 0;\nselp.u32 %0, 1, 0, p;\n}\n" : "=r"(go) : "r"(sBar + B_G2) : "memory");
        bool bad = true;
        if (go) bad = ld_late();
        if (!__any_sync(~0u, bad) || n > (1u << 15)) break;
        if (n == 0) {
          mbar_wait(sBar + B_MD, 0);
#pragma unroll
          for (int i = 0; i < 9; i++) md[i] = lds128(sb + SM_MD + (i * 32 + w8 * 4 + t4) * 16);
          mbar_wait(sBar + B_XR, 0);
#pragma unroll
          for (int i = 0; i < 9; i++) { xa[i] = tr[i * 32]; xb[i] = tr[8 * 292 + i * 32]; }
          mbar_wait(sBar + B_G1, 0);
          STAMP(74);
#pragma unroll
          for (int i = 0; i < 9; i++) {
            const uint32_t w = *reinterpret_cast<const uint32_t*>(smem_raw + SM_MOD + (i * 32 + w8 * 4 + t4) * 8 + (g & 1) * 4);
            wb[i] = g == 0 ? 0x3f803f80u : g < 3 ? w : 0u;
          }
#pragma unroll 1
          for (uint32_t m = 0;; m++) {
#pragma unroll
            for (int i = 0; i < 36; i++) av[i >> 2][i & 3] = 0.f;
#pragma unroll
            for (int s = 0; s < 14; s++) {
              uint32_t v[4];
              ldsm4(v, pb + SM_PB + s * 4096);
              const int t = s % 7, ch = (t + s / 7 * 4) % 9;
              if (t >= 2) mma16816(av[ch], v[0], v[1], v[2], v[3], ident, ident);
              else { mma1688(av[ch], v[0], v[1], ident); mma1688(av[(ch + 7) % 9], v[2], v[3], ident); }
            }
            float t = 0.f;
#pragma unroll
            for (int i = 0; i < 9; i++) t += av[i][0] + av[i][2];
            if (__builtin_expect(!__any_sync(~0u, t != t), 1) || m > (1u << 15)) break;
            bool miss = false;
#pragma unroll 1
            for (int s = 0; s < 56; s++) {
              volatile uint32_t* const pa = reinterpret_cast<uint32_t*>(smem_raw + SM_PB + s * 1024) + w8 * 32 + lane;
              miss |= *pa == ~0u;
              *pa = ldr1(ap + s * 256);
            }
            __syncwarp();
            if (!__any_sync(~0u, miss)) break;
          }
          STAMP(69);
          mbar_wait(sBar + B_G2, 0);
          STAMP(48);
        }
      }
      STAMP(77);
#pragma unroll
      for (int s = 0; s < 4; s++) {
        mma1688(av[(2 * s + 7) % 9], pv[s].x, pv[s].y, ident);
        mma16816(av[(2 * s + 8) % 9], pv[4 + s].x, pv[4 + s].y, pv[8 + s].y, pv[8 + s].x, ident, ident);
      }
#pragma unroll
      for (int i = 0; i < 9; i++) stat(i);
      STAMP(40);
      float* const ps = reinterpret_cast<float*>(smem_raw + SM_PB);
      if (t4 < 2) {
        *reinterpret_cast<float2*>(ps + w8 * 32 + g * 4 + t4 * 2) = make_float2(sx[0], sx[1]);
        *reinterpret_cast<float2*>(ps + 256 + w8 * 32 + g * 4 + t4 * 2) = make_float2(sx[2], sx[3]);
      }
      if (ident) {
        ps[512 + w8 * 32 + g] = (g & 1) ? qa[1] : qa[0];
        ps[512 + w8 * 32 + g + 8] = (g & 1) ? qb[3] : qb[2];
      }
      bar_sync(5, 256);
      STAMP(44);
      float mean = 0.f, dot = 0.f, m2 = 0.f;
#pragma unroll
      for (int i = 0; i < 4; i++) {
        const float4 q = *reinterpret_cast<const float4*>(ps + (lane & 8) * 32 + (lane & 16) * 8 + i * 32 + (lane & 7) * 4);
        mean += q.x; dot += q.y + q.z; m2 += ps[512 + (lane & 16) * 8 + i * 32 + (lane & 15)];
      }
      const float2 sab = *reinterpret_cast<const float2*>(smem_raw + SM_ZERO + 16);
      mean += __shfl_xor_sync(~0u, mean, 16);
      dot += __shfl_xor_sync(~0u, dot, 16);
      m2 += __shfl_xor_sync(~0u, m2, 16);
      mean *= 1.f / DM;
      const float rs = rcp(bfr(sqrt_a(bfr(bfr(fmaxf(fmaf(m2, 1.f / DM, -mean * mean), 0.f)) + 1e-5f))));
      const uint32_t nm = pack_bf16(-mean, -mean);
      uint32_t u = pack_bf16(0.f, fmaf(rs, fmaf(bf_lo(nm), sab.x, dot), sab.y));
      u = ((u & 0x7fff0000u) > 0x7f800000u) ? 0u : (u ^ ((u >> 31) ? 0xffff0000u : 0x80000000u));
      u |= 0xffffu - (row0 + (lane & 15));
      const uint32_t m1 = __reduce_max_sync(~0u, u), m2k = __reduce_max_sync(~0u, u == m1 ? 0u : u);
      if (w8 == 7) asm volatile("st.relaxed.gpu.global.v2.u32 [%0], {%1,%2};" ::"l"(reinterpret_cast<uint2*>(g_ones + F_KEY) + lane * 128 + b), "r"(~m1), "r"(~m2k) : "memory");
      STAMP(41);
      const int r1 = ~m1 & 15, r2 = ~m2k & 15;
      const uint32_t r2t = pack_bf16(rs, rs - bfr(rs));
      const uint32_t rA = __shfl_sync(~0u, r2t, g), rB = __shfl_sync(~0u, r2t, g + 8);
      const uint32_t nmA = __shfl_sync(~0u, nm, g), nmB = __shfl_sync(~0u, nm, g + 8);
      const uint32_t hA = __byte_perm(rA, 0, 0x1010), lA = __byte_perm(rA, 0, 0x3232), hB = __byte_perm(rB, 0, 0x1010), lB = __byte_perm(rB, 0, 0x3232);
      uint32_t* const hx = reinterpret_cast<uint32_t*>(g_ones + F_HX + b * 288) + w8 * 4 + t4;
      const bool topA = g == r1 || g == r2, topB = g + 8 == r1 || g + 8 == r2;
      uint32_t* const pA = hx + (g == r2 ? 576 : 0);
      uint32_t* const pB = hx + (g + 8 == r2 ? 576 : 0);
#pragma unroll
      for (int i = 0; i < 9; i++) {
        const uint32_t da = hadd2(xa[i], nmA), db = hadd2(xb[i], nmB);
        const uint32_t ha = hfma2(hfma2(da, hA, hmul2(da, lA)), md[i].z, md[i].y), hb = hfma2(hfma2(db, hB, hmul2(db, lB)), md[i].z, md[i].y);
        if (topA) str1(pA + i * 32, ha);
        if (topB) str1(pB + i * 32, hb);
        tr[i * 32] = hfma2(md[i].w, ha, xa[i]);
        tr[8 * 292 + i * 32] = hfma2(md[i].w, hb, xb[i]);
      }
#pragma unroll
      for (int i = 0; i < 9; i++) {
        if (topA) str1(pA + 288 + i * 32, xa[i]);
        if (topB) str1(pB + 288 + i * 32, xb[i]);
      }
      if (tid == 128) tsu[34] = (1u << r1) | (1u << r2);
      bar_arrive(11, 288);
    }
    STAMP(75);
    const int kq = w8 >> 1;
    const int ng = w8 < 2 ? 3 : 2;
    uint32_t bg[9][10], bd[12][5];
    mbar_wait(sBar + B_FFN, 0);
    STAMP(42);
    {
      const uint32_t wa = sb + ((w8 & 1) ? SM_WU : SM_WG) + (kq * 144 + (lane & 6) * 2 + ((lane >> 2) & 2) + (lane & 1)) * 80 + (lane >> 4) * 16;
#pragma unroll
      for (int ks = 0; ks < 9; ks++) {
        uint32_t b0[4], b1[4], b2[2];
        ldsm4t(b0, wa + ks * 1280); ldsm4t(b1, wa + ks * 1280 + 32); ldsm2t(b2, wa + ks * 1280 + 64 - (lane >> 4) * 16);
#pragma unroll
        for (int i = 0; i < 4; i++) { bg[ks][i] = b0[i]; bg[ks][4 + i] = b1[i]; }
        bg[ks][8] = b2[0]; bg[ks][9] = b2[1];
      }
#pragma unroll
      for (int i = 0; i < 12; i++) {
        if (i < 8 || ng == 3) {
          const int bx = (w8 >> 1) + (i >> 2) * 4;
          const uint32_t a = sb + SM_WD + bx * 5120 + lane * 128 + (((((w8 & 1) * 4 + (i & 3)) ^ lane) & 7) << 4);
          uint32_t b0[4];
          ldsm4t(b0, a);
          asm volatile("ldmatrix.sync.aligned.m8n8.x1.trans.shared.b16 {%0}, [%1];" : "=r"(bd[i][4]) : "r"(a + 4096) : "memory");
#pragma unroll
          for (int j = 0; j < 4; j++) bd[i][j] = b0[j];
        }
      }
    }
    STAMP(43);
    mbar_wait(sBar + B_G3, 0);
    STAMP(76);
    {
      float c[2][5][4];
#pragma unroll
      for (int i = 0; i < 10; i++) c[i & 1][i >> 1][0] = c[i & 1][i >> 1][1] = c[i & 1][i >> 1][2] = c[i & 1][i >> 1][3] = 0.f;
      const uint2* hp = reinterpret_cast<const uint2*>(smem_raw + SM_T + 4096) + (g & 1) * 144 + kq * 36 + t4;
#pragma unroll
      for (int ks = 0; ks < 9; ks++) {
        const uint2 a = hp[ks * 4];
#pragma unroll
        for (int i = 0; i < 5; i++) mma16816(c[ks & 1][i], a.x, 0u, a.y, 0u, bg[ks][2 * i], bg[ks][2 * i + 1]);
      }
      float* const part = tsf + 64;
      if (g < 2) {
#pragma unroll
        for (int i = 0; i < 5; i++)
          *reinterpret_cast<float2*>(part + w8 * 80 + g * 40 + i * 8 + t4 * 2) = make_float2(c[0][i][0] + c[1][i][0], c[0][i][1] + c[1][i][1]);
      }
      STAMP(45);
      bar_sync(5, 256);
      STAMP(46);
      auto act2 = [&](int f) {
        const float2* pp = reinterpret_cast<const float2*>(part + (g & 1) * 40 + f + (b & 1) * 4);
        const float2 g0 = pp[0], g1 = pp[80], g2 = pp[160], g3 = pp[240], u0 = pp[40], u1 = pp[120], u2 = pp[200], u3 = pp[280];
        return pack_bf16(silu_bf(bfr((g0.x + g1.x) + (g2.x + g3.x))) * bfr((u0.x + u1.x) + (u2.x + u3.x)),
                         silu_bf(bfr((g0.y + g1.y) + (g2.y + g3.y))) * bfr((u0.y + u1.y) + (u2.y + u3.y)));
      };
      const uint32_t v0 = act2((g >> 1) * 8 + t4 * 2), v1 = act2(32 + (t4 & 1) * 2);
      uint32_t a6[5];
#pragma unroll
      for (int i = 0; i < 4; i++) a6[i] = __shfl_sync(~0u, v0, i * 8 + (lane & 7));
      a6[4] = t4 < 2 ? v1 : 0u;
      STAMP(47);
      float* const yp = reinterpret_cast<float*>(g_ones + F_YP) + ((w8 * 2 + (g & 1)) * 128 + b) * 32 + (g >> 1) * 8 + t4 * 2;
#pragma unroll
      for (int m = 0; m < 3; m++) {
        if (m < 2 || ng == 3) {
          float y[4][4];
#pragma unroll
          for (int i = 0; i < 4; i++) {
            y[i][0] = y[i][1] = y[i][2] = y[i][3] = 0.f;
            mma16816(y[i], a6[0], 0u, a6[1], 0u, bd[m * 4 + i][0], bd[m * 4 + i][1]);
          }
#pragma unroll
          for (int i = 0; i < 4; i++) mma16816(y[i], a6[2], 0u, a6[3], 0u, bd[m * 4 + i][2], bd[m * 4 + i][3]);
#pragma unroll
          for (int i = 0; i < 4; i++) mma1688(y[i], a6[4], 0u, bd[m * 4 + i][4]);
          const bool u1 = lane & 8, u2 = lane & 16;
          const float y0 = u2 ? (u1 ? y[3][0] : y[2][0]) : (u1 ? y[1][0] : y[0][0]), y1 = u2 ? (u1 ? y[3][1] : y[2][1]) : (u1 ? y[1][1] : y[0][1]);
          asm volatile("st.relaxed.gpu.global.v2.f32 [%0], {%1,%2};" ::"l"(yp + m * (16 * 4096)), "f"(y0), "f"(y1) : "memory");
        }
      }
    }
    STAMP(78);
    const uint32_t k1 = tsu[32], k2 = tsu[33];
    const int row1 = ~k1 & (SQ - 1), row2 = ~k2 & (SQ - 1);
    const int f = b + 128 * (7 - w8);
    if (f < 144) {
      const int tok = (f >> 2) & 1, col = ((f >> 3) * 4 + (f & 3)) * 8 + (lane & 1) * 4 + (lane & 2) + ((lane >> 2) & 1);
      const uint32_t key = tok ? k2 : k1;
      const int row = tok ? row2 : row1;
      const int c1 = ((row1 >> 5) & 3) * 32 + (row1 >> 7) * 2 + ((row1 >> 4) & 1), cr = ((row >> 5) & 3) * 32 + (row >> 7) * 2 + ((row >> 4) & 1);
      const uint16_t* xp = reinterpret_cast<const uint16_t*>(g_ones + F_HX + cr * 288 + (tok && c1 == cr ? 144 : 0) + 72) + col;
      const float gb = __uint_as_float((uint32_t)reinterpret_cast<const uint16_t*>(smem_raw + SM_MD)[(col >> 1) * 8 + 6 + (col & 1)] << 16);
      const float hv = __uint_as_float((uint32_t)reinterpret_cast<const uint16_t*>(smem_raw + SM_T + 4096)[tok * DM + col] << 16);
      const float r = __uint_as_float((key & 0xffff0000u) ^ ((key >> 31) ? 0x80000000u : 0xffff0000u));
      const float sg = bfr(rcp(1.f + __expf(-r)));
      const uint4* pp = g_ones + F_YP + (f >> 2) * 1024 + (f & 3) * 2 + (lane >> 1) * 8 + (lane & 1);
      uint4 pv[8];
      uint16_t xv;
      PSTAMP(352, 62);
#pragma unroll 1
      for (uint32_t n = 0;; n++) {
        asm volatile("ld.relaxed.gpu.global.u16 %0, [%1];" : "=h"(xv) : "l"(xp) : "memory");
#pragma unroll
        for (int i = 0; i < 8; i++) pv[i] = ldr4(pp + i * 128);
        bool bad = xv == 0xffff;
#pragma unroll
        for (int i = 0; i < 8; i++) bad |= unset(pv[i]);
        if (!bad) break;
        if (n > (1u << 15)) { SETERR(32); break; }
      }
      __syncwarp();
      PSTAMP(352, 63);
      float s[4];
#pragma unroll
      for (int j = 0; j < 4; j++) {
        auto w = [&](int i) { return __uint_as_float(j == 0 ? pv[i].x : j == 1 ? pv[i].y : j == 2 ? pv[i].z : pv[i].w); };
        s[j] = ((w(0) + w(1)) + (w(2) + w(3))) + ((w(4) + w(5)) + (w(6) + w(7)));
      }
      const bool u2 = lane & 2, u4 = lane & 4;
#pragma unroll
      for (int i = 0; i < 2; i++) { const float snd = u2 ? s[i] : s[i + 2], kp = u2 ? s[i + 2] : s[i]; s[i] = kp + __shfl_xor_sync(~0u, snd, 2); }
      { const float snd = u4 ? s[0] : s[1], kp = u4 ? s[1] : s[0]; s[0] = kp + __shfl_xor_sync(~0u, snd, 4); }
      s[0] += __shfl_xor_sync(~0u, s[0], 8);
      s[0] += __shfl_xor_sync(~0u, s[0], 16);
      const float hh = bfr(hv + bfr(bfr(s[0]) * sg));
      if (lane < 8) prm.out[(size_t)row * DM + col] = __float2bfloat16(__uint_as_float((uint32_t)xv << 16) + bfr(gb * hh));
      PSTAMP(352, 49);
    }
    if (w8 == 5 && lane < 9) g_mod1[b * 9 + lane] = make_uint4(0u, 0u, 0u, 0u);
    if (w8 == 5 && lane == 9) *reinterpret_cast<uint2*>(&g_cnt[(C_Q + b) * 32]) = make_uint2(0u, 0u);
    if (w8 == 5 && lane == 10 && b == 0) g_cnt[C_SIDE * 32] = 0;
    STAMP(79); GSTAMP(91);
    }
  }
}

typedef CUresult (*PFN_enc)(CUtensorMap*, CUtensorMapDataType, cuuint32_t, void*, const cuuint64_t*, const cuuint64_t*,
                            const cuuint32_t*, const cuuint32_t*, CUtensorMapInterleave, CUtensorMapSwizzle,
                            CUtensorMapL2promotion, CUtensorMapFloatOOBfill);
static PFN_enc g_enc = nullptr;
static CUtensorMap mk_map(const void* p, uint64_t cols, uint64_t rows, uint32_t bc, uint32_t br, bool swz = true) {
  CUtensorMap m;
  cuuint64_t dims[2] = {cols, rows};
  cuuint64_t strides[1] = {cols * 2};
  cuuint32_t box[2] = {bc, br}, es[2] = {1, 1};
  g_enc(&m, CU_TENSOR_MAP_DATA_TYPE_BFLOAT16, 2, const_cast<void*>(p), dims, strides, box, es, CU_TENSOR_MAP_INTERLEAVE_NONE,
        swz ? CU_TENSOR_MAP_SWIZZLE_128B : CU_TENSOR_MAP_SWIZZLE_NONE, swz ? CU_TENSOR_MAP_L2_PROMOTION_L2_128B : CU_TENSOR_MAP_L2_PROMOTION_NONE,
        CU_TENSOR_MAP_FLOAT_OOB_FILL_NONE);
  return m;
}

extern "C" void kernel_launch(void* const* d_in, const int* in_sizes, int n_in, void* d_out, int out_size) {
  if (!g_enc) {
    cudaDriverEntryPointQueryResult st;
    cudaGetDriverEntryPoint("cuTensorMapEncodeTiled", (void**)&g_enc, cudaEnableDefault, &st);
    cudaFuncSetAttribute(k_mega, cudaFuncAttributeMaxDynamicSharedMemorySize, SM_TOTAL);
  }
  CUtensorMap mX = mk_map(d_in[0], DM, SQ, 64, 128);
  CUtensorMap mWq = mk_map(d_in[3], HQ * DH, DM, 64, 144);
  CUtensorMap mK = mk_map(d_in[1], DH, HKV * SK, 64, 128);
  CUtensorMap mV = mk_map(d_in[2], DH, HKV * SK, 64, 128);
  CUtensorMap mWo = mk_map(d_in[4], DM, HQ * DH, 64, 128);
  CUtensorMap mWg = mk_map(d_in[7], FF, DM, 40, 48, false);
  CUtensorMap mWu = mk_map(d_in[8], FF, DM, 40, 48, false);
  CUtensorMap mWd = mk_map(d_in[9], DM, FF, 64, 40);
  Params prm;
  prm.x = (const bf16*)d_in[0]; prm.k = (const bf16*)d_in[1]; prm.v = (const bf16*)d_in[2]; prm.wo = (const bf16*)d_in[4]; prm.wq = (const bf16*)d_in[3];
  prm.w_r = (const bf16*)d_in[6]; prm.c = (const bf16*)d_in[10]; prm.w_mod = (const bf16*)d_in[11];
  prm.wg = (const bf16*)d_in[7]; prm.wu = (const bf16*)d_in[8]; prm.wd = (const bf16*)d_in[9];
  prm.out = (bf16*)d_out;
  cudaLaunchConfig_t cfg = {};
  cfg.gridDim = dim3(128); cfg.blockDim = dim3(384); cfg.dynamicSmemBytes = SM_TOTAL; cfg.stream = cudaStreamPerThread;
  cudaLaunchAttribute at[1];
  at[0].id = cudaLaunchAttributeClusterDimension;
  at[0].val.clusterDim.x = 2; at[0].val.clusterDim.y = 1; at[0].val.clusterDim.z = 1;
  cfg.attrs = at; cfg.numAttrs = 1;
  cudaLaunchKernelEx(&cfg, k_mega, mX, mWq, mK, mV, mWo, mWg, mWu, mWd, prm);
}
```

```cpp
#include <cuda_runtime.h>
#include <cuda_bf16.h>
#include <cuda.h>
#include <stdint.h>

typedef __nv_bfloat16 bf16;

constexpr int SQ = 2048, DM = 576, HQ = 32, HKV = 16, SK = 2048, DH = 128, FF = 4608;

#define TCH 20
#define TF0 26
#define TW0 16
#define TWN 4
#define FAKEB 0
#define FILLS 30
#define WOMC 0
#define FFNS 0x6420
#define ORD 1
#define FIXS 0
#define HINTH 1
#define HINTW 1
#define PFO 1
#define TN 3
#define FGAP 0
#define FGN 8
#define BGE 0
#define FPRED 1
#define FK 1
#define FD 300
#define XPF 0
#define WQPF0 0
#define WQPF1 0xff
#define FFNQ 2
#define WQPF2 0
#define QTH 7
#define MPF 1
#define FILLP 31
#define FILL0 25
#define FFN0 20
#define FILLN 8
#define FFNB 6
#define PF0 20
#define FFNR 1
#define FFND 1
#define KV0 16
#define KVS 2
#define QPF 6
#define EF 31
#define WOP 20
#define TLBW 0
#define NOFFN 0
#define FLATE 0
#define RELF 1
#define REL_FENCE() asm volatile("fence.acq_rel.gpu;" ::: "memory")
#define FILLMAX (F_N / 128)
#define XN 4
#define MODB 0
#define QPV 0
#define LATEG 0
#define RETL 1
#define HINTA 15
#define SIDEF 3
#define FFNE 15
#define TE_POS 8
#define LAZY_LIMIT 1.8446744e19f
#define LAZY_LOW 5.4210109e-20f
__device__ uint4 g_mod1[8 * 144];
__device__ uint4 g_mod2[288];
__device__ uint4 g_q[128 * 4 * 8 * 256];
constexpr int F_HX = 0;
constexpr int F_YP = 128 * 288;
constexpr int F_KEY = 128 * 576;
constexpr int F_PART = 128 * 640;
constexpr int F_N = 640 + 5120;
__device__ uint4 g_ones[128 * F_N];
__device__ unsigned int g_cnt[136 * 32];
__device__ unsigned int g_err;
#define HAS_ERR
enum { C_SIDE = 1, C_Q = 8 };

#define STAMP(i)
#define KSTAMP(i)
#define GSTAMP(i)
#define SETERR(v)
#define PSTAMP(t, i)

__device__ __forceinline__ int get_lane() {
  int l;
  asm volatile("mov.u32 %0, %%laneid;" : "=r"(l));
  __builtin_assume(l >= 0 && l < 32);
  return l;
}
__device__ __forceinline__ uint32_t smem_u32(const void* p) { return (uint32_t)__cvta_generic_to_shared(p); }
__device__ __forceinline__ void mbar_init(uint32_t a, uint32_t cnt) { asm volatile("mbarrier.init.shared::cta.b64 [%0], %1;" ::"r"(a), "r"(cnt)); }
__device__ __forceinline__ void mbar_expect_tx(uint32_t a, uint32_t bytes) { asm volatile("mbarrier.arrive.expect_tx.shared::cta.b64 _, [%0], %1;" ::"r"(a), "r"(bytes) : "memory"); }
__device__ __forceinline__ void mbar_arrive(uint32_t a) { asm volatile("mbarrier.arrive.shared::cta.b64 _, [%0];" ::"r"(a) : "memory"); }
__device__ __forceinline__ void mbar_arrive_cl(uint32_t a_cluster) { asm volatile("mbarrier.arrive.shared::cluster.b64 _, [%0];" ::"r"(a_cluster) : "memory"); }
__device__ __forceinline__ void mbar_wait(uint32_t a, uint32_t parity) {
  asm volatile(
      "{\n.reg .pred p;\n.reg .u32 n;\nmov.u32 n, 0;\n"
      "WAIT_LOOP:\n"
      "mbarrier.try_wait.parity.shared::cta.b64 p, [%0], %1;\n"
      "@p bra WAIT_DONE;\n"
      "add.u32 n, n, 1;\n"
      "setp.lt.u32 p, n, 65536;\n"
      "@p bra WAIT_LOOP;\n"
      "WAIT_DONE:\n}\n" ::"r"(a), "r"(parity), "l"(&g_err) : "memory");
}
__device__ __forceinline__ void cnt_wait(int idx, unsigned target) {
  for (uint32_t n = 0;; n++) {
    unsigned v;
    asm volatile("ld.relaxed.gpu.global.u32 %0, [%1];" : "=r"(v) : "l"(&g_cnt[idx * 32]) : "memory");
    if (v >= target) break;
    if (n > (1u << 15)) { SETERR(2); break; }
  }
}
__device__ __forceinline__ void cnt_wait1(int word, unsigned target) {
  for (uint32_t n = 0;; n++) {
    unsigned v;
    asm volatile("ld.relaxed.gpu.global.u32 %0, [%1];" : "=r"(v) : "l"(&g_cnt[word]) : "memory");
    if (v >= target) break;
    if (n > (1u << 15)) { SETERR(2); break; }
  }
}
__device__ __forceinline__ void cnt_arrive(int idx) {
  asm volatile("red.relaxed.gpu.global.add.u32 [%0], 1;" ::"l"(&g_cnt[idx * 32]) : "memory");
}
__device__ __forceinline__ uint4 poll4(const uint4* p) {
  uint4 v;
  uint32_t n = 0;
  while (true) {
    asm volatile("ld.relaxed.gpu.global.v4.u32 {%0,%1,%2,%3}, [%4];" : "=r"(v.x), "=r"(v.y), "=r"(v.z), "=r"(v.w) : "l"(p) : "memory");
    if (v.x && v.y && v.z && v.w) break;
    if (++n > (1u << 15)) { SETERR(4); break; }
  }
  return v;
}
__device__ __forceinline__ void poll8(const uint4* p, const uint4* q, uint4& v, uint4& w) {
  uint32_t n = 0;
  while (true) {
    asm volatile("ld.relaxed.gpu.global.v4.u32 {%0,%1,%2,%3}, [%4];" : "=r"(v.x), "=r"(v.y), "=r"(v.z), "=r"(v.w) : "l"(p) : "memory");
    asm volatile("ld.relaxed.gpu.global.v4.u32 {%0,%1,%2,%3}, [%4];" : "=r"(w.x), "=r"(w.y), "=r"(w.z), "=r"(w.w) : "l"(q) : "memory");
    if (v.x && v.y && v.z && v.w && w.x && w.y && w.z && w.w) break;
    if (++n > (1u << 15)) { SETERR(4); break; }
  }
}
__device__ __forceinline__ uint4 ldr4(const void* p) {
  uint4 v;
  asm volatile("ld.relaxed.gpu.global.v4.u32 {%0,%1,%2,%3}, [%4];" : "=r"(v.x), "=r"(v.y), "=r"(v.z), "=r"(v.w) : "l"(p) : "memory");
  return v;
}
__device__ __forceinline__ uint2 ldr2(const void* p) {
  uint2 v;
  asm volatile("ld.relaxed.gpu.global.v2.u32 {%0,%1}, [%2];" : "=r"(v.x), "=r"(v.y) : "l"(p) : "memory");
  return v;
}
__device__ __forceinline__ uint32_t ldr1(const void* p) {
  uint32_t v;
  asm volatile("ld.relaxed.gpu.global.u32 %0, [%1];" : "=r"(v) : "l"(p) : "memory");
  return v;
}
__device__ __forceinline__ void str1(void* p, uint32_t v) { asm volatile("st.relaxed.gpu.global.u32 [%0], %1;" ::"l"(p), "r"(v) : "memory"); }
__device__ __forceinline__ bool unset(uint4 v) { return v.x == ~0u || v.y == ~0u || v.z == ~0u || v.w == ~0u; }
__device__ __forceinline__ bool nan2(uint32_t v) {
  uint32_t r;
  asm("{\n.reg .pred p, q;\nsetp.nan.bf16x2 p|q, %1, %1;\nor.pred p, p, q;\nselp.u32 %0, 1, 0, p;\n}\n" : "=r"(r) : "r"(v));
  return r != 0;
}
__device__ __forceinline__ uint32_t hmul2(uint32_t a, uint32_t b) { uint32_t r; asm("mul.rn.bf16x2 %0, %1, %2;" : "=r"(r) : "r"(a), "r"(b)); return r; }
__device__ __forceinline__ uint32_t hadd2(uint32_t a, uint32_t b) { uint32_t r; asm("add.rn.bf16x2 %0, %1, %2;" : "=r"(r) : "r"(a), "r"(b)); return r; }
__device__ __forceinline__ uint32_t hfma2(uint32_t a, uint32_t b, uint32_t c) { uint32_t r; asm("fma.rn.bf16x2 %0, %1, %2, %3;" : "=r"(r) : "r"(a), "r"(b), "r"(c)); return r; }
__device__ __forceinline__ void mma16816(float (&c)[4], uint32_t a0, uint32_t a1, uint32_t a2, uint32_t a3, uint32_t b0, uint32_t b1) {
  asm volatile("mma.sync.aligned.m16n8k16.row.col.f32.bf16.bf16.f32 {%0,%1,%2,%3}, {%4,%5,%6,%7}, {%8,%9}, {%0,%1,%2,%3};"
               : "+f"(c[0]), "+f"(c[1]), "+f"(c[2]), "+f"(c[3]) : "r"(a0), "r"(a1), "r"(a2), "r"(a3), "r"(b0), "r"(b1));
}
__device__ __forceinline__ void mma1688(float (&c)[4], uint32_t a0, uint32_t a1, uint32_t b0) {
  asm volatile("mma.sync.aligned.m16n8k8.row.col.f32.bf16.bf16.f32 {%0,%1,%2,%3}, {%4,%5}, {%6}, {%0,%1,%2,%3};"
               : "+f"(c[0]), "+f"(c[1]), "+f"(c[2]), "+f"(c[3]) : "r"(a0), "r"(a1), "r"(b0));
}
__device__ __forceinline__ void ldsm4t(uint32_t (&r)[4], uint32_t a) {
  asm volatile("ldmatrix.sync.aligned.m8n8.x4.trans.shared.b16 {%0,%1,%2,%3}, [%4];" : "=r"(r[0]), "=r"(r[1]), "=r"(r[2]), "=r"(r[3]) : "r"(a) : "memory");
}
__device__ __forceinline__ void ldsm4(uint32_t (&r)[4], uint32_t a) {
  asm volatile("ldmatrix.sync.aligned.m8n8.x4.shared.b16 {%0,%1,%2,%3}, [%4];" : "=r"(r[0]), "=r"(r[1]), "=r"(r[2]), "=r"(r[3]) : "r"(a) : "memory");
}
__device__ __forceinline__ void ldsm2t(uint32_t (&r)[2], uint32_t a) {
  asm volatile("ldmatrix.sync.aligned.m8n8.x2.trans.shared.b16 {%0,%1}, [%2];" : "=r"(r[0]), "=r"(r[1]) : "r"(a) : "memory");
}
__device__ __forceinline__ float warp_sum(float v) {
#pragma unroll
  for (int o = 16; o; o >>= 1) v += __shfl_xor_sync(~0u, v, o);
  return v;
}
__device__ __forceinline__ void tma_load_2d(uint32_t dst, const CUtensorMap* map, uint32_t mbar, int c0, int c1) {
  asm volatile("cp.async.bulk.tensor.2d.shared::cluster.global.mbarrier::complete_tx::bytes [%0], [%1, {%3, %4}], [%2];"
               ::"r"(dst), "l"(map), "r"(mbar), "r"(c0), "r"(c1) : "memory");
}
__device__ __forceinline__ void tma_load_2d_mc(uint32_t dst, const CUtensorMap* map, uint32_t mbar, int c0, int c1) {
  asm volatile("cp.async.bulk.tensor.2d.shared::cluster.global.mbarrier::complete_tx::bytes.multicast::cluster [%0], [%1, {%3, %4}], [%2], %5;"
               ::"r"(dst), "l"(map), "r"(mbar), "r"(c0), "r"(c1), "h"((uint16_t)3) : "memory");
}
__device__ __forceinline__ uint64_t pol_first() {
  uint64_t p;
  asm("createpolicy.fractional.L2::evict_first.b64 %0, 1.0;" : "=l"(p));
  return p;
}
__device__ __forceinline__ void tma_load_2d_h(uint32_t dst, const CUtensorMap* map, uint32_t mbar, int c0, int c1, uint64_t pol) {
  asm volatile("cp.async.bulk.tensor.2d.shared::cluster.global.mbarrier::complete_tx::bytes.L2::cache_hint [%0], [%1, {%3, %4}], [%2], %5;"
               ::"r"(dst), "l"(map), "r"(mbar), "r"(c0), "r"(c1), "l"(pol) : "memory");
}
__device__ __forceinline__ void tma_load_2d_mc_h(uint32_t dst, const CUtensorMap* map, uint32_t mbar, int c0, int c1, uint64_t pol) {
  asm volatile("cp.async.bulk.tensor.2d.shared::cluster.global.mbarrier::complete_tx::bytes.multicast::cluster.L2::cache_hint [%0], [%1, {%3, %4}], [%2], %5, %6;"
               ::"r"(dst), "l"(map), "r"(mbar), "r"(c0), "r"(c1), "h"((uint16_t)3), "l"(pol) : "memory");
}
__device__ __forceinline__ void tma_load_3d(uint32_t dst, const CUtensorMap* map, uint32_t mbar, int c0, int c1, int c2) {
  asm volatile("cp.async.bulk.tensor.3d.shared::cluster.global.mbarrier::complete_tx::bytes [%0], [%1, {%3, %4, %5}], [%2];"
               ::"r"(dst), "l"(map), "r"(mbar), "r"(c0), "r"(c1), "r"(c2) : "memory");
}
__device__ __forceinline__ void tma_load_4d_h(uint32_t dst, const CUtensorMap* map, uint32_t mbar, int c0, int c1, int c2, int c3, uint64_t pol) {
  asm volatile("cp.async.bulk.tensor.4d.shared::cluster.global.mbarrier::complete_tx::bytes.L2::cache_hint [%0], [%1, {%3, %4, %5, %6}], [%2], %7;"
               ::"r"(dst), "l"(map), "r"(mbar), "r"(c0), "r"(c1), "r"(c2), "r"(c3), "l"(pol) : "memory");
}
__device__ __forceinline__ void tma_prefetch_2d(const CUtensorMap* map, int c0, int c1) {
  asm volatile("cp.async.bulk.prefetch.tensor.2d.L2.global.tile [%0, {%1, %2}];" ::"l"(map), "r"(c0), "r"(c1) : "memory");
}
__device__ __forceinline__ void bulk_prefetch(const void* p, uint32_t bytes) {
  asm volatile("cp.async.bulk.prefetch.L2.global [%0], %1;" ::"l"(p), "r"(bytes) : "memory");
}
__device__ __forceinline__ void bulk_load(uint32_t dst, const void* src, uint32_t bytes, uint32_t mbar) {
  asm volatile("cp.async.bulk.shared::cluster.global.mbarrier::complete_tx::bytes [%0], [%1], %2, [%3];"
               ::"r"(dst), "l"(src), "r"(bytes), "r"(mbar) : "memory");
}
__device__ __forceinline__ void wgmma_fence() { asm volatile("wgmma.fence.sync.aligned;" ::: "memory"); }
__device__ __forceinline__ void wgmma_commit() { asm volatile("wgmma.commit_group.sync.aligned;" ::: "memory"); }
template <int N> __device__ __forceinline__ void wgmma_wait() { asm volatile("wgmma.wait_group.sync.aligned %0;" ::"n"(N) : "memory"); }
__device__ __forceinline__ void fence_async() { asm volatile("fence.proxy.async.shared::cta;" ::: "memory"); }
__device__ __forceinline__ void bar_sync(int id, int n) { asm volatile("bar.sync %0, %1;" ::"r"(id), "r"(n) : "memory"); }
__device__ __forceinline__ void bar_arrive(int id, int n) { asm volatile("bar.arrive %0, %1;" ::"r"(id), "r"(n) : "memory"); }

constexpr uint32_t SM_BASE = 1024;
__host__ __device__ constexpr uint32_t mk_desc(uint32_t addr, uint32_t lbo_bytes) { return ((addr & 0x3FFFF) >> 4) | ((lbo_bytes >> 4) << 16); }

#define R32(d) \
  "+f"(d[0]), "+f"(d[1]), "+f"(d[2]), "+f"(d[3]), "+f"(d[4]), "+f"(d[5]), "+f"(d[6]), "+f"(d[7]), \
  "+f"(d[8]), "+f"(d[9]), "+f"(d[10]), "+f"(d[11]), "+f"(d[12]), "+f"(d[13]), "+f"(d[14]), "+f"(d[15]), \
  "+f"(d[16]), "+f"(d[17]), "+f"(d[18]), "+f"(d[19]), "+f"(d[20]), "+f"(d[21]), "+f"(d[22]), "+f"(d[23]), \
  "+f"(d[24]), "+f"(d[25]), "+f"(d[26]), "+f"(d[27]), "+f"(d[28]), "+f"(d[29]), "+f"(d[30]), "+f"(d[31])
#define R64(d) R32(d), \
  "+f"(d[32]), "+f"(d[33]), "+f"(d[34]), "+f"(d[35]), "+f"(d[36]), "+f"(d[37]), "+f"(d[38]), "+f"(d[39]), \
  "+f"(d[40]), "+f"(d[41]), "+f"(d[42]), "+f"(d[43]), "+f"(d[44]), "+f"(d[45]), "+f"(d[46]), "+f"(d[47]), \
  "+f"(d[48]), "+f"(d[49]), "+f"(d[50]), "+f"(d[51]), "+f"(d[52]), "+f"(d[53]), "+f"(d[54]), "+f"(d[55]), \
  "+f"(d[56]), "+f"(d[57]), "+f"(d[58]), "+f"(d[59]), "+f"(d[60]), "+f"(d[61]), "+f"(d[62]), "+f"(d[63])
#define S32 \
  "{%0,%1,%2,%3,%4,%5,%6,%7,%8,%9,%10,%11,%12,%13,%14,%15,%16,%17,%18,%19,%20,%21,%22,%23,%24,%25,%26,%27,%28,%29,%30,%31}"
#define S64 \
  "{%0,%1,%2,%3,%4,%5,%6,%7,%8,%9,%10,%11,%12,%13,%14,%15,%16,%17,%18,%19,%20,%21,%22,%23,%24,%25,%26,%27,%28,%29,%30,%31," \
  "%32,%33,%34,%35,%36,%37,%38,%39,%40,%41,%42,%43,%44,%45,%46,%47,%48,%49,%50,%51,%52,%53,%54,%55,%56,%57,%58,%59,%60,%61,%62,%63}"

template <int TB>
__device__ __forceinline__ void wgmma128_rs(float (&d)[64], uint32_t a0, uint32_t a1, uint32_t a2, uint32_t a3, uint32_t db, int scale_d) {
  asm volatile("{\n.reg .pred p;\n.reg .b64 q;\nsetp.ne.b32 p, %69, 0;\nmov.b64 q, {%68, 0x40000040};\n"
               "wgmma.mma_async.sync.aligned.m64n128k16.f32.bf16.bf16 " S64 ", {%64,%65,%66,%67}, q, p, 1, 1, %70;\n}\n"
               : R64(d) : "r"(a0), "r"(a1), "r"(a2), "r"(a3), "r"(db), "r"(scale_d), "n"(TB));
}
__device__ __forceinline__ void wgmma64_rs(float (&d)[32], uint32_t a0, uint32_t a1, uint32_t a2, uint32_t a3, uint32_t db, int scale_d) {
  asm volatile("{\n.reg .pred p;\n.reg .b64 q;\nsetp.ne.b32 p, %37, 0;\nmov.b64 q, {%36, 0x40000040};\n"
               "wgmma.mma_async.sync.aligned.m64n64k16.f32.bf16.bf16 " S32 ", {%32,%33,%34,%35}, q, p, 1, 1, 1;\n}\n"
               : R32(d) : "r"(a0), "r"(a1), "r"(a2), "r"(a3), "r"(db), "r"(scale_d));
}
__device__ __forceinline__ uint32_t pack_bf16(float a, float b) {
  uint32_t r;
  asm("cvt.rn.bf16x2.f32 %0, %1, %2;" : "=r"(r) : "f"(b), "f"(a));
  return r;
}
__device__ __forceinline__ float ex2(float x) { float y; asm("ex2.approx.ftz.f32 %0, %1;" : "=f"(y) : "f"(x)); return y; }
__device__ __forceinline__ float bfr(float x) { return __bfloat162float(__float2bfloat16(x)); }
__device__ __forceinline__ float bf_lo(uint32_t u) { return __uint_as_float(u << 16); }
__device__ __forceinline__ float bf_hi(uint32_t u) { return __uint_as_float(u & 0xffff0000u); }
__device__ __forceinline__ uint4 lds128(uint32_t a) {
  uint4 v;
  asm volatile("ld.shared.v4.b32 {%0,%1,%2,%3}, [%4];" : "=r"(v.x), "=r"(v.y), "=r"(v.z), "=r"(v.w) : "r"(a) : "memory");
  return v;
}
__device__ __forceinline__ void sts128(uint32_t a, uint4 v) {
  asm volatile("st.shared.v4.b32 [%0], {%1,%2,%3,%4};" ::"r"(a), "r"(v.x), "r"(v.y), "r"(v.z), "r"(v.w) : "memory");
}
__device__ __forceinline__ void red_add_v4(float4* p, float a, float b, float c, float d) {
  asm volatile("red.global.add.v4.f32 [%0], {%1,%2,%3,%4};" ::"l"(p), "f"(a), "f"(b), "f"(c), "f"(d) : "memory");
}
__device__ __forceinline__ float rcp(float x) { float y; asm("rcp.approx.ftz.f32 %0, %1;" : "=f"(y) : "f"(x)); return y; }
__device__ __forceinline__ float sqrt_a(float x) { float y; asm("sqrt.approx.ftz.f32 %0, %1;" : "=f"(y) : "f"(x)); return y; }
__device__ __forceinline__ float silu_bf(float v) { return bfr(v * rcp(1.f + __expf(-v))); }

constexpr int SM_STASH = 131072;
constexpr int QG = 73728;
constexpr int SM_STG = 210944;
constexpr int SM_XCH = 196608;
constexpr int SM_MISC = 229376;
constexpr int SM_TOTAL = 232448;
constexpr int B_FULLQ = 0, B_TB = 24, B_G2 = 32, B_G3 = 40, B_FULLA = 64, B_XR = 96, B_FULLO = 184, B_FFN = 160, B_FD = 168, B_MD = 176, B_X = 272,
              B_EMPTYQ = 280, B_G1 = 304, B_EMPTYO = 328, B_ST = 392,
              B_EMPTYA = 400, B_M = 432, B_XF = 144;
constexpr int SM_MOD = SM_MISC + 448;
constexpr int SM_FILL = SM_MISC + 512;
constexpr int SM_M2 = SM_MISC + 2560;
constexpr int SM_RED = SM_MISC + 2752;
constexpr int SM_ZERO = SM_MISC + 3040;
constexpr int SM_WG = 137216;
constexpr int SM_X2 = 65536;
constexpr int SM_WD = 84992;
constexpr int SM_T = 23040;
constexpr int T_H = 2816;
constexpr int SM_PS = SM_T + 5120;
constexpr int SM_OUT = SM_MISC - 16384;
constexpr int SM_MD = SM_STASH;

struct Params {
  const bf16 *x, *k, *c, *w_mod, *w_r, *wo, *v, *wq, *wg, *wu, *wd;
  bf16* out;
};

__global__ void __launch_bounds__(384, 1)
k_mega(const __grid_constant__ CUtensorMap mX, const __grid_constant__ CUtensorMap mWq,
       const __grid_constant__ CUtensorMap mK, const __grid_constant__ CUtensorMap mV,
       const __grid_constant__ CUtensorMap mWo, const __grid_constant__ CUtensorMap mWg,
       const __grid_constant__ CUtensorMap mWu, const __grid_constant__ CUtensorMap mWd, const Params prm) {
  extern __shared__ __align__(1024) uint8_t smem_raw[];
  const uint32_t sb = smem_u32(smem_raw);
  if ((sb & 0x3FFFF) != SM_BASE) __trap();
  const uint32_t sBar = sb + SM_MISC;
  const int tid = threadIdx.x;
  const int lane = get_lane();
  PSTAMP(0, 84);
  const int warp = __shfl_sync(~0u, tid >> 5, 0);
  const int b = blockIdx.x, rank = b & 1, qt = (b >> 1) & 15, kg = b >> 5, hg = kg * 2 + rank;
  const int hcol = (kg * 8 + rank) * DH;
  auto wq_prefetch = [&](int mask) {
    const bf16* wp = prm.wq + (size_t)(qt * 36 + ((tid - 128) >> 3)) * (HQ * DH) + hcol + ((tid & 6) * 2 + (tid & 1)) * 64;
    if ((mask >> (tid & 7)) & 1) {
      asm volatile("prefetch.global.L2 [%0];" ::"l"(wp));
      if (warp == 4) asm volatile("prefetch.global.L2 [%0];" ::"l"(wp + 32 * (HQ * DH)));
    }
  };
  if (warp >= 4) wq_prefetch(WQPF0);
  if (lane == 0 && warp >= 4) {
    if (MPF && warp < 10 && b < 96) bulk_prefetch(prm.w_mod + (size_t)(b * 6 + warp - 4) * (6 * DM), 2 * DM * 2);
    const int c0 = warp < 9 ? 1 : 8, c1 = warp < 11 ? c0 : 16, c2 = warp < 11 ? c0 : 3;
#pragma unroll
    for (int j = 0; j < 7; j++) mbar_init(sBar + (warp - 4) * 56 + j * 8, j == 0 ? c0 : j < 5 ? c1 : c2);
    *reinterpret_cast<uint4*>(smem_raw + SM_ZERO) = make_uint4(0u, 0u, 0u, 0u);
    asm volatile("fence.mbarrier_init.release.cluster;" ::: "memory");
  }
  __syncwarp();
  asm volatile("barrier.cluster.arrive.relaxed.aligned;" ::: "memory");
#define CL_WAIT() asm volatile("barrier.cluster.wait.acquire.aligned;" ::: "memory")
  const bool do_mod1 = warp >= 1 && warp < 4 && b < 72;
  if (warp < 4) {
    asm volatile("setmaxnreg.dec.sync.aligned.u32 40;");
    if (warp == 0) {
      PSTAMP(0, 85);
      CL_WAIT();
      PSTAMP(0, 86);
      if (lane == 0) {
        mbar_expect_tx(sBar + B_X, 9 * 16384);
#pragma unroll
        for (int i = 0; i < 5; i++)
          if (i < 4 || rank == 0) tma_load_2d_mc(sb + (2 * i + rank) * 16384, &mX, sBar + B_X, (2 * i + rank) * 64, qt * 128);
      }
    }
    PSTAMP(0, 87);
    if (do_mod1) {
      const int st = tid - 32;
      const uint32_t stg = sb + SM_STG + st * 16;
      {
        const bf16* wp = prm.w_mod + (size_t)(st >> 1) * (6 * DM) + b * 16 + (st & 1) * 8;
#pragma unroll
        for (int i = 0; i < 12; i++)
          asm volatile("cp.async.cg.shared.global [%0], [%1], 16;" ::"r"(stg + i * 1536), "l"(wp + (size_t)i * 48 * (6 * DM)) : "memory");
      }
      float* const sc = reinterpret_cast<float*>(smem_raw + SM_MOD);
#pragma unroll
      for (int i = 0; i < 3; i++) {
        const uint32_t v = __ldg(reinterpret_cast<const uint32_t*>(prm.c) + st + i * 96);
        *reinterpret_cast<float2*>(sc + (st + i * 96) * 2) = make_float2(silu_bf(bf_lo(v)), silu_bf(bf_hi(v)));
      }
      bar_sync(6, 96);
      PSTAMP(32, 88);
      asm volatile("cp.async.wait_all;" ::: "memory");
      PSTAMP(32, 93);
      float a[8];
#pragma unroll
      for (int i = 0; i < 8; i++) a[i] = 0.f;
#pragma unroll 3
      for (int i = 0; i < 12; i++) {
        const float sv = sc[(st >> 1) + 48 * i];
        const uint4 v = lds128(stg + i * 1536);
        a[0] += sv * bf_lo(v.x); a[1] += sv * bf_hi(v.x); a[2] += sv * bf_lo(v.y); a[3] += sv * bf_hi(v.y);
        a[4] += sv * bf_lo(v.z); a[5] += sv * bf_hi(v.z); a[6] += sv * bf_lo(v.w); a[7] += sv * bf_hi(v.w);
      }
      const bool u2 = lane & 2, u4 = lane & 4, u8 = lane & 8;
#pragma unroll
      for (int i = 0; i < 4; i++) { float snd = u2 ? a[i] : a[i + 4]; float kp = u2 ? a[i + 4] : a[i]; a[i] = kp + __shfl_xor_sync(~0u, snd, 2); }
#pragma unroll
      for (int i = 0; i < 2; i++) { float snd = u4 ? a[i] : a[i + 2]; float kp = u4 ? a[i + 2] : a[i]; a[i] = kp + __shfl_xor_sync(~0u, snd, 4); }
      { float snd = u8 ? a[0] : a[1]; float kp = u8 ? a[1] : a[0]; a[0] = kp + __shfl_xor_sync(~0u, snd, 8); }
      a[0] += __shfl_xor_sync(~0u, a[0], 16);
      float* const red = reinterpret_cast<float*>(smem_raw + SM_RED);
      if (lane < 16) red[(warp - 1) * 16 + (lane & 1) * 8 + (u2 ? 4 : 0) + (u4 ? 2 : 0) + (u8 ? 1 : 0)] = a[0];
      PSTAMP(32, 94);
      bar_sync(6, 96);
      PSTAMP(32, 95);
      if (st < 64) {
        const float* rp = red + (lane & 7) * 2;
        const float2 x = *reinterpret_cast<const float2*>(rp), y = *reinterpret_cast<const float2*>(rp + 16), z = *reinterpret_cast<const float2*>(rp + 32);
        uint32_t w = pack_bf16(x.x + y.x + z.x, x.y + y.y + z.y);
        if (b >= 36) w = hadd2(w, 0x3f803f80u);
        asm volatile("st.relaxed.gpu.global.u32 [%0], %1;" ::"l"(reinterpret_cast<uint32_t*>(g_mod1) + (st >> 3) * 576 + b * 8 + (lane & 7)), "r"(~w) : "memory");
      }
    }
    __syncwarp();
    PSTAMP(32, 89);
    if (warp > 0) {
      CL_WAIT();
      fence_async();
      if (tid < 104) {
        uint4 v, w;
        mbar_wait(sBar + B_X, 0);
        poll8(g_mod1 + (b & 7) * 144 + tid - 32, g_mod1 + (b & 7) * 144 + tid + 40, v, w);
        sts128(sb + SM_MOD + (tid - 32) * 32, make_uint4(~v.x, ~w.x, ~v.y, ~w.y));
        sts128(sb + SM_MOD + (tid - 32) * 32 + 16, make_uint4(~v.z, ~w.z, ~v.w, ~w.w));
      }
      __syncwarp();
      PSTAMP(32, 92);
      bar_arrive(3, 224);
      bar_arrive(4, 224);
      if (lane == 0) asm volatile("mbarrier.arrive.shared::cta.b64 _, [%0];" ::"r"(sBar + B_M) : "memory");
    }
    auto ffn_box = [&](int fb) {
      tma_load_2d(sb + (fb == 5 || fb == 6 ? -57600 : SM_WG) + fb * 11520, fb >= 4 ? &mWu : &mWg, sBar + B_FFN, (b * 36) & ~7, (fb & 3) * 144);
    };
    if (warp == 0) {
     if (lane == 0) {
      const uint64_t pol = pol_first();
      auto kv_load = [&](int t) {
        const int s = t & 3;
        mbar_wait(sBar + B_EMPTYA + s * 8, (t >> 2) & 1);
        mbar_expect_tx(sBar + B_FULLA + s * 8, 32768);
        if (EF & 1) tma_load_2d_mc_h(sb + s * 32768 + rank * 16384, (t & 1) ? &mV : &mK, sBar + B_FULLA + s * 8, rank * 64, kg * 4 * SK + (t >> 1) * 128, pol);
        else tma_load_2d_mc(sb + s * 32768 + rank * 16384, (t & 1) ? &mV : &mK, sBar + B_FULLA + s * 8, rank * 64, kg * 4 * SK + (t >> 1) * 128);
      };
#pragma unroll 1
      for (int i = 0, g = 1; i < 32; i++) {
        const int hh = (i >> 2) + 2;
        if (i == QTH) mbar_wait(sBar + B_M, 0);
        if (!(i & 3)) {
          mbar_wait(sBar + B_EMPTYQ + g * 8, i >= 12 && i < 24);
          mbar_expect_tx(sBar + B_FULLQ + g * 8, QG);
        }
        if (EF & 2) tma_load_2d_h(sb + g * QG + (i & 3) * 18432, &mWq, sBar + B_FULLQ + g * 8, hcol + (hh & 6) * 128 + (hh & 1) * 64, (i & 3) * 144, pol);
        else tma_load_2d(sb + g * QG + (i & 3) * 18432, &mWq, sBar + B_FULLQ + g * 8, hcol + (hh & 6) * 128 + (hh & 1) * 64, (i & 3) * 144);
        if ((i & 3) == 3 && ++g == 3) g = 0;
      }
#pragma unroll 1
      for (int u = 0; u < 128; u++) kv_load(u < 5 || u == 127 ? u : (u & 1) ? u + 1 : u - 1);
      mbar_wait(sBar + B_X, 1);
      {
        mbar_expect_tx(sBar + B_FFN, 2 * DM * 80);
        mbar_expect_tx(sBar + B_FD, 9 * 5120);
#pragma unroll 1
        for (int i = 0; i < 18; i++) {
          const int g = i & 3;
          mbar_wait(sBar + (i < 4 ? B_EMPTYA : B_EMPTYO) + g * 8, i >= 8 && !(i & 4));
          KSTAMP(270 + i);
          mbar_expect_tx(sBar + B_FULLO + g * 8, 32768);
          tma_load_4d_h(sb + g * 32768, &mWo, sBar + B_FULLO + g * 8, (i >> 1) * 64, 0, rank, kg * 4 + (i & 1) * 2, pol);
        }
        mbar_expect_tx(sBar + B_XR, 16 * 1152);
      }
     }
     __syncwarp();
     {
        const int lane = get_lane();
        mbar_wait(sBar + B_EMPTYO + 16, 1);
        if (lane < 16) bulk_load(sb + SM_X2 + lane * 1168, prm.x + (size_t)(qt * 128 + hg * 16 + lane) * DM, 1152, sBar + B_XR);
        __syncwarp();
        if (lane == 0) {
          mbar_wait(sBar + B_EMPTYO + 24, 1);
          if (LATEG & 4) mbar_wait(sBar + B_G1, 0);
          tma_load_3d(sb + SM_WD, &mWd, sBar + B_FD, 0, b * 36, 0);
          mbar_wait(sBar + B_EMPTYO, 0);
          if (LATEG & 2) mbar_wait(sBar + B_G1, 0);
          ffn_box(5); ffn_box(6);
        }
      }
    } else if (warp == 3) {
#pragma unroll 1
      for (int i = 0, g = 1; i < 8; i++) {
        mbar_wait(sBar + B_FULLQ + g * 8, i >= 3 && i < 6);
        if (++g == 3) g = 0;
        KSTAMP(170 + i * 2); bar_sync(1, 288); KSTAMP(171 + i * 2);
      }
      long long nxt = 0;
#pragma unroll 1
      for (int u = 0; u < 128; u++) {
        const int t = (u == 0 || u == 127) ? u : (u & 1) ? u + 1 : u - 1;
        mbar_wait(sBar + B_FULLA + (t & 3) * 8, (t >> 2) & 1);
        if (!(t & 3)) *reinterpret_cast<volatile uint32_t*>(smem_raw + SM_ZERO + 12) = t >> 2;
        if (!(t & 1) || t == 127) { KSTAMP((t + 1) & ~1);
          bar_sync(1, 288); KSTAMP(((t + 1) & ~1) + 1); }
        else { bar_sync(10, 160); }
      }
      if (lane < 2) mbar_expect_tx(sBar + B_XF + lane * 8, 8192);
#pragma unroll 1
      for (int i = 0; i < 18; i++) {
        mbar_wait(sBar + B_FULLO + (i & 3) * 8, (i >> 2) & 1);
        KSTAMP(190 + i);
        if ((i & 1) && i > 1 && i < 17) {
          const uint32_t xf = sBar + B_XF + ((i - 2) & 2) * 4;
          KSTAMP(260 + (i >> 1));
          mbar_wait(xf, ((i - 2) >> 2) & 1);
          __syncwarp();
          if (lane == 0) mbar_expect_tx(xf, 8192);
        }
        KSTAMP(130 + i * 2); bar_sync(1, 288); KSTAMP(131 + i * 2);
      }
    } else if (warp > 0) {
      const int st = tid - 32;
      mbar_wait(sBar + B_FULLQ + 8, 0);
      mbar_wait(sBar + B_FULLQ + 8, 1);
      const bf16* const kvp = (rank ? prm.v : prm.k) + ((size_t)kg * 4 * SK + qt * 128) * DH;
      if (st == 0) bulk_prefetch(kvp, 32768);
      mbar_wait(sBar + B_FULLA, 0);
      mbar_wait(sBar + B_FULLA, 1);
      if (warp == 1) {
#pragma unroll 1
        for (int grp = b < 72 ? b : 288; grp < 288; grp += 72) {
          float a[8];
#pragma unroll
          for (int i = 0; i < 8; i++) a[i] = 0.f;
#pragma unroll 2
          for (int r = lane; r < DM; r += 32) {
            uint4 v;
            if (EF & 16) asm("ld.global.nc.L2::cache_hint.v4.u32 {%0,%1,%2,%3}, [%4], %5;" : "=r"(v.x), "=r"(v.y), "=r"(v.z), "=r"(v.w) : "l"(prm.w_mod + (size_t)r * (6 * DM) + 2 * DM + grp * 8), "l"(pol_first()));
            else v = __ldg(reinterpret_cast<const uint4*>(prm.w_mod + (size_t)r * (6 * DM) + 2 * DM + grp * 8));
            float s = silu_bf(__bfloat162float(prm.c[r]));
            a[0] += s * bf_lo(v.x); a[1] += s * bf_hi(v.x); a[2] += s * bf_lo(v.y); a[3] += s * bf_hi(v.y);
            a[4] += s * bf_lo(v.z); a[5] += s * bf_hi(v.z); a[6] += s * bf_lo(v.w); a[7] += s * bf_hi(v.w);
          }
#pragma unroll
          for (int i = 0; i < 8; i++) a[i] = warp_sum(a[i]);
          if (lane == 0) {
            const int kind = grp / 72;
#pragma unroll
            for (int i = 0; i < 4; i++) {
              uint32_t w = pack_bf16(a[2 * i], a[2 * i + 1]);
              if (kind == 2) w = hadd2(w, 0x3f803f80u);
              reinterpret_cast<uint32_t*>(smem_raw + SM_M2)[i * 4 + kind] = w;
            }
            if (kind == 3) {
              fence_async();
              asm volatile("cp.async.bulk.global.shared::cta.bulk_group [%0], [%1], 64;" ::"l"(g_mod2 + b * 4), "r"(sb + SM_M2) : "memory");
              asm volatile("cp.async.bulk.commit_group;\ncp.async.bulk.wait_group 0;" ::: "memory");
              if (SIDEF & 1) asm volatile("fence.acq_rel.gpu;" ::: "memory");
              cnt_arrive(C_SIDE);
            }
          }
        }
        __syncwarp();
        bar_sync(8, 160);
        if (lane < 8) asm volatile("red.relaxed.gpu.global.add.u32 [%0], 1;" ::"l"(&g_cnt[(C_Q + qt * 8 + lane) * 32 + 1]) : "memory");
        PSTAMP(32, 56);
        const int lane = get_lane();
        PSTAMP(32, 57);
        cnt_wait1((C_Q + qt * 8 + hg) * 32 + 1, 8);
        PSTAMP(32, 59);
        if (lane == 0) mbar_arrive(sBar + B_G2);
        uint32_t k1 = ~0u, k2 = ~0u;
        uint4 hv[4];
        uint2 hw = make_uint2(0u, 0u);
        auto h_load = [&]() {
          const int r1 = k1 & (SQ - 1), r2 = k2 & (SQ - 1);
          const int r = lane < 16 ? r1 : r2;
          const int c = ((r >> 5) & 3) * 32 + (r >> 7) * 2 + ((r >> 4) & 1);
          const uint4* p = g_ones + F_HX + (c * 288 + (lane >= 16 && (r1 >> 4) == (r2 >> 4) ? 144 : 0) + (lane & 15));
#pragma unroll
          for (int i = 0; i < 4; i++) hv[i] = ldr4(p + i * 16);
          hw = ldr2(reinterpret_cast<const uint2*>(p + 64) - (lane & 15));
        };
#pragma unroll
        for (int i = 0; i < 4; i++) hv[i] = make_uint4(0u, 0u, 0u, 0u);
        const uint4* kp = g_ones + F_KEY + (b & 31) * 64 + lane * 2;
        auto merge = [](uint32_t& m1, uint32_t& m2, uint32_t n1, uint32_t n2) { m2 = min(max(m1, n1), min(m2, n2)); m1 = min(m1, n1); };
#pragma unroll 1
        for (uint32_t n = 0;; n++) {
          uint4 a, c;
          asm volatile("ld.relaxed.gpu.global.v4.u32 {%0,%1,%2,%3}, [%8];\nld.relaxed.gpu.global.v4.u32 {%4,%5,%6,%7}, [%8+16];"
                       : "=r"(a.x), "=r"(a.y), "=r"(a.z), "=r"(a.w), "=r"(c.x), "=r"(c.y), "=r"(c.z), "=r"(c.w) : "l"(kp) : "memory");
          const bool all = !__any_sync(~0u, unset(a) || unset(c));
          merge(a.x, a.y, a.z, a.w);
          merge(a.x, a.y, c.x, c.y);
          merge(a.x, a.y, c.z, c.w);
          const uint32_t m1 = __reduce_min_sync(~0u, a.x);
          const uint32_t m2 = __reduce_min_sync(~0u, a.x == m1 ? a.y : a.x);
          bool bad = m1 != k1 || m2 != k2 || hw.x == ~0u || hw.y == ~0u;
#pragma unroll
          for (int i = 0; i < 4; i++) bad |= unset(hv[i]);
          bad = __any_sync(~0u, bad);
          if (all && !bad) break;
          if (n > (1u << 15)) { SETERR(4); break; }
          if (bad) { k1 = m1; k2 = m2; h_load(); }
        }
        PSTAMP(32, 60);
        {
          const uint32_t ha = sb + SM_T + T_H + (lane >> 4) * 1152 + (lane & 15) * 16;
#pragma unroll
          for (int i = 0; i < 4; i++) sts128(ha + i * 256, hv[i]);
          asm volatile("st.shared.v2.b32 [%0], {%1,%2};" ::"r"(ha + 1024 - (lane & 15) * 8), "r"(hw.x), "r"(hw.y) : "memory");
        }
        if (lane == 0) asm volatile("st.shared.v2.b32 [%0], {%1,%2};" ::"r"(sb + SM_T + 128), "r"(~k1), "r"(~k2) : "memory");
        __syncwarp();
        if (lane == 0) mbar_arrive(sBar + B_G3);
        PSTAMP(32, 61);
      } else {
#pragma unroll
        for (int i = 0; i < 4; i++) sts128(sb + SM_FILL + i * 512 + lane * 16, make_uint4(~0u, ~0u, ~0u, ~0u));
        fence_async();
        __syncwarp();
        const int lane = get_lane();
        const uint32_t dump = sb + SM_RED + 64 + lane * 4;
        auto touch128 = [&](const void* q) { asm volatile("cp.async.ca.shared.global.L2::128B [%0], [%1], 4;" ::"r"(dump), "l"(q) : "memory"); };
        auto touch256 = [&](const void* q) { asm volatile("cp.async.ca.shared.global.L2::256B [%0], [%1], 4;" ::"r"(dump), "l"(q) : "memory"); };
#pragma unroll 1
        for (int p = 2; p < FILLP; p++) {
          if (*reinterpret_cast<volatile uint32_t*>(smem_raw + SM_ZERO + 12) < p) mbar_wait(sBar + B_FULLA, p & 1);
          if (lane == 0) {
            if ((p & 7) == 3 && p < 24) bulk_prefetch(kvp + (size_t)((p >> 3) + 1) * SK * DH, 32768);
            if (!(TCH & 2) && (p & 7) == QPF && p < 24) bulk_prefetch(g_q + ((size_t)b * 4 + (p >> 3) + 1) * 2048, 32768);
            if (!(TCH & 4) && p == FILLP - 1) bulk_prefetch(prm.x + (size_t)(qt * 128 + hg * 16) * DM, 16 * DM * 2);
            if (p == WOP) bulk_prefetch(prm.wo + ((size_t)kg * 1024 + (b & 31) * 32) * DM, 32 * DM * 2);
            if (p >= PF0 && p < PF0 + 9) {
              const int i = p - PF0, m = PFO ? 2 - i / 3 : i / 3;
              bulk_prefetch((m == 0 ? prm.wg : m == 1 ? prm.wu : prm.wd) + (size_t)(b * 3 + i % 3) * (DM * 12), DM * 24);
            }
          }
          __syncwarp();
          if ((TCH & 2) && (p & 7) == QPF && p < 24) {
#pragma unroll
            for (int i = 0; i < 4; i++) touch256(g_q + ((size_t)b * 4 + (p >> 3) + 1) * 2048 + (i * 32 + lane) * 16);
          }
          if ((TCH & 1) && p >= TF0 && p < TF0 + 9) {
            const int i = p - TF0, c0 = (b * 36) & ~7;
#pragma unroll
            for (int j = 0; j < (FAKEB ? 0 : 4); j++) {
              const int r = i * 64 + (j & 1) * 32 + lane;
              const bf16* q = ((j & 2) ? prm.wu : prm.wg) + (size_t)r * FF + c0;
              touch128(q);
              if ((c0 & 63) > 24) touch128(q + 38);
            }
            if (lane < 20) touch256(prm.wd + min(b * 162 + i * 20 + lane, 128 * 162 - 1) * 128);
          }
          if ((TCH & 16) && p >= TF0 && p < TF0 + 9 / TN) {
            const int i = (p - TF0) * TN, c0 = (b * 36) & ~7;
#pragma unroll
            for (int j = 0; j < TN; j++) {
              const bf16* q = prm.wu + (size_t)(144 + (i + j) * 32 + lane) * FF + c0;
              touch128(q);
              if ((c0 & 63) > 24) touch128(q + 38);
              if (lane < 20) touch256(prm.wd + min(b * 162 + (i + j) * 20 + lane, 128 * 162 - 1) * 128);
            }
          }
          if ((TCH & 4) && p >= FILLP - 3 && lane < 24) touch256(prm.x + (size_t)(qt * 128 + hg * 16) * DM + ((p - FILLP + 3) * 24 + lane) * 128);
          if ((TCH & 8) && p >= TW0 && p < TW0 + TWN) {
            const int i = (qt * TWN + p - TW0) * 144 % 2304;
#pragma unroll
            for (int j = 0; j < 5; j++)
              if (j < 4 || lane < 16) touch256(prm.wo + (size_t)(hcol + i / 576 * 256) * DM + (i % 576 + j * 32 + lane) * 128);
          }
          if (p >= FILL0)
#pragma unroll 1
          for (int z = 0; z < (FGAP ? FGN : 1); z++) {
            if (FGAP && z) __nanosleep(FGAP);
            const int i = lane >= 16 ? lane - 16 : (p - FILL0) * FILLN + lane + 5;
            if ((lane >= 16 ? p == FILLS && i < 5 : lane < FILLN && i < FILLMAX) && (!FGAP || (lane & (FGN - 1)) == z)) {
              uint4* const fp = g_ones + (i < 5 ? b * 640 : F_PART - 640 + b * 5120) + i * 128;
              if (EF & 32) asm volatile("cp.async.bulk.global.shared::cta.bulk_group.L2::cache_hint [%0], [%1], 2048, %2;" ::"l"(fp), "r"(sb + SM_FILL), "l"(pol_first()) : "memory");
              else asm volatile("cp.async.bulk.global.shared::cta.bulk_group [%0], [%1], 2048;" ::"l"(fp), "r"(sb + SM_FILL) : "memory");
            }
          }
        }
        asm volatile("cp.async.bulk.commit_group;\ncp.async.bulk.wait_group 0;" ::: "memory");
        if (SIDEF & 2) asm volatile("fence.acq_rel.gpu;" ::: "memory");
        __syncwarp();
        PSTAMP(64, 51);
        if (lane == 0) {
          cnt_arrive(C_SIDE);
          PSTAMP(64, 52);
          cnt_wait(C_SIDE, 128 + 72);
          PSTAMP(64, 53);
          asm volatile("mbarrier.arrive.shared::cta.b64 _, [%0];" ::"r"(sBar + B_X) : "memory");
        }
        __syncwarp();
        if (lane == 0) {
          asm volatile("prefetch.tensormap [%0];\nprefetch.tensormap [%1];\nprefetch.tensormap [%2];\nprefetch.tensormap [%3];" ::"l"(&mWo), "l"(&mWg), "l"(&mWu), "l"(&mWd) : "memory");
          mbar_wait(sBar + B_ST, 0);
          mbar_expect_tx(sBar + B_MD, 5760);
          bulk_load(sb + SM_MD, g_mod2, 4608, sBar + B_MD);
          bulk_load(sb + SM_MD + 4608, prm.w_r, 1152, sBar + B_MD);
        }
        __syncwarp();
        {
          mbar_wait(sBar + B_MD, 0);
          float sA = 0.f, sB = 0.f;
#pragma unroll 1
          for (int i = lane; i < 288; i += 32) {
            const uint4 m = lds128(sb + SM_MD + i * 16);
            const uint32_t w = *reinterpret_cast<const uint32_t*>(smem_raw + SM_MD + 4608 + i * 4);
            const float a0 = bf_lo(m.z) * bf_lo(w), a1 = bf_hi(m.z) * bf_hi(w);
            const uint32_t hi = pack_bf16(a0, a1);
            *reinterpret_cast<uint2*>(smem_raw + SM_MOD + i * 8) = make_uint2(pack_bf16(a0 - bf_lo(hi), a1 - bf_hi(hi)), hi);
            sA += a0 + a1;
            sB = fmaf(bf_lo(m.y), bf_lo(w), fmaf(bf_hi(m.y), bf_hi(w), sB));
          }
          sA = warp_sum(sA); sB = warp_sum(sB);
          *reinterpret_cast<float2*>(smem_raw + SM_ZERO + 16) = make_float2(sA, sB);
          __syncwarp();
          if (lane == 0) mbar_arrive(sBar + B_TB);
        }
        if (lane == 0) {
#pragma unroll 1
          for (int r = 0, fb = 0; r < 4; r++) {
#pragma unroll 1
            for (const int fe = (FFNS >> (r * 4)) & 15; fb < fe; fb++) ffn_box(fb == 5 ? 7 : fb);
            if (r < 3) mbar_wait(sBar + B_EMPTYO + 16, r & 1);
          }
        }
        __syncwarp();
        const uint32_t* const tsu = reinterpret_cast<const uint32_t*>(smem_raw + SM_T);
        const int row = qt * 128 + hg * 16 + lane;
        auto out_row = [&]() {
          asm volatile("cp.async.bulk.global.shared::cta.bulk_group [%0], [%1], 1152;" ::"l"(prm.out + (size_t)row * DM), "r"(sb + SM_X2 + lane * 1168) : "memory");
        };
        bar_sync(11, 288);
        fence_async();
        const bool top = (*(volatile const uint32_t*)(tsu + 34) >> lane) & 1;
        if (lane < 16 && !top) out_row();
        mbar_wait(sBar + B_G3, 0);
        if (top && row != (int)(~*(volatile const uint32_t*)(tsu + 32) & (SQ - 1)) && row != (int)(~*(volatile const uint32_t*)(tsu + 33) & (SQ - 1))) out_row();
        asm volatile("cp.async.bulk.commit_group;\ncp.async.bulk.wait_group.read 0;" ::: "memory");
      }
    }
  } else {
    const int cw = (warp >> 2) - 1;
    const int w8 = warp - 4;
    const int ct = tid - 128;
    const int lane = get_lane(), g = lane >> 2, t4 = lane & 3;
    uint32_t relBar;
    asm volatile("mapa.shared::cluster.u32 %0, %1, %2;" : "=r"(relBar) : "r"(sBar), "r"(rank ^ (lane & 1)));
    auto release = [&](int off) {
      if (lane < 2) mbar_arrive_cl(relBar + off);
    };
    auto release1 = [&](int off) {
      if (lane == 0) mbar_arrive_cl(relBar + off);
    };
    auto turn_begin = [&]() {
      asm volatile("{\n.reg .pred p;\nsetp.eq.b32 p, %0, 0;\n@p bar.sync 1, 288;\n@!p bar.sync 2, 256;\n}\n" ::"r"(cw) : "memory");
      wgmma_fence();
    };
    auto turn_end = [&]() { asm volatile("{\n.reg .pred p;\nsetp.eq.b32 p, %0, 0;\n@p bar.arrive 2, 256;\n@!p bar.arrive 1, 288;\n}\n" ::"r"(cw) : "memory"); };
    STAMP(0); GSTAMP(90);
    CL_WAIT();
    asm volatile("setmaxnreg.inc.sync.aligned.u32 232;");
    float S[64], O[64];
    uint32_t P[32], Qf[32];
    constexpr uint32_t dB_k = mk_desc(SM_BASE, 16);
    constexpr uint32_t dB_n16 = mk_desc(SM_BASE, 16384);
    uint4* const qpark = g_q + (size_t)b * (4 * 8 * 256) + ct;
    {
      uint32_t A[144];
      const uint32_t la = sb + (w8 * 16 + ((lane & 15) ^ (rank * 8))) * 128 + (((lane >> 4) ^ (lane & 7)) << 4);
      mbar_wait(sBar + B_X, 0);
      wq_prefetch(WQPF1);
      STAMP(1);
#pragma unroll
      for (int k = 0; k < 36; k++) {
        uint32_t a[4];
        ldsm4(a, (la ^ ((k & 3) << 5)) + (k >> 2) * 16384);
        A[k * 4] = a[0]; A[k * 4 + 1] = a[1]; A[k * 4 + 2] = a[2]; A[k * 4 + 3] = a[3];
      }
      const uint32_t one = 0x3f803f80u;
      float c[4][4];
#pragma unroll
      for (int i = 0; i < 16; i++) c[i >> 2][i & 3] = 0.f;
#pragma unroll
      for (int k = 0; k < 36; k++) mma16816(c[k & 3], A[k * 4], A[k * 4 + 1], A[k * 4 + 2], A[k * 4 + 3], one, one);
      if (lane < 3) mbar_arrive_cl(sBar + B_EMPTYQ + lane * 8);
      const float mA = ((c[0][0] + c[1][0]) + (c[2][0] + c[3][0])) * (1.f / DM), mB = ((c[0][2] + c[1][2]) + (c[2][2] + c[3][2])) * (1.f / DM);
      if (cw == 1) bar_sync(7, 256);
      uint32_t zero;
      asm volatile("ld.shared.b32 %0, [%1];" : "=r"(zero) : "r"(sb + SM_ZERO) : "memory");
      const uint32_t nA = pack_bf16(-mA, -mA) | zero, nB = pack_bf16(-mB, -mB) | zero;
      const float eA = mA + bf_lo(nA), eB = mB + bf_lo(nB);
#pragma unroll
      for (int i = 0; i < 16; i++) c[i >> 2][i & 3] = 0.f;
#pragma unroll
      for (int k = 0; k < 36; k++) {
        A[k * 4] = hadd2(A[k * 4], nA); A[k * 4 + 1] = hadd2(A[k * 4 + 1], nB); A[k * 4 + 2] = hadd2(A[k * 4 + 2], nA); A[k * 4 + 3] = hadd2(A[k * 4 + 3], nB);
        mma16816(c[k & 3], hmul2(A[k * 4], A[k * 4]), hmul2(A[k * 4 + 1], A[k * 4 + 1]), hmul2(A[k * 4 + 2], A[k * 4 + 2]), hmul2(A[k * 4 + 3], A[k * 4 + 3]), one, one);
      }
      const float vA = (c[0][0] + c[1][0]) + (c[2][0] + c[3][0]), vB = (c[0][2] + c[1][2]) + (c[2][2] + c[3][2]);
      const float rA = rsqrtf(fmaxf(vA * (1.f / DM) - eA * eA, 0.f) + 1e-5f), rB = rsqrtf(fmaxf(vB * (1.f / DM) - eB * eB, 0.f) + 1e-5f);
      const uint32_t hA = pack_bf16(rA, rA), hB = pack_bf16(rB, rB);
      const uint32_t lA = pack_bf16(rA - bf_lo(hA), rA - bf_lo(hA)), lB = pack_bf16(rB - bf_lo(hB), rB - bf_lo(hB));
      const uint32_t oA = pack_bf16(-eA * rA, -eA * rA), oB = pack_bf16(-eB * rB, -eB * rB);
#pragma unroll
      for (int i = 0; i < 144; i++) A[i] = hfma2(A[i], (i & 1) ? hB : hA, hfma2(A[i], (i & 1) ? lB : lA, (i & 1) ? oB : oA));
      asm volatile("st.shared.b32 [%0], %1;" ::"r"(sb + SM_ZERO + 4), "r"(A[143] ^ A[100]) : "memory");
      if (cw == 0) bar_arrive(7, 256);
      STAMP(2);
      bar_sync(3 + cw, 224);
      wq_prefetch(WQPF2);
      STAMP(3);
#pragma unroll
      for (int k = 0; k < 72; k++) {
        const uint2 m = *reinterpret_cast<const uint2*>(smem_raw + SM_MOD + (k * 4 + t4) * 8);
        A[k * 2] = hfma2(A[k * 2], m.y, m.x); A[k * 2 + 1] = hfma2(A[k * 2 + 1], m.y, m.x);
      }
      STAMP(4); GSTAMP(64);
      float qa[32];
      if (cw == 0) bar_arrive(1, 288);
#pragma unroll 1
      for (int hh = 2, gr = 1;; hh++) {
#pragma unroll
        for (int p = 0; p < 4; p++) {
          if (p == 0) turn_begin();
          const uint32_t db = dB_k + gr * (QG >> 4) + p * 1152;
#pragma unroll
          for (int kk = 0; kk < 9; kk++)
            wgmma64_rs(qa, A[p * 36 + kk * 4], A[p * 36 + kk * 4 + 1], A[p * 36 + kk * 4 + 2], A[p * 36 + kk * 4 + 3], db + kk * 128, (p | kk) != 0);
        }
        wgmma_commit();
        turn_end();
        wgmma_wait<0>();
        if (hh < 7) release1(B_EMPTYQ + gr * 8);
        else if (hh < 9) { release(B_EMPTYA + gr * 16); release(B_EMPTYA + gr * 16 + 8); }
        if (++gr == 3) gr = 0;
#pragma unroll
        for (int j = 0; j < 4; j++)
          qpark[((hh & 7) * 4 + j) * 256] = make_uint4(pack_bf16(qa[8 * j], qa[8 * j + 1]), pack_bf16(qa[8 * j + 2], qa[8 * j + 3]),
                                                       pack_bf16(qa[8 * j + 4], qa[8 * j + 5]), pack_bf16(qa[8 * j + 6], qa[8 * j + 7]));
        if (hh == 9) break;
      }
#pragma unroll
      for (int j = 0; j < 4; j++) {
        const uint4 v = __ldcg(qpark + j * 256);
        Qf[4 * j] = v.x; Qf[4 * j + 1] = v.y; Qf[4 * j + 2] = v.z; Qf[4 * j + 3] = v.w;
      }
#pragma unroll
      for (int j = 0; j < 16; j++) Qf[16 + j] = pack_bf16(qa[2 * j], qa[2 * j + 1]);
    }
    STAMP(5); GSTAMP(65);
    const float sc = 0.08838834764831845f * 1.4426950408889634f;
    float mb0 = 0.f, mb1 = 0.f, l0 = 0.f, l1 = 0.f;
    float i0 = 0.f, i1 = 0.f;
    auto o_scale = [&]() {
      float a0 = l0, a1 = l1;
      a0 += __shfl_xor_sync(~0u, a0, 1); a0 += __shfl_xor_sync(~0u, a0, 2);
      a1 += __shfl_xor_sync(~0u, a1, 1); a1 += __shfl_xor_sync(~0u, a1, 2);
      i0 = rcp(a0); i1 = rcp(a1);
    };
    auto o_frag = [&](int i) {
      return make_uint4(pack_bf16(O[i * 8] * i0, O[i * 8 + 1] * i0), pack_bf16(O[i * 8 + 2] * i1, O[i * 8 + 3] * i1),
                        pack_bf16(O[i * 8 + 4] * i0, O[i * 8 + 5] * i0), pack_bf16(O[i * 8 + 6] * i1, O[i * 8 + 7] * i1));
    };
    auto row_max = [&](float& x0, float& x1) {
      float y0 = fmaxf(S[0], S[1]), y1 = fmaxf(S[2], S[3]), z0 = fmaxf(S[4], S[5]), z1 = fmaxf(S[6], S[7]);
#pragma unroll
      for (int j = 2; j < 16; j += 2) {
        y0 = fmaxf(y0, fmaxf(S[j * 4], S[j * 4 + 1])); y1 = fmaxf(y1, fmaxf(S[j * 4 + 2], S[j * 4 + 3]));
        z0 = fmaxf(z0, fmaxf(S[j * 4 + 4], S[j * 4 + 5])); z1 = fmaxf(z1, fmaxf(S[j * 4 + 6], S[j * 4 + 7]));
      }
      x0 = fmaxf(y0, z0); x1 = fmaxf(y1, z1);
      x0 = fmaxf(x0, __shfl_xor_sync(~0u, x0, 1)); x1 = fmaxf(x1, __shfl_xor_sync(~0u, x1, 1));
      x0 = fmaxf(x0, __shfl_xor_sync(~0u, x0, 2)); x1 = fmaxf(x1, __shfl_xor_sync(~0u, x1, 2));
    };
    float s0, s1;
    auto exps = [&](int j0, int j1) {
#pragma unroll
      for (int j = j0; j < j1; j++) {
        S[j * 4] = ex2(fmaf(S[j * 4], sc, -mb0)); S[j * 4 + 1] = ex2(fmaf(S[j * 4 + 1], sc, -mb0));
        S[j * 4 + 2] = ex2(fmaf(S[j * 4 + 2], sc, -mb1)); S[j * 4 + 3] = ex2(fmaf(S[j * 4 + 3], sc, -mb1));
        s0 += S[j * 4] + S[j * 4 + 1]; s1 += S[j * 4 + 2] + S[j * 4 + 3];
      }
    };
    auto cvtP = [&]() {
#pragma unroll
      for (int i = 0; i < 32; i++) P[i] = pack_bf16(S[2 * i], S[2 * i + 1]);
    };
    auto issue_qk = [&](uint32_t db) {
#pragma unroll
      for (int kk = 0; kk < 8; kk++)
        wgmma128_rs<0>(S, Qf[kk * 4], Qf[kk * 4 + 1], Qf[kk * 4 + 2], Qf[kk * 4 + 3], db + (kk >> 2) * 1024 + (kk & 3) * 2, kk != 0);
    };
    auto issue_pv = [&](uint32_t db, int first) {
#pragma unroll
      for (int kk = 0; kk < 8; kk++) {
        if (kk == TE_POS) turn_end();
        wgmma128_rs<1>(O, P[kk * 4], P[kk * 4 + 1], P[kk * 4 + 2], P[kk * 4 + 3], db + kk * 128, kk ? 1 : !first);
      }
      wgmma_commit();
      if (TE_POS == 8) turn_end();
    };
    auto sched_fence = [&]() {
      asm volatile("st.shared.v2.f32 [%0], {%1,%2};" ::"r"(sb + SM_RED), "f"(s0), "f"(s1) : "memory");
    };
    {
      STAMP(6);
      turn_begin();
      issue_qk(dB_k);
      wgmma_commit();
      turn_end();
      wgmma_wait<0>();
      release(B_EMPTYA);
      s0 = 0.f; s1 = 0.f;
      float x0, x1;
      row_max(x0, x1);
      mb0 = x0 * sc; mb1 = x1 * sc;
      exps(0, 16);
      cvtP();
      l0 = s0; l1 = s1;
    }
    const uint4* qn = qpark + 8 * 256;
    asm volatile("" : "+l"(qn));
    uint32_t kd = dB_k + 4096;
#pragma unroll 1
    for (int t = 1; t < 64; t++, kd ^= 4096) {
      const int j = t & 15, h = t >> 4;
      const int ks = (t & 1) * 2, vs = 3 - ks;
      turn_begin();
      issue_qk(kd);
      wgmma_commit();
      if (__builtin_expect(j == 1 && h, 0)) {
#pragma unroll
        for (int i = 0; i < 8; i++) sts128(sb + SM_STASH + (h - 1) * 32768 + i * 4096 + ct * 16, o_frag(i));
        wgmma_fence();
      }
      if (cw == 0) bar_sync(10, 160);
      issue_pv(kd ^ (dB_k ^ (dB_n16 + 6144)), j == 1);
      wgmma_wait<1>();
      release(B_EMPTYA + ks * 8);
      if (j == 15 && h < 3) {
#pragma unroll
        for (int i = 0; i < 8; i++) {
          uint4 v;
          if (EF & 4) asm volatile("ld.global.cg.L2::cache_hint.v4.u32 {%0,%1,%2,%3}, [%4], %5;" : "=r"(v.x), "=r"(v.y), "=r"(v.z), "=r"(v.w) : "l"(qn + i * 256), "l"(pol_first()));
          else v = __ldcg(qn + i * 256);
          Qf[4 * i] = v.x; Qf[4 * i + 1] = v.y; Qf[4 * i + 2] = v.z; Qf[4 * i + 3] = v.w;
        }
        qn += 8 * 256;
      }
      s0 = 0.f; s1 = 0.f;
      exps(0, 8);
      sched_fence();
      wgmma_wait<0>();
      release(B_EMPTYA + vs * 8);
      float lo = 0.f;
      if (__builtin_expect(j == 0, 0)) {
        o_scale();
        l0 = 0.f; l1 = 0.f;
        lo = LAZY_LOW;
      }
      bool bad = __any_sync(~0u, !(s0 <= LAZY_LIMIT && s1 <= LAZY_LIMIT));
      if (__builtin_expect(!bad, 1)) {
        exps(8, 16);
        cvtP();
        bad = __any_sync(~0u, !(s0 <= LAZY_LIMIT && s1 <= LAZY_LIMIT && s0 >= lo && s1 >= lo));
      }
      if (__builtin_expect(bad, 0)) {
        const uint32_t* kp = reinterpret_cast<const uint32_t*>(prm.k + ((size_t)kg * 4 * SK + t * 128 + g) * DH) + t4;
        const uint4* qp = qpark + h * (8 * 256);
        float4 tmp[16];
        uint4 qf[8];
#pragma unroll
        for (int kk = 0; kk < 8; kk++) qf[kk] = __ldcg(qp + kk * 256);
#pragma unroll 1
        for (int jn = 0; jn < 16; jn++) {
          float c[4] = {0.f, 0.f, 0.f, 0.f};
#pragma unroll
          for (int kk = 0; kk < 8; kk++) mma16816(c, qf[kk].x, qf[kk].y, qf[kk].z, qf[kk].w, __ldg(kp + jn * 512 + kk * 8), __ldg(kp + jn * 512 + kk * 8 + 4));
          tmp[jn] = make_float4(c[0], c[1], c[2], c[3]);
        }
#pragma unroll
        for (int jn = 0; jn < 16; jn++) { const float4 c = tmp[jn]; S[jn * 4] = c.x; S[jn * 4 + 1] = c.y; S[jn * 4 + 2] = c.z; S[jn * 4 + 3] = c.w; }
        float x0, x1;
        row_max(x0, x1);
        const float n0 = j ? fmaxf(mb0, x0 * sc) : x0 * sc, n1 = j ? fmaxf(mb1, x1 * sc) : x1 * sc;
        const float f0 = j ? ex2(mb0 - n0) : 1.f, f1 = j ? ex2(mb1 - n1) : 1.f;
        mb0 = n0; mb1 = n1;
        l0 *= f0; l1 *= f1;
#pragma unroll
        for (int i = 0; i < 16; i++) { O[i * 4] *= f0; O[i * 4 + 1] *= f0; O[i * 4 + 2] *= f1; O[i * 4 + 3] *= f1; }
        s0 = 0.f; s1 = 0.f;
        exps(0, 16);
        cvtP();
      }
      l0 += s0; l1 += s1;
    }
    STAMP(70); GSTAMP(66);
    turn_begin();
    issue_pv(dB_n16 + 6144, 0);
    int nc = 0;
    uint32_t ra[7], rb[7], ld[16];
    const uint32_t* const ap = reinterpret_cast<const uint32_t*>(g_ones + F_PART) + (qt * 8 + hg) * 20480 + w8 * 32 + get_lane();
    auto ld_sum = [&](uint32_t& a, uint32_t& c, const uint32_t* w) {
      a = pack_bf16((bf_lo(w[0]) + bf_lo(w[2])) + (bf_lo(w[4]) + bf_lo(w[6])), (bf_hi(w[0]) + bf_hi(w[2])) + (bf_hi(w[4]) + bf_hi(w[6])));
      c = pack_bf16((bf_lo(w[1]) + bf_lo(w[3])) + (bf_lo(w[5]) + bf_lo(w[7])), (bf_hi(w[1]) + bf_hi(w[3])) + (bf_hi(w[5]) + bf_hi(w[7])));
    };
    {
      const int lane = get_lane();
      uint32_t A[128];
#pragma unroll
      for (int i = 0; i < 16; i++) {
        const uint4 v = lds128(sb + SM_STASH + i * 4096 + ct * 16);
        A[i * 4] = v.x; A[i * 4 + 1] = v.y; A[i * 4 + 2] = v.z; A[i * 4 + 3] = v.w;
      }
      o_scale();
      wgmma_wait<0>();
#pragma unroll
      for (int i = 16; i < 24; i++) {
        const uint4 v = lds128(sb + SM_STASH + i * 4096 + ct * 16);
        A[i * 4] = v.x; A[i * 4 + 1] = v.y; A[i * 4 + 2] = v.z; A[i * 4 + 3] = v.w;
      }
#pragma unroll
      for (int i = 0; i < 8; i++) {
        const uint4 v = o_frag(i);
        A[96 + i * 4] = v.x; A[96 + i * 4 + 1] = v.y; A[96 + i * 4 + 2] = v.z; A[96 + i * 4 + 3] = v.w;
      }
      if (__any_sync(~0u, A[95] != 0x12345678u || A[64] != 0x9abcdef0u || lane == 0)) {
        release(B_EMPTYA + 24);
        release1(B_ST);
      }
      STAMP(71);
      uint32_t xb = w8 * 1024 + lane * 16;
      const uint32_t peer = __shfl_sync(~0u, relBar, 1) - sBar;
      float c0[32], kp[16];
      int gr = 0;
#pragma unroll
      for (int i = 0; i < 8; i++) ld[i] = ~0u;
#pragma unroll
      for (int i = 0; i < 5; i++) ra[i] = rb[i] = 0;
      auto ld_take = [&]() {
        uint32_t a, d;
        ld_sum(a, d, ld);
#pragma unroll
        for (int i = 0; i < 5; i++)
          if (nc == i) { ra[i] = a; rb[i] = d; }
        nc += !__any_sync(~0u, nan2(hadd2(a, d)));
      };
      uint32_t* dp = reinterpret_cast<uint32_t*>(g_ones + F_PART) + (qt * 8 + w8) * 20480 + kg * 512 + rank * 256 + lane;
      auto recv = [&]() {
        uint4 u[2];
#pragma unroll
        for (int j = 0; j < 2; j++) u[j] = lds128(sb + SM_XCH + xb + j * 512);
#pragma unroll
        for (int j = 0; j < 2; j++) {
          str1(dp + j * 128, pack_bf16(kp[j * 8] + bf_lo(u[j].x), kp[j * 8 + 1] + bf_hi(u[j].x)));
          str1(dp + j * 128 + 32, pack_bf16(kp[j * 8 + 2] + bf_lo(u[j].y), kp[j * 8 + 3] + bf_hi(u[j].y)));
          str1(dp + j * 128 + 64, pack_bf16(kp[j * 8 + 4] + bf_lo(u[j].z), kp[j * 8 + 5] + bf_hi(u[j].z)));
          str1(dp + j * 128 + 96, pack_bf16(kp[j * 8 + 6] + bf_lo(u[j].w), kp[j * 8 + 7] + bf_hi(u[j].w)));
        }
        dp += 2048;
        xb ^= 8192;
      };
#pragma unroll 1
      for (int c = 0;; c++) {
#pragma unroll
        for (int hd = 0; hd < 4; hd++) {
          if (!(hd & 1)) turn_begin();
          const uint32_t db = dB_k + (gr + (hd & 1)) * 1024;
#pragma unroll
          for (int kk = 0; kk < 8; kk++)
            wgmma64_rs(c0, A[hd * 32 + kk * 4], A[hd * 32 + kk * 4 + 1], A[hd * 32 + kk * 4 + 2], A[hd * 32 + kk * 4 + 3], db + kk * 128, (hd | kk) != 0);
          if (hd & 1) {
            wgmma_commit();
            if (hd == 1 || c < 8 || cw == 0) turn_end();
            if (hd == 1 ? c == 8 : (c & 7) != 0) {
              if (hd == 1) mbar_wait(sBar + B_XF + 8, 1);
              recv();
            }
            if (hd == 1 && c >= 3 && c < 8) {
              ld_take();
#pragma unroll
              for (int i = 0; i < 8; i++) ld[i] = ldr1(ap + nc * 2048 + i * 256);
            }
            if (hd == HINTH && c == 8 && cw == HINTW) bar_arrive(8, 160);
            if (hd == 3 && c == 8) {
              ld_take();
#pragma unroll
              for (int i = 0; i < 16; i++) ld[i] = ldr1(ap + 5 * 2048 + i * 256);
            }
            wgmma_wait<0>();
            release1(B_EMPTYO + gr * 4);
            gr = (gr + 2) & 7;
          }
        }
        if (c == 8) break;
        if (c == 0) mbar_wait(sBar + B_EMPTYA + 24, 0);
#pragma unroll
        for (int j = 0; j < 2; j++)
          asm volatile("st.async.shared::cluster.mbarrier::complete_tx::bytes.v4.b32 [%0], {%1,%2,%3,%4}, [%5];" ::"r"(sb + SM_XCH + xb + peer + j * 512),
                       "r"(pack_bf16(c0[j * 16 + 2], c0[j * 16 + 3])), "r"(pack_bf16(c0[j * 16 + 6], c0[j * 16 + 7])), "r"(pack_bf16(c0[j * 16 + 10], c0[j * 16 + 11])),
                       "r"(pack_bf16(c0[j * 16 + 14], c0[j * 16 + 15])), "r"(sBar + B_XF + (c & 1) * 8 + peer) : "memory");
#pragma unroll
        for (int j = 0; j < 16; j++) kp[j] = c0[(j >> 1) * 4 + (j & 1)];
      }
      STAMP(72); GSTAMP(67);
      uint2* const dst = reinterpret_cast<uint2*>(g_ones + F_PART) + ((qt * 8 + w8) * 40 + 32 + rank * 4 + kg) * 256 + lane;
#pragma unroll
      for (int jb = 0; jb < 8; jb++)
        asm volatile("st.relaxed.gpu.global.v2.u32 [%0], {%1,%2};" ::"l"(dst + jb * 32), "r"(pack_bf16(c0[jb * 4], c0[jb * 4 + 1])), "r"(pack_bf16(c0[jb * 4 + 2], c0[jb * 4 + 3])) : "memory");
    }
    STAMP(73);
    {
    const int lane = get_lane(), g = lane >> 2, t4 = lane & 3;
    uint32_t* const tsu = reinterpret_cast<uint32_t*>(smem_raw + SM_T);
    float* const tsf = reinterpret_cast<float*>(smem_raw + SM_T);
    const int row0 = qt * 128 + hg * 16;
    const int kq = w8 >> 1;
    uint32_t bg[9][10], bd[9][5];
    auto ld_bg = [&]() {
      mbar_wait(sBar + B_FFN, 0);
      const uint32_t wa = sb + (w8 == 3 || w8 == 5 ? -11520 : (w8 & 1) ? SM_WG + 46080 : SM_WG) + (kq * 144 + (lane & 15)) * 80 + (lane >> 4) * 16;
#pragma unroll
      for (int ks = 0; ks < 9; ks++) {
        uint32_t b0[4], b1[4], b2[2];
        ldsm4t(b0, wa + ks * 1280); ldsm4t(b1, wa + ks * 1280 + 32); ldsm2t(b2, wa + ks * 1280 + 64 - (lane >> 4) * 16);
#pragma unroll
        for (int i = 0; i < 4; i++) { bg[ks][i] = b0[i]; bg[ks][4 + i] = b1[i]; }
        bg[ks][8] = b2[0]; bg[ks][9] = b2[1];
      }
    };
    {
      uint32_t xa[9], xb[9], wb[9];
      uint4 md[9];
      float av[2][4];
      uint2 pv[12];
      const uint32_t ident = (g >> 1) == t4 ? 0x3f80u << ((g & 1) * 16) : 0u;
      auto ld_late = [&]() {
        bool bad = false;
#pragma unroll
        for (int s = 0; s < 12; s++)
          if (pv[s].x == ~0u || pv[s].y == ~0u) {
            bad = true;
            if (s < 4) { pv[s].x = ldr1(ap + (28 + s) * 512); pv[s].y = ldr1(ap + (28 + s) * 512 + 256); }
            else pv[s] = ldr2(ap + (28 + s) * 512 + w8 * 32 + lane);
          }
        return bad;
      };
#pragma unroll
      for (int s = 0; s < 12; s++) pv[s] = make_uint2(~0u, ~0u);
      uint32_t* const tr = reinterpret_cast<uint32_t*>(smem_raw + SM_X2) + g * 292 + w8 * 4 + t4;
      float sx[4] = {0.f, 0.f, 0.f, 0.f}, qa[4] = {0.f, 0.f, 0.f, 0.f}, qb[4] = {0.f, 0.f, 0.f, 0.f};
      auto stat = [&](int i, uint32_t a, uint32_t c) {
        xa[i] = hfma2(md[i].x, a, xa[i]);
        xb[i] = hfma2(md[i].x, c, xb[i]);
        mma1688(sx, xa[i], xb[i], wb[i]);
        mma1688(qa, xa[i], xb[i], xa[i]);
        mma1688(qb, xa[i], xb[i], xb[i]);
      };
      mbar_wait(sBar + B_TB, 0);
#pragma unroll
      for (int i = 0; i < 9; i++) {
        md[i] = lds128(sb + SM_MD + (i * 32 + w8 * 4 + t4) * 16);
        const uint32_t w = *reinterpret_cast<const uint32_t*>(smem_raw + SM_MOD + (i * 32 + w8 * 4 + t4) * 8 + (g & 1) * 4);
        wb[i] = g == 0 ? 0x3f803f80u : g < 3 ? w : 0u;
      }
      mbar_wait(sBar + B_XR, 0);
#pragma unroll
      for (int i = 0; i < 9; i++) { xa[i] = tr[i * 32]; xb[i] = tr[8 * 292 + i * 32]; }
      mbar_wait(sBar + B_EMPTYO, 0);
      STAMP(74);
      ld_sum(ra[5], rb[5], ld);
      ld_sum(ra[6], rb[6], ld + 8);
      {
        if (__builtin_expect(__any_sync(~0u, nc < 5 || nan2(hadd2(hadd2(ra[5], rb[5]), hadd2(ra[6], rb[6])))), 0)) {
          uint32_t w[56];
#pragma unroll
          for (int i = 0; i < 56; i++) w[i] = i >= 40 ? ld[i - 40] : (i >> 3) >= nc ? ~0u : 0u;
#pragma unroll 1
          for (uint32_t n = 0;; n++) {
            bool bad = false;
#pragma unroll
            for (int i = 0; i < 56; i++)
              if (w[i] == ~0u) { bad = true; w[i] = ldr1(ap + i * 256); }
            if (!__any_sync(~0u, bad) || n > (1u << 15)) break;
            if (FIXS) __nanosleep(FIXS);
          }
#pragma unroll
          for (int i = 0; i < 7; i++) {
            uint32_t a, d;
            ld_sum(a, d, w + i * 8);
            if (i >= nc) { ra[i] = a; rb[i] = d; }
          }
        }
      }
      STAMP(69);
      mbar_wait(sBar + B_G2, 0);
      STAMP(48);
#pragma unroll 1
      for (uint32_t n = 0;; n++) {
        const bool bad = ld_late();
        if (!__any_sync(~0u, bad) || n > (1u << 15)) break;
        if (n == 0) {
#pragma unroll
          for (int i = 0; i < 7; i++) stat(i, ra[i], rb[i]);
          if (BGE) ld_bg();
        }
      }
      STAMP(77);
      if (lane == 0) mbar_arrive(sBar + B_G1);
#pragma unroll
      for (int i = 0; i < 8; i++) av[i >> 2][i & 3] = 0.f;
#pragma unroll
      for (int s = 0; s < 4; s++) {
        if (s & 1) mma16816(av[0], pv[s - 1].x, pv[s - 1].y, pv[s].x, pv[s].y, ident, ident);
        mma16816(av[1], pv[4 + s].x, pv[4 + s].y, pv[8 + s].y, pv[8 + s].x, ident, ident);
      }
#pragma unroll
      for (int i = 0; i < 2; i++) stat(7 + i, pack_bf16(av[i][0], av[i][1]), pack_bf16(av[i][2], av[i][3]));
      STAMP(40);
      float* const ps = reinterpret_cast<float*>(smem_raw + SM_PS);
      if (t4 < 2) {
        *reinterpret_cast<float2*>(ps + w8 * 32 + g * 4 + t4 * 2) = make_float2(sx[0], sx[1]);
        *reinterpret_cast<float2*>(ps + 256 + w8 * 32 + g * 4 + t4 * 2) = make_float2(sx[2], sx[3]);
      }
      if (ident) {
        ps[512 + w8 * 32 + g] = (g & 1) ? qa[1] : qa[0];
        ps[512 + w8 * 32 + g + 8] = (g & 1) ? qb[3] : qb[2];
      }
      bar_sync(5, 256);
      STAMP(44);
      float mean = 0.f, dot = 0.f, m2 = 0.f;
#pragma unroll
      for (int i = 0; i < 4; i++) {
        const float4 q = *reinterpret_cast<const float4*>(ps + (lane & 8) * 32 + (lane & 16) * 8 + i * 32 + (lane & 7) * 4);
        mean += q.x; dot += q.y + q.z; m2 += ps[512 + (lane & 16) * 8 + i * 32 + (lane & 15)];
      }
      const float2 sab = *reinterpret_cast<const float2*>(smem_raw + SM_ZERO + 16);
      mean += __shfl_xor_sync(~0u, mean, 16);
      dot += __shfl_xor_sync(~0u, dot, 16);
      m2 += __shfl_xor_sync(~0u, m2, 16);
      mean *= 1.f / DM;
      const float rs = rcp(bfr(sqrt_a(bfr(bfr(fmaxf(fmaf(m2, 1.f / DM, -mean * mean), 0.f)) + 1e-5f))));
      const uint32_t nm = pack_bf16(-mean, -mean);
      uint32_t u = pack_bf16(0.f, fmaf(rs, fmaf(bf_lo(nm), sab.x, dot), sab.y));
      u = ((u & 0x7fff0000u) > 0x7f800000u) ? 0u : (u ^ ((u >> 31) ? 0xffff0000u : 0x80000000u));
      u |= 0xffffu - (row0 + (lane & 15));
      const uint32_t m1 = __reduce_max_sync(~0u, u), m2k = __reduce_max_sync(~0u, u == m1 ? 0u : u);
      if (w8 == 7) asm volatile("st.relaxed.gpu.global.v2.u32 [%0], {%1,%2};" ::"l"(reinterpret_cast<uint2*>(g_ones + F_KEY) + lane * 128 + b), "r"(~m1), "r"(~m2k) : "memory");
      STAMP(41);
      const int r1 = ~m1 & 15, r2 = ~m2k & 15;
      const uint32_t r2t = pack_bf16(rs, rs - bfr(rs));
      const uint32_t rA = __shfl_sync(~0u, r2t, g), rB = __shfl_sync(~0u, r2t, g + 8);
      const uint32_t nmA = __shfl_sync(~0u, nm, g), nmB = __shfl_sync(~0u, nm, g + 8);
      const uint32_t hA = __byte_perm(rA, 0, 0x1010), lA = __byte_perm(rA, 0, 0x3232), hB = __byte_perm(rB, 0, 0x1010), lB = __byte_perm(rB, 0, 0x3232);
      uint32_t* const hx = reinterpret_cast<uint32_t*>(g_ones + F_HX + b * 288) + w8 * 4 + t4;
      const bool topA = g == r1 || g == r2, topB = g + 8 == r1 || g + 8 == r2;
      uint32_t* const pA = hx + (g == r2 ? 576 : 0);
      uint32_t* const pB = hx + (g + 8 == r2 ? 576 : 0);
#pragma unroll
      for (int i = 0; i < 9; i++) {
        const uint32_t da = hadd2(xa[i], nmA), db = hadd2(xb[i], nmB);
        const uint32_t ha = hfma2(hfma2(da, hA, hmul2(da, lA)), md[i].z, md[i].y), hb = hfma2(hfma2(db, hB, hmul2(db, lB)), md[i].z, md[i].y);
        if (topA) str1(pA + i * 32, ha);
        if (topB) str1(pB + i * 32, hb);
        tr[i * 32] = hfma2(md[i].w, ha, xa[i]);
        tr[8 * 292 + i * 32] = hfma2(md[i].w, hb, xb[i]);
      }
#pragma unroll
      for (int i = 0; i < 9; i++) {
        if (topA) str1(pA + 288 + i * 32, xa[i]);
        if (topB) str1(pB + 288 + i * 32, xb[i]);
      }
      if (tid == 128) tsu[34] = (1u << r1) | (1u << r2);
      bar_arrive(11, 288);
    }
    STAMP(75);
    if (!BGE) ld_bg();
    mbar_wait(sBar + B_FD, 0);
    STAMP(42);
    {
      const uint32_t a = sb + SM_WD + lane * 128 + (((w8 ^ lane) & 7) << 4);
#pragma unroll
      for (int i = 0; i < 9; i++) {
        uint32_t b0[4];
        ldsm4t(b0, a + i * 5120);
        asm volatile("ldmatrix.sync.aligned.m8n8.x1.trans.shared.b16 {%0}, [%1];" : "=r"(bd[i][4]) : "r"(a + i * 5120 + 4096) : "memory");
#pragma unroll
        for (int j = 0; j < 4; j++) bd[i][j] = b0[j];
      }
    }
    STAMP(43);
    mbar_wait(sBar + B_G3, 0);
    STAMP(76);
    {
      float c[2][3][4];
#pragma unroll
      for (int i = 0; i < 6; i++) c[i & 1][i >> 1][0] = c[i & 1][i >> 1][1] = c[i & 1][i >> 1][2] = c[i & 1][i >> 1][3] = 0.f;
      uint32_t hb[5][4];
#pragma unroll
      for (int i = 0; i < 5; i++) ldsm4(hb[i], sb + SM_T + T_H + (lane & 1) * 1152 + kq * 288 + (lane >> 3) * 16 + i * 64);
#pragma unroll
      for (int ks = 0; ks < 9; ks++) {
        const uint32_t h0 = hb[ks >> 1][(ks & 1) * 2], h1 = hb[ks >> 1][(ks & 1) * 2 + 1];
        mma16816(c[ks & 1][0], bg[ks][0], bg[ks][2], bg[ks][1], bg[ks][3], h0, h1);
        mma16816(c[ks & 1][1], bg[ks][4], bg[ks][6], bg[ks][5], bg[ks][7], h0, h1);
        mma16816(c[ks & 1][2], bg[ks][8], 0u, bg[ks][9], 0u, h0, h1);
      }
      float* const part = tsf + 64;
      const bool u1 = lane & 1, u2 = lane & 2;
#pragma unroll
      for (int i = 0; i < 3; i++) {
        const float v = (u2 ? (u1 ? c[0][i][3] : c[0][i][2]) : (u1 ? c[0][i][1] : c[0][i][0])) + (u2 ? (u1 ? c[1][i][3] : c[1][i][2]) : (u1 ? c[1][i][1] : c[1][i][0]));
        if (i < 2 || !u2) part[w8 * 80 + (t4 & 1) * 40 + i * 16 + (t4 >> 1) * 8 + g] = v;
      }
      STAMP(45);
      bar_sync(5, 256);
      STAMP(46);
      auto act2 = [&](int f) {
        const float2* pp = reinterpret_cast<const float2*>(part + (g & 1) * 40 + f + (b & 1) * 4);
        const float2 g0 = pp[0], g1 = pp[80], g2 = pp[160], g3 = pp[240], u0 = pp[40], u1 = pp[120], u2 = pp[200], u3 = pp[280];
        return pack_bf16(silu_bf(bfr((g0.x + g1.x) + (g2.x + g3.x))) * bfr((u0.x + u1.x) + (u2.x + u3.x)),
                         silu_bf(bfr((g0.y + g1.y) + (g2.y + g3.y))) * bfr((u0.y + u1.y) + (u2.y + u3.y)));
      };
      const uint32_t v0 = act2((g >> 1) * 8 + t4 * 2), v1 = act2(32 + (t4 & 1) * 2);
      uint32_t a6[5];
#pragma unroll
      for (int i = 0; i < 4; i++) a6[i] = __shfl_sync(~0u, v0, i * 8 + (lane & 7));
      a6[4] = t4 < 2 ? v1 : 0u;
      STAMP(47);
      float* const yp = reinterpret_cast<float*>(g_ones + F_YP) + b * 64 + g * 2;
      float y[5][4];
#pragma unroll
      for (int i = 0; i < 5; i++) {
        y[i][0] = y[i][1] = y[i][2] = y[i][3] = 0.f;
        mma16816(y[i], bd[2 * i][0], i < 4 ? bd[(2 * i + 1) % 9][0] : 0u, bd[2 * i][1], i < 4 ? bd[(2 * i + 1) % 9][1] : 0u, a6[0], a6[1]);
      }
#pragma unroll
      for (int i = 0; i < 5; i++) mma16816(y[i], bd[2 * i][2], i < 4 ? bd[(2 * i + 1) % 9][2] : 0u, bd[2 * i][3], i < 4 ? bd[(2 * i + 1) % 9][3] : 0u, a6[2], a6[3]);
#pragma unroll
      for (int i = 0; i < 5; i++) mma1688(y[i], bd[2 * i][4], i < 4 ? bd[(2 * i + 1) % 9][4] : 0u, a6[4]);
#pragma unroll
      for (int m = 0; m < 2; m++) {
        const float y0 = u2 ? (u1 ? y[2 * m + 1][2] : y[2 * m + 1][0]) : (u1 ? y[2 * m][2] : y[2 * m][0]);
        const float y1 = u2 ? (u1 ? y[2 * m + 1][3] : y[2 * m + 1][1]) : (u1 ? y[2 * m][3] : y[2 * m][1]);
        asm volatile("st.relaxed.gpu.global.v2.f32 [%0], {%1,%2};" ::"l"(yp + (m * 8 + w8) * 8192 + t4 * 16), "f"(y0), "f"(y1) : "memory");
      }
      if (t4 == 0) asm volatile("st.relaxed.gpu.global.v2.f32 [%0], {%1,%2};" ::"l"(yp + (16 + (w8 >> 2)) * 8192 + (w8 & 3) * 16), "f"(y[4][0]), "f"(y[4][1]) : "memory");
    }
    STAMP(78);
    if (b < 72) {
      const uint4* pp = g_ones + F_YP + (b >> 2) * 2048 + (w8 * 16 + g) * 16 + (b & 3) * 4 + t4;
      const uint4 none = make_uint4(~0u, ~0u, ~0u, ~0u);
      uint4 r0 = none, r1 = none, q[FK][2];
      PSTAMP(352, 62);
#pragma unroll
      for (int j = 0; j < FK; j++) {
        if (j) { const uint32_t t0 = clock(); while (clock() - t0 < FD) {} }
        q[j][0] = ldr4(pp); q[j][1] = ldr4(pp + 128);
      }
      float gb, hv, sg;
      uint16_t xv = 0;
      bf16* op;
      if (w8 == 7) {
        const uint32_t k1 = tsu[32], k2 = tsu[33];
        const int row1 = ~k1 & (SQ - 1), row2 = ~k2 & (SQ - 1);
        const int tok = lane & 1, col = (b < 64 ? ((b >> 5) * 4 + (b & 3)) * 64 + (b & 28) * 2 : b * 8) + ((lane >> 1) & 7);
        const uint32_t key = tok ? k2 : k1;
        const int row = tok ? row2 : row1;
        const int c1 = ((row1 >> 5) & 3) * 32 + (row1 >> 7) * 2 + ((row1 >> 4) & 1), cr = ((row >> 5) & 3) * 32 + (row >> 7) * 2 + ((row >> 4) & 1);
        const uint16_t* xp = reinterpret_cast<const uint16_t*>(g_ones + F_HX + cr * 288 + (tok && c1 == cr ? 144 : 0) + 72) + col;
        gb = __uint_as_float((uint32_t)reinterpret_cast<const uint16_t*>(smem_raw + SM_MD)[(col >> 1) * 8 + 6 + (col & 1)] << 16);
        hv = __uint_as_float((uint32_t)reinterpret_cast<const uint16_t*>(smem_raw + SM_T + T_H)[tok * DM + col] << 16);
        sg = bfr(rcp(1.f + __expf(-__uint_as_float((key & 0xffff0000u) ^ ((key >> 31) ? 0x80000000u : 0xffff0000u)))));
        op = prm.out + (size_t)row * DM + col;
#pragma unroll 1
        for (uint32_t n = 0; n < (1u << 15); n++) {
          asm volatile("ld.relaxed.gpu.global.u16 %0, [%1];" : "=h"(xv) : "l"(xp) : "memory");
          if (xv != 0xffff) break;
        }
        __syncwarp();
      }
#pragma unroll 1
      for (uint32_t n = 0;; n++) {
        bool done = false;
#pragma unroll
        for (int j = 0; j < FK; j++) {
          if (unset(r0)) r0 = q[j][0];
          if (unset(r1)) r1 = q[j][1];
          const bool m0 = unset(r0), m1 = unset(r1);
          if (!__any_sync(~0u, m0 || m1)) { done = true; break; }
          if (m0) q[j][0] = ldr4(pp);
          if (m1) q[j][1] = ldr4(pp + 128);
        }
        if (done) break;
        if (n > (1u << 14)) { SETERR(32); break; }
      }
      PSTAMP(352, 63);
      float s[4] = {__uint_as_float(r0.x) + __uint_as_float(r1.x), __uint_as_float(r0.y) + __uint_as_float(r1.y),
                    __uint_as_float(r0.z) + __uint_as_float(r1.z), __uint_as_float(r0.w) + __uint_as_float(r1.w)};
      const bool u4 = lane & 4, u8 = lane & 8;
#pragma unroll
      for (int i = 0; i < 2; i++) { const float snd = u4 ? s[i] : s[i + 2], kp = u4 ? s[i + 2] : s[i]; s[i] = kp + __shfl_xor_sync(~0u, snd, 4); }
      { const float snd = u8 ? s[0] : s[1], kp = u8 ? s[1] : s[0]; s[0] = kp + __shfl_xor_sync(~0u, snd, 8); }
      s[0] += __shfl_xor_sync(~0u, s[0], 16);
      float* const fs = reinterpret_cast<float*>(smem_raw + SM_PS);
      if (lane < 16) fs[(t4 * 4 + (g & 1) * 2 + (g >> 1)) * 8 + w8] = s[0];
      if (w8 < 7) bar_arrive(5, 256);
      else {
        bar_sync(5, 256);
        const float4 a = *reinterpret_cast<const float4*>(fs + (lane & 15) * 8), c = *reinterpret_cast<const float4*>(fs + (lane & 15) * 8 + 4);
        const float hh = bfr(hv + bfr(bfr(((a.x + a.y) + (a.z + a.w)) + ((c.x + c.y) + (c.z + c.w))) * sg));
        if (lane < 16) *op = __float2bfloat16(__uint_as_float((uint32_t)xv << 16) + bfr(gb * hh));
      }
      PSTAMP(352, 49);
    }
    if (w8 == 5 && lane < 9) g_mod1[b * 9 + lane] = make_uint4(0u, 0u, 0u, 0u);
    if (w8 == 5 && lane == 9) *reinterpret_cast<uint2*>(&g_cnt[(C_Q + b) * 32]) = make_uint2(0u, 0u);
    if (w8 == 5 && lane == 10 && b == 0) g_cnt[C_SIDE * 32] = 0;
    STAMP(79); GSTAMP(91);
    }
  }
}

typedef CUresult (*PFN_enc)(CUtensorMap*, CUtensorMapDataType, cuuint32_t, void*, const cuuint64_t*, const cuuint64_t*,
                            const cuuint32_t*, const cuuint32_t*, CUtensorMapInterleave, CUtensorMapSwizzle,
                            CUtensorMapL2promotion, CUtensorMapFloatOOBfill);
static PFN_enc g_enc = nullptr;
static CUtensorMap mk_map(const void* p, uint64_t cols, uint64_t rows, uint32_t bc, uint32_t br, bool swz = true) {
  CUtensorMap m;
  cuuint64_t dims[2] = {cols, rows};
  cuuint64_t strides[1] = {cols * 2};
  cuuint32_t box[2] = {bc, br}, es[2] = {1, 1};
  g_enc(&m, CU_TENSOR_MAP_DATA_TYPE_BFLOAT16, 2, const_cast<void*>(p), dims, strides, box, es, CU_TENSOR_MAP_INTERLEAVE_NONE,
        swz ? CU_TENSOR_MAP_SWIZZLE_128B : CU_TENSOR_MAP_SWIZZLE_NONE, swz ? CU_TENSOR_MAP_L2_PROMOTION_L2_128B : CU_TENSOR_MAP_L2_PROMOTION_NONE,
        CU_TENSOR_MAP_FLOAT_OOB_FILL_NONE);
  return m;
}

static CUtensorMap mk_map_n(const void* p, int n, const cuuint64_t* dims, const cuuint64_t* strides, const cuuint32_t* box) {
  CUtensorMap m;
  cuuint32_t es[4] = {1, 1, 1, 1};
  g_enc(&m, CU_TENSOR_MAP_DATA_TYPE_BFLOAT16, n, const_cast<void*>(p), dims, strides, box, es, CU_TENSOR_MAP_INTERLEAVE_NONE,
        CU_TENSOR_MAP_SWIZZLE_128B, CU_TENSOR_MAP_L2_PROMOTION_L2_128B, CU_TENSOR_MAP_FLOAT_OOB_FILL_NONE);
  return m;
}

extern "C" void kernel_launch(void* const* d_in, const int* in_sizes, int n_in, void* d_out, int out_size) {
  if (!g_enc) {
    cudaDriverEntryPointQueryResult st;
    cudaGetDriverEntryPoint("cuTensorMapEncodeTiled", (void**)&g_enc, cudaEnableDefault, &st);
    cudaFuncSetAttribute(k_mega, cudaFuncAttributeMaxDynamicSharedMemorySize, SM_TOTAL);
  }
  CUtensorMap mX = mk_map(d_in[0], DM, SQ, 64, 128);
  CUtensorMap mWq = mk_map(d_in[3], HQ * DH, DM, 64, 144);
  CUtensorMap mK = mk_map(d_in[1], DH, HKV * SK, 64, 128);
  CUtensorMap mV = mk_map(d_in[2], DH, HKV * SK, 64, 128);
  const cuuint64_t od[4] = {DM, DH, 2, HKV}, os[3] = {DM * 2, DH * DM * 2, 2 * DH * DM * 2};
  const cuuint32_t ob[4] = {64, DH, 1, 2};
  CUtensorMap mWo = mk_map_n(d_in[4], 4, od, os, ob);
  CUtensorMap mWg = mk_map(d_in[7], FF, DM, 40, 144, false);
  CUtensorMap mWu = mk_map(d_in[8], FF, DM, 40, 144, false);
  const cuuint64_t dd[3] = {64, FF, 9}, ds[2] = {DM * 2, 128};
  const cuuint32_t db[3] = {64, 40, 9};
  CUtensorMap mWd = mk_map_n(d_in[9], 3, dd, ds, db);
  Params prm;
  prm.x = (const bf16*)d_in[0]; prm.k = (const bf16*)d_in[1]; prm.v = (const bf16*)d_in[2]; prm.wo = (const bf16*)d_in[4]; prm.wq = (const bf16*)d_in[3];
  prm.w_r = (const bf16*)d_in[6]; prm.c = (const bf16*)d_in[10]; prm.w_mod = (const bf16*)d_in[11];
  prm.wg = (const bf16*)d_in[7]; prm.wu = (const bf16*)d_in[8]; prm.wd = (const bf16*)d_in[9];
  prm.out = (bf16*)d_out;
  cudaLaunchConfig_t cfg = {};
  cfg.gridDim = dim3(128); cfg.blockDim = dim3(384); cfg.dynamicSmemBytes = SM_TOTAL; cfg.stream = cudaStreamPerThread;
  cudaLaunchAttribute at[1];
  at[0].id = cudaLaunchAttributeClusterDimension;
  at[0].val.clusterDim.x = 2; at[0].val.clusterDim.y = 1; at[0].val.clusterDim.z = 1;
  cfg.attrs = at; cfg.numAttrs = 1;
  cudaLaunchKernelEx(&cfg, k_mega, mX, mWq, mK, mV, mWo, mWg, mWu, mWd, prm);
}
```

```cpp
#include <cuda_runtime.h>
#include <cuda_bf16.h>
#include <cuda.h>
#include <stdint.h>

typedef __nv_bfloat16 bf16;

constexpr int SQ = 2048, DM = 576, HQ = 32, HKV = 16, SK = 2048, DH = 128, FF = 4608;

#define TCH 20
#define TF0 26
#define TW0 16
#define TWN 4
#define FAKEB 0
#define FILLS 30
#define WOMC 0
#define FFNS 0x6420
#define ORD 1
#define FIXS 0
#define HINTH 1
#define HINTW 1
#define PFO 1
#define TN 3
#define FGAP 0
#define FGN 8
#define BGE 5
#define FPRED 1
#define XD 500
#define CV 1
#define WARM 0
#define XT 0
#define CT 0
#define TMP 1
#define XO 0
#define RS0 0
#define CL 0
#define PM 0
#define PN 4
#define MM 31
#define XW 1
#define GP 0
#define FX 1
#define MG 1
#define MGL 0
#define HX 1
#define N2 1
#define HS 0
#define EH 8
#define XD1 1000
#define PW 0
#define QW 0
#define B7 1
#define LN_LIMIT 0.0625f
#define TG 9
#define TL 1
#define KICK 0
#define MT 1
#define MWARM 0
#define PE 0
#define PD 0
#define FK 1
#define FD 300
#define XPF 0
#define WQPF0 0
#define WQPF1 0xff
#define FFNQ 2
#define WQPF2 0
#define QTH 4
#define MPF 1
#define FILLP 31
#define FILL0 25
#define FFN0 20
#define FILLN 8
#define FFNB 6
#define PF0 20
#define FFNR 1
#define FFND 1
#define KV0 16
#define KVS 2
#define QPF 6
#define EF 31
#define WOP 20
#define TLBW 0
#define NOFFN 0
#define FLATE 0
#define RELF 1
#define REL_FENCE() asm volatile("fence.acq_rel.gpu;" ::: "memory")
#define FILLMAX (F_N / 128)
#define XN 4
#define MODB 0
#define QPV 0
#define LATEG 0
#define RETL 1
#define HINTA 15
#define SIDEF 3
#define FFNE 15
#define TE_POS 8
#define LAZY_LIMIT 1.8446744e19f
#define LAZY_LOW 5.4210109e-20f
__device__ uint4 g_mod1[8 * 144];
__device__ uint4 g_mod2[288];
__device__ uint4 g_q[128 * 4 * 8 * 256];
constexpr int F_HX = 0;
constexpr int F_YP = 128 * 288;
constexpr int F_KEY = 128 * 576;
constexpr int F_PART = 128 * 640;
constexpr int F_N = 640 + 5120;
__device__ uint4 g_ones[128 * F_N];
__device__ __align__(128) unsigned int g_cnt[136 * 32];
__device__ unsigned int g_err;
#define HAS_ERR
enum { C_SIDE = 1, C_Q = 8 };

#define STAMP(i)
#define KSTAMP(i)
#define GSTAMP(i)
#define SETERR(v)
#define ES(t, w, i)
#define ESC(i)
#define PSTAMP(t, i)

__device__ __forceinline__ int get_lane() {
  int l;
  asm volatile("mov.u32 %0, %%laneid;" : "=r"(l));
  __builtin_assume(l >= 0 && l < 32);
  return l;
}
__device__ __forceinline__ uint32_t clk() { uint32_t c; asm volatile("mov.u32 %0, %%clock;" : "=r"(c) :: "memory"); return c; }
__device__ __forceinline__ void delay(uint32_t n) { const uint32_t t0 = clk(); while (clk() - t0 < n) {} }
__device__ __forceinline__ uint32_t smem_u32(const void* p) { return (uint32_t)__cvta_generic_to_shared(p); }
__device__ __forceinline__ void mbar_init(uint32_t a, uint32_t cnt) { asm volatile("mbarrier.init.shared::cta.b64 [%0], %1;" ::"r"(a), "r"(cnt)); }
__device__ __forceinline__ void mbar_expect_tx(uint32_t a, uint32_t bytes) { asm volatile("mbarrier.arrive.expect_tx.shared::cta.b64 _, [%0], %1;" ::"r"(a), "r"(bytes) : "memory"); }
__device__ __forceinline__ void mbar_arrive(uint32_t a) { asm volatile("mbarrier.arrive.shared::cta.b64 _, [%0];" ::"r"(a) : "memory"); }
__device__ __forceinline__ void mbar_arrive_cl(uint32_t a_cluster) { asm volatile("mbarrier.arrive.shared::cluster.b64 _, [%0];" ::"r"(a_cluster) : "memory"); }
__device__ __forceinline__ void mbar_wait(uint32_t a, uint32_t parity) {
  asm volatile(
      "{\n.reg .pred p;\n.reg .u32 n;\nmov.u32 n, 0;\n"
      "WAIT_LOOP:\n"
      "mbarrier.try_wait.parity.shared::cta.b64 p, [%0], %1;\n"
      "@p bra WAIT_DONE;\n"
      "add.u32 n, n, 1;\n"
      "setp.lt.u32 p, n, 65536;\n"
      "@p bra WAIT_LOOP;\n"
      "WAIT_DONE:\n}\n" ::"r"(a), "r"(parity), "l"(&g_err) : "memory");
}
__device__ __forceinline__ void cnt_wait(int idx, unsigned target) {
  for (uint32_t n = 0;; n++) {
    unsigned v;
    asm volatile("ld.relaxed.gpu.global.u32 %0, [%1];" : "=r"(v) : "l"(&g_cnt[idx * 32]) : "memory");
    if (v >= target) break;
    if (n > (1u << 15)) { SETERR(2); break; }
  }
}
__device__ __forceinline__ void cnt_wait1(int word, unsigned target) {
  for (uint32_t n = 0;; n++) {
    unsigned v;
    asm volatile("ld.relaxed.gpu.global.u32 %0, [%1];" : "=r"(v) : "l"(&g_cnt[word]) : "memory");
    if (v >= target) break;
    if (n > (1u << 15)) { SETERR(2); break; }
  }
}
__device__ __forceinline__ void cnt_arrive(int idx) {
  asm volatile("red.relaxed.gpu.global.add.u32 [%0], 1;" ::"l"(&g_cnt[idx * 32]) : "memory");
}
__device__ __forceinline__ uint4 poll4(const uint4* p) {
  uint4 v;
  uint32_t n = 0;
  while (true) {
    asm volatile("ld.relaxed.gpu.global.v4.u32 {%0,%1,%2,%3}, [%4];" : "=r"(v.x), "=r"(v.y), "=r"(v.z), "=r"(v.w) : "l"(p) : "memory");
    if (v.x && v.y && v.z && v.w) break;
    if (++n > (1u << 15)) { SETERR(4); break; }
  }
  return v;
}
__device__ __forceinline__ void poll8(const uint4* p, const uint4* q, uint4& v, uint4& w) {
  uint32_t n = 0;
#pragma unroll 1
  while (true) {
    asm volatile("ld.relaxed.gpu.global.v4.u32 {%0,%1,%2,%3}, [%4];" : "=r"(v.x), "=r"(v.y), "=r"(v.z), "=r"(v.w) : "l"(p) : "memory");
    asm volatile("ld.relaxed.gpu.global.v4.u32 {%0,%1,%2,%3}, [%4];" : "=r"(w.x), "=r"(w.y), "=r"(w.z), "=r"(w.w) : "l"(q) : "memory");
    if (v.x && v.y && v.z && v.w && w.x && w.y && w.z && w.w) break;
    if (++n > (1u << 15)) { SETERR(4); break; }
  }
}
__device__ __forceinline__ uint4 ldr4(const void* p) {
  uint4 v;
  asm volatile("ld.relaxed.gpu.global.v4.u32 {%0,%1,%2,%3}, [%4];" : "=r"(v.x), "=r"(v.y), "=r"(v.z), "=r"(v.w) : "l"(p) : "memory");
  return v;
}
__device__ __forceinline__ uint2 ldr2(const void* p) {
  uint2 v;
  asm volatile("ld.relaxed.gpu.global.v2.u32 {%0,%1}, [%2];" : "=r"(v.x), "=r"(v.y) : "l"(p) : "memory");
  return v;
}
__device__ __forceinline__ uint32_t ldr1(const void* p) {
  uint32_t v;
  asm volatile("ld.relaxed.gpu.global.u32 %0, [%1];" : "=r"(v) : "l"(p) : "memory");
  return v;
}
__device__ __forceinline__ void str1(void* p, uint32_t v) { asm volatile("st.relaxed.gpu.global.u32 [%0], %1;" ::"l"(p), "r"(v) : "memory"); }
__device__ __forceinline__ bool unset(uint4 v) { return v.x == ~0u || v.y == ~0u || v.z == ~0u || v.w == ~0u; }
__device__ __forceinline__ bool nan2(uint32_t v) {
  uint32_t r;
  asm("{\n.reg .pred p, q;\nsetp.nan.bf16x2 p|q, %1, %1;\nor.pred p, p, q;\nselp.u32 %0, 1, 0, p;\n}\n" : "=r"(r) : "r"(v));
  return r != 0;
}
__device__ __forceinline__ uint32_t hmul2(uint32_t a, uint32_t b) { uint32_t r; asm("mul.rn.bf16x2 %0, %1, %2;" : "=r"(r) : "r"(a), "r"(b)); return r; }
__device__ __forceinline__ uint32_t hadd2(uint32_t a, uint32_t b) { uint32_t r; asm("add.rn.bf16x2 %0, %1, %2;" : "=r"(r) : "r"(a), "r"(b)); return r; }
__device__ __forceinline__ uint32_t hfma2(uint32_t a, uint32_t b, uint32_t c) { uint32_t r; asm("fma.rn.bf16x2 %0, %1, %2, %3;" : "=r"(r) : "r"(a), "r"(b), "r"(c)); return r; }
__device__ __forceinline__ void mma16816(float (&c)[4], uint32_t a0, uint32_t a1, uint32_t a2, uint32_t a3, uint32_t b0, uint32_t b1) {
  asm volatile("mma.sync.aligned.m16n8k16.row.col.f32.bf16.bf16.f32 {%0,%1,%2,%3}, {%4,%5,%6,%7}, {%8,%9}, {%0,%1,%2,%3};"
               : "+f"(c[0]), "+f"(c[1]), "+f"(c[2]), "+f"(c[3]) : "r"(a0), "r"(a1), "r"(a2), "r"(a3), "r"(b0), "r"(b1));
}
__device__ __forceinline__ void mma1688(float (&c)[4], uint32_t a0, uint32_t a1, uint32_t b0) {
  asm volatile("mma.sync.aligned.m16n8k8.row.col.f32.bf16.bf16.f32 {%0,%1,%2,%3}, {%4,%5}, {%6}, {%0,%1,%2,%3};"
               : "+f"(c[0]), "+f"(c[1]), "+f"(c[2]), "+f"(c[3]) : "r"(a0), "r"(a1), "r"(b0));
}
__device__ __forceinline__ void ldsm4t(uint32_t (&r)[4], uint32_t a) {
  asm volatile("ldmatrix.sync.aligned.m8n8.x4.trans.shared.b16 {%0,%1,%2,%3}, [%4];" : "=r"(r[0]), "=r"(r[1]), "=r"(r[2]), "=r"(r[3]) : "r"(a) : "memory");
}
__device__ __forceinline__ void ldsm4(uint32_t (&r)[4], uint32_t a) {
  asm volatile("ldmatrix.sync.aligned.m8n8.x4.shared.b16 {%0,%1,%2,%3}, [%4];" : "=r"(r[0]), "=r"(r[1]), "=r"(r[2]), "=r"(r[3]) : "r"(a) : "memory");
}
__device__ __forceinline__ void ldsm2t(uint32_t (&r)[2], uint32_t a) {
  asm volatile("ldmatrix.sync.aligned.m8n8.x2.trans.shared.b16 {%0,%1}, [%2];" : "=r"(r[0]), "=r"(r[1]) : "r"(a) : "memory");
}
__device__ __forceinline__ float warp_sum(float v) {
#pragma unroll
  for (int o = 16; o; o >>= 1) v += __shfl_xor_sync(~0u, v, o);
  return v;
}
__device__ __forceinline__ void tma_load_2d(uint32_t dst, const CUtensorMap* map, uint32_t mbar, int c0, int c1) {
  asm volatile("cp.async.bulk.tensor.2d.shared::cluster.global.mbarrier::complete_tx::bytes [%0], [%1, {%3, %4}], [%2];"
               ::"r"(dst), "l"(map), "r"(mbar), "r"(c0), "r"(c1) : "memory");
}
__device__ __forceinline__ void tma_load_2d_mc(uint32_t dst, const CUtensorMap* map, uint32_t mbar, int c0, int c1) {
  asm volatile("cp.async.bulk.tensor.2d.shared::cluster.global.mbarrier::complete_tx::bytes.multicast::cluster [%0], [%1, {%3, %4}], [%2], %5;"
               ::"r"(dst), "l"(map), "r"(mbar), "r"(c0), "r"(c1), "h"((uint16_t)3) : "memory");
}
__device__ __forceinline__ uint64_t pol_first() {
  uint64_t p;
  asm("createpolicy.fractional.L2::evict_first.b64 %0, 1.0;" : "=l"(p));
  return p;
}
__device__ __forceinline__ void tma_load_2d_h(uint32_t dst, const CUtensorMap* map, uint32_t mbar, int c0, int c1, uint64_t pol) {
  asm volatile("cp.async.bulk.tensor.2d.shared::cluster.global.mbarrier::complete_tx::bytes.L2::cache_hint [%0], [%1, {%3, %4}], [%2], %5;"
               ::"r"(dst), "l"(map), "r"(mbar), "r"(c0), "r"(c1), "l"(pol) : "memory");
}
__device__ __forceinline__ void tma_load_2d_mc_h(uint32_t dst, const CUtensorMap* map, uint32_t mbar, int c0, int c1, uint64_t pol) {
  asm volatile("cp.async.bulk.tensor.2d.shared::cluster.global.mbarrier::complete_tx::bytes.multicast::cluster.L2::cache_hint [%0], [%1, {%3, %4}], [%2], %5, %6;"
               ::"r"(dst), "l"(map), "r"(mbar), "r"(c0), "r"(c1), "h"((uint16_t)3), "l"(pol) : "memory");
}
__device__ __forceinline__ void tma_load_3d(uint32_t dst, const CUtensorMap* map, uint32_t mbar, int c0, int c1, int c2) {
  asm volatile("cp.async.bulk.tensor.3d.shared::cluster.global.mbarrier::complete_tx::bytes [%0], [%1, {%3, %4, %5}], [%2];"
               ::"r"(dst), "l"(map), "r"(mbar), "r"(c0), "r"(c1), "r"(c2) : "memory");
}
__device__ __forceinline__ void tma_load_3d_mc(uint32_t dst, const CUtensorMap* map, uint32_t mbar, int c0, int c1, int c2) {
  asm volatile("cp.async.bulk.tensor.3d.shared::cluster.global.mbarrier::complete_tx::bytes.multicast::cluster [%0], [%1, {%3, %4, %5}], [%2], %6;"
               ::"r"(dst), "l"(map), "r"(mbar), "r"(c0), "r"(c1), "r"(c2), "h"((uint16_t)3) : "memory");
}
__device__ __forceinline__ void tma_load_4d_h(uint32_t dst, const CUtensorMap* map, uint32_t mbar, int c0, int c1, int c2, int c3, uint64_t pol) {
  asm volatile("cp.async.bulk.tensor.4d.shared::cluster.global.mbarrier::complete_tx::bytes.L2::cache_hint [%0], [%1, {%3, %4, %5, %6}], [%2], %7;"
               ::"r"(dst), "l"(map), "r"(mbar), "r"(c0), "r"(c1), "r"(c2), "r"(c3), "l"(pol) : "memory");
}
__device__ __forceinline__ void tma_prefetch_2d(const CUtensorMap* map, int c0, int c1) {
  asm volatile("cp.async.bulk.prefetch.tensor.2d.L2.global.tile [%0, {%1, %2}];" ::"l"(map), "r"(c0), "r"(c1) : "memory");
}
__device__ __forceinline__ void bulk_prefetch(const void* p, uint32_t bytes) {
  asm volatile("cp.async.bulk.prefetch.L2.global [%0], %1;" ::"l"(p), "r"(bytes) : "memory");
}
__device__ __forceinline__ void bulk_load(uint32_t dst, const void* src, uint32_t bytes, uint32_t mbar) {
  asm volatile("cp.async.bulk.shared::cluster.global.mbarrier::complete_tx::bytes [%0], [%1], %2, [%3];"
               ::"r"(dst), "l"(src), "r"(bytes), "r"(mbar) : "memory");
}
__device__ __forceinline__ void wgmma_fence() { asm volatile("wgmma.fence.sync.aligned;" ::: "memory"); }
__device__ __forceinline__ void wgmma_commit() { asm volatile("wgmma.commit_group.sync.aligned;" ::: "memory"); }
template <int N> __device__ __forceinline__ void wgmma_wait() { asm volatile("wgmma.wait_group.sync.aligned %0;" ::"n"(N) : "memory"); }
__device__ __forceinline__ void fence_async() { asm volatile("fence.proxy.async.shared::cta;" ::: "memory"); }
__device__ __forceinline__ void bar_sync(int id, int n) { asm volatile("bar.sync %0, %1;" ::"r"(id), "r"(n) : "memory"); }
__device__ __forceinline__ void bar_arrive(int id, int n) { asm volatile("bar.arrive %0, %1;" ::"r"(id), "r"(n) : "memory"); }

constexpr uint32_t SM_BASE = 1024;
__host__ __device__ constexpr uint32_t mk_desc(uint32_t addr, uint32_t lbo_bytes) { return ((addr & 0x3FFFF) >> 4) | ((lbo_bytes >> 4) << 16); }

#define R32(d) \
  "+f"(d[0]), "+f"(d[1]), "+f"(d[2]), "+f"(d[3]), "+f"(d[4]), "+f"(d[5]), "+f"(d[6]), "+f"(d[7]), \
  "+f"(d[8]), "+f"(d[9]), "+f"(d[10]), "+f"(d[11]), "+f"(d[12]), "+f"(d[13]), "+f"(d[14]), "+f"(d[15]), \
  "+f"(d[16]), "+f"(d[17]), "+f"(d[18]), "+f"(d[19]), "+f"(d[20]), "+f"(d[21]), "+f"(d[22]), "+f"(d[23]), \
  "+f"(d[24]), "+f"(d[25]), "+f"(d[26]), "+f"(d[27]), "+f"(d[28]), "+f"(d[29]), "+f"(d[30]), "+f"(d[31])
#define R64(d) R32(d), \
  "+f"(d[32]), "+f"(d[33]), "+f"(d[34]), "+f"(d[35]), "+f"(d[36]), "+f"(d[37]), "+f"(d[38]), "+f"(d[39]), \
  "+f"(d[40]), "+f"(d[41]), "+f"(d[42]), "+f"(d[43]), "+f"(d[44]), "+f"(d[45]), "+f"(d[46]), "+f"(d[47]), \
  "+f"(d[48]), "+f"(d[49]), "+f"(d[50]), "+f"(d[51]), "+f"(d[52]), "+f"(d[53]), "+f"(d[54]), "+f"(d[55]), \
  "+f"(d[56]), "+f"(d[57]), "+f"(d[58]), "+f"(d[59]), "+f"(d[60]), "+f"(d[61]), "+f"(d[62]), "+f"(d[63])
#define S32 \
  "{%0,%1,%2,%3,%4,%5,%6,%7,%8,%9,%10,%11,%12,%13,%14,%15,%16,%17,%18,%19,%20,%21,%22,%23,%24,%25,%26,%27,%28,%29,%30,%31}"
#define S64 \
  "{%0,%1,%2,%3,%4,%5,%6,%7,%8,%9,%10,%11,%12,%13,%14,%15,%16,%17,%18,%19,%20,%21,%22,%23,%24,%25,%26,%27,%28,%29,%30,%31," \
  "%32,%33,%34,%35,%36,%37,%38,%39,%40,%41,%42,%43,%44,%45,%46,%47,%48,%49,%50,%51,%52,%53,%54,%55,%56,%57,%58,%59,%60,%61,%62,%63}"

template <int TB>
__device__ __forceinline__ void wgmma128_rs(float (&d)[64], uint32_t a0, uint32_t a1, uint32_t a2, uint32_t a3, uint32_t db, int scale_d) {
  asm volatile("{\n.reg .pred p;\n.reg .b64 q;\nsetp.ne.b32 p, %69, 0;\nmov.b64 q, {%68, 0x40000040};\n"
               "wgmma.mma_async.sync.aligned.m64n128k16.f32.bf16.bf16 " S64 ", {%64,%65,%66,%67}, q, p, 1, 1, %70;\n}\n"
               : R64(d) : "r"(a0), "r"(a1), "r"(a2), "r"(a3), "r"(db), "r"(scale_d), "n"(TB));
}
__device__ __forceinline__ void wgmma64_rs(float (&d)[32], uint32_t a0, uint32_t a1, uint32_t a2, uint32_t a3, uint32_t db, int scale_d) {
  asm volatile("{\n.reg .pred p;\n.reg .b64 q;\nsetp.ne.b32 p, %37, 0;\nmov.b64 q, {%36, 0x40000040};\n"
               "wgmma.mma_async.sync.aligned.m64n64k16.f32.bf16.bf16 " S32 ", {%32,%33,%34,%35}, q, p, 1, 1, 1;\n}\n"
               : R32(d) : "r"(a0), "r"(a1), "r"(a2), "r"(a3), "r"(db), "r"(scale_d));
}
__device__ __forceinline__ uint32_t pack_bf16(float a, float b) {
  uint32_t r;
  asm("cvt.rn.bf16x2.f32 %0, %1, %2;" : "=r"(r) : "f"(b), "f"(a));
  return r;
}
__device__ __forceinline__ float ex2(float x) { float y; asm("ex2.approx.ftz.f32 %0, %1;" : "=f"(y) : "f"(x)); return y; }
__device__ __forceinline__ float bfr(float x) { return __bfloat162float(__float2bfloat16(x)); }
__device__ __forceinline__ float bf_lo(uint32_t u) { return __uint_as_float(u << 16); }
__device__ __forceinline__ float bf_hi(uint32_t u) { return __uint_as_float(u & 0xffff0000u); }
__device__ __forceinline__ uint4 lds128(uint32_t a) {
  uint4 v;
  asm volatile("ld.shared.v4.b32 {%0,%1,%2,%3}, [%4];" : "=r"(v.x), "=r"(v.y), "=r"(v.z), "=r"(v.w) : "r"(a) : "memory");
  return v;
}
__device__ __forceinline__ void sts128(uint32_t a, uint4 v) {
  asm volatile("st.shared.v4.b32 [%0], {%1,%2,%3,%4};" ::"r"(a), "r"(v.x), "r"(v.y), "r"(v.z), "r"(v.w) : "memory");
}
__device__ __forceinline__ void red_add_v4(float4* p, float a, float b, float c, float d) {
  asm volatile("red.global.add.v4.f32 [%0], {%1,%2,%3,%4};" ::"l"(p), "f"(a), "f"(b), "f"(c), "f"(d) : "memory");
}
__device__ __forceinline__ float rcp(float x) { float y; asm("rcp.approx.ftz.f32 %0, %1;" : "=f"(y) : "f"(x)); return y; }
__device__ __forceinline__ float sqrt_a(float x) { float y; asm("sqrt.approx.ftz.f32 %0, %1;" : "=f"(y) : "f"(x)); return y; }
__device__ __forceinline__ float silu_f(float v) { return v * rcp(1.f + __expf(-v)); }
__device__ __forceinline__ float silu_bf(float v) { return bfr(v * rcp(1.f + __expf(-v))); }

constexpr int SM_STASH = 131072;
constexpr int QG = 73728;
constexpr int SM_STG = 3 * QG - 18432;
constexpr int SM_MT = 3 * QG;
constexpr int SM_MB = SM_MT + 4608;
constexpr int SM_XCH = 196608;
constexpr int SM_MISC = 229376;
constexpr int SM_TOTAL = 232448;
constexpr int B_FULLQ = 0, B_TB = 24, B_G2 = 32, B_G3 = 40, B_QH = 48, B_FULLA = 64, B_XR = 96, B_FULLO = 184, B_FFN = 160, B_FD = 168, B_MD = 176, B_X = 2944, B_X1 = 2952, B_MM = 2984,
              B_EMPTYQ = 280, B_G1 = 304, B_EMPTYO = 328, B_ST = 392,
              B_EMPTYA = 400, B_M = 432, B_XF = 144;
constexpr int SM_MOD = SM_MISC + 448;
constexpr int SM_FILL = SM_MISC + 512;
constexpr int SM_M2 = SM_MISC + 2560;
constexpr int SM_RED = SM_MISC + 2752;
constexpr int SM_ZERO = SM_MISC + 3040;
constexpr int SM_WG = 137216;
constexpr int SM_X2 = 65536;
constexpr int SM_WD = 84992;
constexpr int SM_T = 23040;
constexpr int T_H = 2816;
constexpr int SM_PS = SM_T + 5120;
constexpr int SM_OUT = SM_MISC - 16384;
constexpr int SM_MD = SM_STASH;

template <class F>
__device__ __forceinline__ void ln_rows(uint32_t (&A)[144], uint32_t la, int lane, F done) {
  float mA = 0.f, mB = 0.f, vA, vB;
  bool redo = la >> 31;
#pragma unroll 1
  do {
    if (__builtin_expect(redo, 0)) {
      const uint32_t n2 = __shfl_sync(~0u, pack_bf16(mA, mB), (lane & 7) * 4);
      const uint32_t n = __byte_perm(n2, 0, (lane & 8) ? 0x3232 : 0x1010);
#pragma unroll 1
      for (int k = 0; k < 36; k++) {
        const uint32_t a = (la ^ ((k & 3) << 5)) + (k >> 2) * 4096;
        const uint4 v = lds128(a);
        sts128(a, make_uint4(hadd2(v.x, n), hadd2(v.y, n), hadd2(v.z, n), hadd2(v.w, n)));
      }
      fence_async();
      __syncwarp();
    }
    const uint32_t one = 0x3f803f80u;
    float c[3][4], q[3][4];
#pragma unroll
    for (int i = 0; i < 12; i++) c[i >> 2][i & 3] = q[i >> 2][i & 3] = 0.f;
#pragma unroll
    for (int k = 0; k < 36; k++) {
      uint32_t a[4];
      ldsm4(a, (la ^ ((k & 3) << 5)) + (k >> 2) * 4096);
      A[k * 4] = a[0]; A[k * 4 + 1] = a[1]; A[k * 4 + 2] = a[2]; A[k * 4 + 3] = a[3];
    }
#pragma unroll
    for (int k = 0; k < 36; k++) {
      mma16816(c[k % 3], A[k * 4], A[k * 4 + 1], A[k * 4 + 2], A[k * 4 + 3], one, one);
      mma16816(q[k % 3], hmul2(A[k * 4], A[k * 4]), hmul2(A[k * 4 + 1], A[k * 4 + 1]), hmul2(A[k * 4 + 2], A[k * 4 + 2]), hmul2(A[k * 4 + 3], A[k * 4 + 3]), one, one);
    }
    mA = (c[0][0] + c[1][0] + c[2][0]) * (-1.f / DM); mB = (c[0][2] + c[1][2] + c[2][2]) * (-1.f / DM);
    vA = fmaf(-mA, mA, (q[0][0] + q[1][0] + q[2][0]) * (1.f / DM)); vB = fmaf(-mB, mB, (q[0][2] + q[1][2] + q[2][2]) * (1.f / DM));
    redo = __any_sync(~0u, !(mA * mA <= LN_LIMIT * vA && mB * mB <= LN_LIMIT * vB)) && !redo;
  } while (__builtin_expect(redo, 0));
  done();
  const float rA = rsqrtf(fmaxf(vA, 0.f) + 1e-5f), rB = rsqrtf(fmaxf(vB, 0.f) + 1e-5f);
  const uint32_t hA = pack_bf16(rA, rA), hB = pack_bf16(rB, rB);
  const uint32_t lA = pack_bf16(rA - bf_lo(hA), rA - bf_lo(hA)), lB = pack_bf16(rB - bf_lo(hB), rB - bf_lo(hB));
  const uint32_t oA = pack_bf16(mA * rA, mA * rA), oB = pack_bf16(mB * rB, mB * rB);
#pragma unroll
  for (int i = 0; i < 144; i++) A[i] = hfma2(A[i], (i & 1) ? hB : hA, N2 ? ((i & 1) ? oB : oA) : hfma2(A[i], (i & 1) ? lB : lA, (i & 1) ? oB : oA));
}
__device__ __forceinline__ void modulate(uint32_t (&A)[144], uint32_t mt) {
#pragma unroll
  for (int k = 0; k < 36; k++) {
    const uint4 m = lds128(mt + k * 64);
    A[k * 4] = hfma2(A[k * 4], m.y, m.x); A[k * 4 + 1] = hfma2(A[k * 4 + 1], m.y, m.x);
    A[k * 4 + 2] = hfma2(A[k * 4 + 2], m.w, m.z); A[k * 4 + 3] = hfma2(A[k * 4 + 3], m.w, m.z);
  }
}
__device__ __forceinline__ void q_mma(float (&qa)[32], const uint32_t (&A)[144], uint32_t db) {
#pragma unroll
  for (int k = 0; k < 36; k++) wgmma64_rs(qa, A[k * 4], A[k * 4 + 1], A[k * 4 + 2], A[k * 4 + 3], db + k * 128, k != 0);
  wgmma_commit();
}
constexpr float Q_SCALE = 0.08838834764831845f * 1.4426950408889634f;

struct Params {
  uint4* mod1;
  const bf16 *c, *w_mod, *x, *k, *v, *wq, *w_r, *wo, *wg, *wu, *wd;
  bf16* out;
};

__global__ void __cluster_dims__(2, 1, 1) __launch_bounds__(384, 1)
k_mega(const Params prm, const __grid_constant__ CUtensorMap mX, const __grid_constant__ CUtensorMap mWq,
       const __grid_constant__ CUtensorMap mK, const __grid_constant__ CUtensorMap mV,
       const __grid_constant__ CUtensorMap mWo, const __grid_constant__ CUtensorMap mWg,
       const __grid_constant__ CUtensorMap mWu, const __grid_constant__ CUtensorMap mWd, const __grid_constant__ CUtensorMap mM) {
  extern __shared__ __align__(1024) uint8_t smem_raw[];
#define ECLK(x)
  const uint32_t sb = smem_u32(smem_raw);
  if ((sb & 0x3FFFF) != SM_BASE) __trap();
  const uint32_t sBar = sb + SM_MISC;
  const int tid = threadIdx.x;
  const int lane = get_lane();
  const int warp = __shfl_sync(~0u, tid >> 5, 0);
  const int b = blockIdx.x, rank = b & 1, qt = (b >> 1) & 15, kg = b >> 5, hg = kg * 2 + rank;
  const int hcol = (kg * 8 + rank) * DH;
#define CL_ARRIVE() asm volatile("barrier.cluster.arrive.relaxed.aligned;" ::: "memory")
#define CL_WAIT() asm volatile("barrier.cluster.wait.acquire.aligned;" ::: "memory")
  if (__builtin_expect(b >= 128, 0)) {
    if (tid == 0) {
#pragma unroll
      for (int i = 0; i < 6; i++) mbar_init(sBar + i * 8, i < 3 ? 1 : 8);
      asm volatile("fence.mbarrier_init.release.cluster;" ::: "memory");
    }
    __syncthreads();
    if (warp < 4) {
      asm volatile("setmaxnreg.dec.sync.aligned.u32 40;");
      if (tid == 0) {
#pragma unroll 1
        for (int n = 0, g = 0, ph = 1, m = 0, row = (b - 128) * 512; n < 40; n++) {
          if (n >= 3) mbar_wait(sBar + 24 + g * 8, ph);
          mbar_expect_tx(sBar + g * 8, QG);
          if (m < 2) {
            tma_load_3d(sb + g * QG, &mX, sBar + g * 8, 0, row, 0);
            tma_load_3d(sb + g * QG + QG / 2, &mX, sBar + g * 8, 0, row + 32, 0);
            row += 64;
          } else {
#pragma unroll 1
            for (int i = 0; i < 4; i++) tma_load_2d(sb + g * QG + i * 18432, &mWq, sBar + g * 8, (((m - 2) >> 1) * 8 + (m & 1) + 6) * DH + 64, i * 144);
          }
          if (++g == 3) { g = 0; ph ^= 1; }
          if (++m == 10) m = 0;
        }
      } else if (warp > 0) {
        if (tid < 104) {
          uint4 v, w;
          poll8(prm.mod1 + tid - 32, prm.mod1 + tid + 40, v, w);
          uint2* const mt = reinterpret_cast<uint2*>(smem_raw + SM_MT) + ((tid - 32) >> 1) * 8 + (tid & 1);
          mt[0] = make_uint2(~v.x, ~w.x); mt[2] = make_uint2(~v.y, ~w.y); mt[4] = make_uint2(~v.z, ~w.z); mt[6] = make_uint2(~v.w, ~w.w);
        }
        __syncwarp();
        bar_arrive(3, 352);
      }
    } else {
      asm volatile("setmaxnreg.inc.sync.aligned.u32 232;");
      const int cw = (warp >> 2) - 1, w8 = warp - 4;
      bar_sync(3, 352);
      if (cw == 0) bar_arrive(1, 256);
#pragma unroll 1
      for (int it = 0, n = 0; it < 4; it++) {
        uint32_t A[144];
        {
          const int g = (n + cw) % 3;
          mbar_wait(sBar + g * 8, ((n + cw) / 3) & 1);
          ln_rows(A, sb + g * QG + (w8 & 2) * (QG / 4) + ((w8 & 1) * 16 + (lane & 15)) * 128 + (((lane >> 4) ^ (lane & 7)) << 4), lane,
                  [&]() { if (lane < 2) mbar_arrive(sBar + 24 + g * 8); });
          modulate(A, sb + SM_MT + (lane & 3) * 16);
        }
        n += 2;
        const int b0 = ((b - 128) * 4 + it) * 2;
#pragma unroll 1
        for (int d = 0; d < 8; d++, n++) {
          const int g = n % 3;
          float qa[32];
          mbar_wait(sBar + g * 8, (n / 3) & 1);
          bar_sync(1 + cw, 256);
          wgmma_fence();
          q_mma(qa, A, mk_desc(SM_BASE, 16) + g * (QG >> 4));
          if (n + cw < 40) bar_arrive(2 - cw, 256);
          wgmma_wait<0>();
          if (lane == 0) mbar_arrive(sBar + 24 + g * 8);
          uint4* const qp = g_q + (((d >> 1) * 32 + b0 + (d & 1)) * (4 * 8 * 256) + 28 * 256 + w8 * 32 + lane);
#pragma unroll
          for (int j = 0; j < 4; j++) {
            uint32_t u[4];
#pragma unroll
            for (int i = 0; i < 4; i++) u[i] = pack_bf16(qa[8 * j + 2 * i] * Q_SCALE, qa[8 * j + 2 * i + 1] * Q_SCALE);
            qp[j * 256] = (d & 1) ? make_uint4(u[1], u[0], u[3], u[2]) : make_uint4(u[0], u[1], u[2], u[3]);
          }
        }
        asm volatile("fence.acq_rel.gpu;" ::: "memory");
        __syncwarp();
        if (lane < 8) asm volatile("red.relaxed.gpu.global.add.u32 [%0], 1;" ::"l"(&g_cnt[(C_Q + (lane >> 1) * 32 + b0 + (lane & 1)) * 32 + 2]) : "memory");
      }
    }
    return;
  }
  uint32_t cv[3];
  auto ld_c = [&]() {
#pragma unroll
    for (int i = 0; i < 3; i++) asm volatile("ld.volatile.global.u32 %0, [%1];" : "=r"(cv[i]) : "l"(reinterpret_cast<const uint32_t*>(prm.c) + (warp - 1) * 96 + i * 32 + lane) : "memory");
  };
  if (warp < 4 && warp > 0 && b < 72) {
    if (CL == 0) ld_c();
    if (lane == 0) {
      mbar_init(sBar + B_X1 + warp * 8, 1);
      asm volatile("fence.mbarrier_init.release.cluster;" ::: "memory");
      tma_load_2d(sb + SM_STG + (warp - 1) * 6144, &mM, sBar + B_X1 + warp * 8, b * 16, (warp - 1) * 192);
      mbar_expect_tx(sBar + B_X1 + warp * 8, 6144);
    }
    if (CL == 2) { __syncwarp(); ld_c(); }
  }
  if (tid == 0) {
    if (TMP) asm volatile("prefetch.tensormap [%0];" ::"l"(&mX) : "memory");
    mbar_init(sBar + B_X, 1);
    mbar_init(sBar + B_X1, 1);
#pragma unroll
    for (int i = 0; i < __builtin_popcount(MM); i++) mbar_init(sBar + B_MM + i * 8, 1);
    asm volatile("fence.mbarrier_init.release.cluster;" ::: "memory");
  }
  __syncwarp();
  ECLK(e1);
  CL_ARRIVE();
  ECLK(e2);
  if (warp < 4) asm volatile("setmaxnreg.dec.sync.aligned.u32 40;");
  if (warp == 0) {
    CL_WAIT();
    ECLK(e3);
    CL_ARRIVE();
    bar_sync(9, 288);
    if (lane == 0) {
      if (XD) delay(XD);
      tma_load_3d_mc(sb + rank * (QG / 2), &mX, sBar + B_X, 0, qt * 128 + rank * 32, 0);
      mbar_expect_tx(sBar + B_X, QG);
      if (!XO) {
        if (XD1) delay(XD1);
        tma_load_3d_mc(sb + QG + rank * (QG / 2), &mX, sBar + B_X1, 0, qt * 128 + 64 + rank * 32, 0);
        mbar_expect_tx(sBar + B_X1, QG);
      }
    }
    __syncwarp();
    ECLK(e4);
  } else if (warp < 4) {
    ECLK(e3);
    if (b < 72) {
      if (CL == 1) ld_c();
      const int g = lane >> 2, t4 = lane & 3;
      uint32_t se[3] = {0u, 0u, 0u}, so[3] = {0u, 0u, 0u};
#pragma unroll 1
      for (int live = !MWARM; live < 2; live++) {
        if (live) {
#pragma unroll
          for (int i = 0; i < 3; i++) {
            const uint32_t u = __shfl_sync(~0u, cv[i], lane);
            const uint32_t v = pack_bf16(silu_f(bf_lo(u)), silu_f(bf_hi(u)));
            se[i] = (g & 1) ? 0u : v; so[i] = (g & 1) ? v : 0u;
          }
          ECLK(e4);
          mbar_wait(sBar + B_X1 + warp * 8, 0);
          ES(32, 0, 93);
        }
        float a[4][4];
#pragma unroll
        for (int i = 0; i < 16; i++) a[i >> 2][i & 3] = 0.f;
        const uint32_t la = sb + SM_STG + ((lane >> 3) & 1) * 16 + ((warp - 1) * 192 + (lane & 7) + (lane >> 4) * 8) * 32;
#pragma unroll
        for (int i = 0; i < 12; i++) {
          uint32_t w[4];
          ldsm4t(w, la + i * 512);
          mma16816(a[i & 3], w[0], w[1], w[2], w[3], se[i >> 2], so[i >> 2]);
        }
        float v0 = (t4 & 2) ? ((t4 & 1) ? a[3][0] + a[3][1] : a[2][0] + a[2][1]) : ((t4 & 1) ? a[1][0] + a[1][1] : a[0][0] + a[0][1]);
        float v1 = (t4 & 2) ? ((t4 & 1) ? a[3][2] + a[3][3] : a[2][2] + a[2][3]) : ((t4 & 1) ? a[1][2] + a[1][3] : a[0][2] + a[0][3]);
        float* const red = reinterpret_cast<float*>(smem_raw + SM_MT + 2560 + live * 768);
        red[g * 12 + (warp - 1) * 4 + t4] = v0;
        red[g * 12 + 96 + (warp - 1) * 4 + t4] = v1;
        ES(32, 0, 94);
        bar_sync(6, 96);
        const float4* rp = reinterpret_cast<const float4*>(red + (lane & 7) * 24);
        const float4 x0 = rp[0], x1 = rp[1], x2 = rp[2], y0 = rp[3], y1 = rp[4], y2 = rp[5];
        uint32_t w = pack_bf16((((x0.x + x0.y) + (x0.z + x0.w)) + ((x1.x + x1.y) + (x1.z + x1.w))) + ((x2.x + x2.y) + (x2.z + x2.w)),
                               (((y0.x + y0.y) + (y0.z + y0.w)) + ((y1.x + y1.y) + (y1.z + y1.w))) + ((y2.x + y2.y) + (y2.z + y2.w)));
        if (b >= 36) w = hadd2(w, 0x3f803f80u);
        if (live && tid < 96)
          asm volatile("st.relaxed.gpu.global.u32 [%0], %1;" ::"l"(reinterpret_cast<uint32_t*>(prm.mod1) + ((tid - 32) >> 3) * 576 + b * 8 + (lane & 7)), "r"(~w) : "memory");
      }
    } else if (PD) delay(PD);
    ES(32, 0, 89);
    CL_WAIT();
    CL_ARRIVE();
    CL_WAIT();
    if (lane == 0) mbar_arrive(sBar + B_M);
    if (tid < 104) {
      uint4 v, w;
      if (PW) mbar_wait(sBar + B_X, 0);
      bool ok = false;
#pragma unroll 1
      for (int i = 0; i < __builtin_popcount(MM) && !ok; i++) {
        mbar_wait(sBar + B_MM + i * 8, 0);
        v = lds128(sb + SM_MB + (tid - 32) * 16);
        w = lds128(sb + SM_MB + (tid + 40) * 16);
        ok = v.x && v.y && v.z && v.w && w.x && w.y && w.z && w.w;
      }
      if (!ok) poll8(prm.mod1 + (b & 7) * 144 + tid - 32, prm.mod1 + (b & 7) * 144 + tid + 40, v, w);
      uint2* const mt = reinterpret_cast<uint2*>(smem_raw + SM_MT) + ((tid - 32) >> 1) * 8 + (tid & 1);
      mt[0] = make_uint2(~v.x, ~w.x); mt[2] = make_uint2(~v.y, ~w.y); mt[4] = make_uint2(~v.z, ~w.z); mt[6] = make_uint2(~v.w, ~w.w);
    }
    __syncwarp();
    ES(32, 0, 92);
    bar_arrive(3, 224);
    bar_arrive(4, 224);
    if (lane == 0) mbar_arrive(sBar + B_M + 8);
  } else {
    if (lane == 0) {
      if (MPF && warp < 10 && b < 96) bulk_prefetch(prm.w_mod + (size_t)(b * 6 + warp - 4) * (6 * DM), 2 * DM * 2);
      const int c0 = warp < 9 ? 1 : 8, c1 = warp < 11 ? c0 : 16, c2 = warp < 11 ? c0 : 3;
#pragma unroll
      for (int j = 0; j < 7; j++) mbar_init(sBar + (warp - 4) * 56 + j * 8, j == 0 ? c0 : j < 5 ? c1 : c2);
      *reinterpret_cast<uint4*>(smem_raw + SM_ZERO) = make_uint4(0u, 0u, 0u, 0u);
      asm volatile("fence.mbarrier_init.release.cluster;" ::: "memory");
    }
    __syncwarp();
    CL_WAIT();
    CL_ARRIVE();
    bar_sync(9, 288);
  }
  if (warp < 4) {
    auto ffn_box = [&](int fb) {
      tma_load_2d(sb + (fb == 5 || fb == 6 ? -57600 : SM_WG) + fb * 11520, fb >= 4 ? &mWu : &mWg, sBar + B_FFN, (b * 36) & ~7, (fb & 3) * 144);
    };
    if (__shfl_sync(~0u, tid, 0) == 0) {
     if (lane == 0) {
      const uint64_t pol = pol_first();
      auto kv_load = [&](int t) {
        const int s = t & 3;
        mbar_wait(sBar + B_EMPTYA + s * 8, (t >> 2) & 1);
        mbar_expect_tx(sBar + B_FULLA + s * 8, 32768);
        if (EF & 1) tma_load_2d_mc_h(sb + s * 32768 + rank * 16384, (t & 1) ? &mV : &mK, sBar + B_FULLA + s * 8, rank * 64, kg * 4 * SK + (t >> 1) * 128, pol);
        else tma_load_2d_mc(sb + s * 32768 + rank * 16384, (t & 1) ? &mV : &mK, sBar + B_FULLA + s * 8, rank * 64, kg * 4 * SK + (t >> 1) * 128);
      };
#pragma unroll 1
      for (int i = 0, g = 2; i < 28; i++) {
        const int hh = (i >> 2) + 2 + (i >= 20);
        if (XO && i == XO) {
          tma_load_3d_mc(sb + QG + rank * (QG / 2), &mX, sBar + B_X1, 0, qt * 128 + 64 + rank * 32, 0);
          mbar_expect_tx(sBar + B_X1, QG);
        }
        if (XW && i == XW - 1) mbar_wait(sBar + B_X, 0);
        if (i < 7 && ((MM >> i) & 1)) {
          const uint32_t mb = sBar + B_MM + __popc(MM & ((1 << i) - 1)) * 8;
          bulk_load(sb + SM_MB, prm.mod1 + (b & 7) * 144, 2304, mb);
          mbar_expect_tx(mb, 2304);
        }
        if (i == 3) mbar_wait(sBar + B_M, 0);
        if (i == QTH) mbar_wait(sBar + B_M + 8, 0);
        if (!(i & 3)) {
          if (i) mbar_wait(sBar + B_EMPTYQ + g * 8, i >= 16);
          else if (QW) mbar_wait(sBar + B_X, 0);
          mbar_expect_tx(sBar + B_FULLQ + g * 8, QG);
        }
        if (EF & 2) tma_load_2d_h(sb + g * QG + (i & 3) * 18432, &mWq, sBar + B_FULLQ + g * 8, hcol + (hh & 6) * 128 + (hh & 1) * 64, (i & 3) * 144, pol);
        else tma_load_2d(sb + g * QG + (i & 3) * 18432, &mWq, sBar + B_FULLQ + g * 8, hcol + (hh & 6) * 128 + (hh & 1) * 64, (i & 3) * 144);
        if ((i & 3) == 3 && ++g == 3) g = 0;
      }
#pragma unroll 1
      for (int u = 0; u < 128; u++) kv_load(u < 5 || u == 127 ? u : (u & 1) ? u + 1 : u - 1);
      mbar_wait(sBar + B_X, 1);
      {
        mbar_expect_tx(sBar + B_FFN, 2 * DM * 80);
        mbar_expect_tx(sBar + B_FD, 9 * 5120);
#pragma unroll 1
        for (int i = 0; i < 18; i++) {
          const int g = i & 3;
          mbar_wait(sBar + (i < 4 ? B_EMPTYA : B_EMPTYO) + g * 8, i >= 8 && !(i & 4));
          KSTAMP(270 + i);
          mbar_expect_tx(sBar + B_FULLO + g * 8, 32768);
          tma_load_4d_h(sb + g * 32768, &mWo, sBar + B_FULLO + g * 8, (i >> 1) * 64, 0, rank, kg * 4 + (i & 1) * 2, pol);
        }
        mbar_expect_tx(sBar + B_XR, 16 * 1152);
      }
     }
     __syncwarp();
     CL_WAIT();
     {
        const int lane = get_lane();
        mbar_wait(sBar + B_EMPTYO + 16, 1);
        if (lane < 16) bulk_load(sb + SM_X2 + lane * 1168, prm.x + (size_t)(qt * 128 + hg * 16 + lane) * DM, 1152, sBar + B_XR);
        __syncwarp();
        if (lane == 0) {
          mbar_wait(sBar + B_EMPTYO + 24, 1);
          if (LATEG & 4) mbar_wait(sBar + B_G1, 0);
          tma_load_3d(sb + SM_WD, &mWd, sBar + B_FD, 0, b * 36, 0);
          mbar_wait(sBar + B_EMPTYO, 0);
          if (LATEG & 2) mbar_wait(sBar + B_G1, 0);
          ffn_box(5); ffn_box(6);
        }
      }
    } else if (warp == 3) {
#pragma unroll 1
      for (int i = 1, g = 0; i < 7; i++) {
        mbar_wait(sBar + B_FULLQ + g * 8, i >= 3 && i < 6);
        if (++g == 3) g = 0;
        if (i == 0) { ES(96, 0, 9); } else { KSTAMP(170 + i * 2); } bar_sync(1, 288); if (i == 0) { ES(96, 0, 10); } else { KSTAMP(171 + i * 2); }
      }
      long long nxt = 0;
#pragma unroll 1
      for (int u = 0; u < 128; u++) {
        const int t = (u == 0 || u == 127) ? u : (u & 1) ? u + 1 : u - 1;
        mbar_wait(sBar + B_FULLA + (t & 3) * 8, (t >> 2) & 1);
        if (t == 94) mbar_wait(sBar + B_QH, 0);
        if (!(t & 3)) *reinterpret_cast<volatile uint32_t*>(smem_raw + SM_ZERO + 12) = t >> 2;
        if (!(t & 1) || t == 127) { KSTAMP((t + 1) & ~1);
          bar_sync(1, 288); KSTAMP(((t + 1) & ~1) + 1); }
        else { bar_sync(10, 160); }
      }
      if (lane < 2) mbar_expect_tx(sBar + B_XF + lane * 8, 8192);
#pragma unroll 1
      for (int i = 0; i < 18; i++) {
        mbar_wait(sBar + B_FULLO + (i & 3) * 8, (i >> 2) & 1);
        KSTAMP(190 + i);
        if ((i & 1) && i > 1 && i < 17) {
          const uint32_t xf = sBar + B_XF + ((i - 2) & 2) * 4;
          KSTAMP(260 + (i >> 1));
          mbar_wait(xf, ((i - 2) >> 2) & 1);
          __syncwarp();
          if (lane == 0) mbar_expect_tx(xf, 8192);
        }
        KSTAMP(130 + i * 2);
        if (MG && i == 0) bar_sync(10, 160); else bar_sync(1, 288);
        KSTAMP(131 + i * 2);
      }
    } else if (warp > 0) {
      const int st = tid - 32;
      mbar_wait(sBar + B_FULLQ + 16, 0);
      mbar_wait(sBar + B_FULLQ + 16, 1);
      const bf16* const kvp = (rank ? prm.v : prm.k) + ((size_t)kg * 4 * SK + qt * 128) * DH;
      if (st == 0) bulk_prefetch(kvp, 32768);
      mbar_wait(sBar + B_FULLA, 0);
      mbar_wait(sBar + B_FULLA, 1);
      if (warp == 1) {
#pragma unroll 1
        for (int grp = b < 72 ? b : 288; grp < 288; grp += 72) {
          float a[8];
#pragma unroll
          for (int i = 0; i < 8; i++) a[i] = 0.f;
#pragma unroll 2
          for (int r = lane; r < DM; r += 32) {
            uint4 v;
            if (EF & 16) asm("ld.global.nc.L2::cache_hint.v4.u32 {%0,%1,%2,%3}, [%4], %5;" : "=r"(v.x), "=r"(v.y), "=r"(v.z), "=r"(v.w) : "l"(prm.w_mod + (size_t)r * (6 * DM) + 2 * DM + grp * 8), "l"(pol_first()));
            else v = __ldg(reinterpret_cast<const uint4*>(prm.w_mod + (size_t)r * (6 * DM) + 2 * DM + grp * 8));
            float s = silu_bf(__bfloat162float(prm.c[r]));
            a[0] += s * bf_lo(v.x); a[1] += s * bf_hi(v.x); a[2] += s * bf_lo(v.y); a[3] += s * bf_hi(v.y);
            a[4] += s * bf_lo(v.z); a[5] += s * bf_hi(v.z); a[6] += s * bf_lo(v.w); a[7] += s * bf_hi(v.w);
          }
#pragma unroll
          for (int i = 0; i < 8; i++) a[i] = warp_sum(a[i]);
          if (lane == 0) {
            const int kind = grp / 72;
#pragma unroll
            for (int i = 0; i < 4; i++) {
              uint32_t w = pack_bf16(a[2 * i], a[2 * i + 1]);
              if (kind == 2) w = hadd2(w, 0x3f803f80u);
              reinterpret_cast<uint32_t*>(smem_raw + SM_M2)[i * 4 + kind] = w;
            }
            if (kind == 3) {
              fence_async();
              asm volatile("cp.async.bulk.global.shared::cta.bulk_group [%0], [%1], 64;" ::"l"(g_mod2 + b * 4), "r"(sb + SM_M2) : "memory");
              asm volatile("cp.async.bulk.commit_group;\ncp.async.bulk.wait_group 0;" ::: "memory");
              if (SIDEF & 1) asm volatile("fence.acq_rel.gpu;" ::: "memory");
              cnt_arrive(C_SIDE);
            }
          }
        }
        __syncwarp();
        bar_sync(8, 160);
        if (lane < 8) asm volatile("red.relaxed.gpu.global.add.u32 [%0], 1;" ::"l"(&g_cnt[(C_Q + qt * 8 + lane) * 32 + 1]) : "memory");
        PSTAMP(32, 56);
        const int lane = get_lane();
        PSTAMP(32, 57);
        cnt_wait1((C_Q + qt * 8 + hg) * 32 + 1, 8);
        PSTAMP(32, 59);
        if (lane == 0) mbar_arrive(sBar + B_G2);
        uint32_t k1 = ~0u, k2 = ~0u;
        uint4 hv[4];
        uint2 hw = make_uint2(0u, 0u);
        auto h_load = [&]() {
          const int r1 = k1 & (SQ - 1), r2 = k2 & (SQ - 1);
          const int r = lane < 16 ? r1 : r2;
          const int c = ((r >> 5) & 3) * 32 + (r >> 7) * 2 + ((r >> 4) & 1);
          const uint4* p = g_ones + F_HX + (c * 288 + (lane >= 16 && (r1 >> 4) == (r2 >> 4) ? 144 : 0) + (lane & 15));
#pragma unroll
          for (int i = 0; i < 4; i++) hv[i] = ldr4(p + i * 16);
          hw = ldr2(reinterpret_cast<const uint2*>(p + 64) - (lane & 15));
        };
#pragma unroll
        for (int i = 0; i < 4; i++) hv[i] = make_uint4(0u, 0u, 0u, 0u);
        const uint4* kp = g_ones + F_KEY + (b & 31) * 64 + lane * 2;
        auto merge = [](uint32_t& m1, uint32_t& m2, uint32_t n1, uint32_t n2) { m2 = min(max(m1, n1), min(m2, n2)); m1 = min(m1, n1); };
#pragma unroll 1
        for (uint32_t n = 0;; n++) {
          uint4 a, c;
          asm volatile("ld.relaxed.gpu.global.v4.u32 {%0,%1,%2,%3}, [%8];\nld.relaxed.gpu.global.v4.u32 {%4,%5,%6,%7}, [%8+16];"
                       : "=r"(a.x), "=r"(a.y), "=r"(a.z), "=r"(a.w), "=r"(c.x), "=r"(c.y), "=r"(c.z), "=r"(c.w) : "l"(kp) : "memory");
          const bool all = !__any_sync(~0u, unset(a) || unset(c));
          merge(a.x, a.y, a.z, a.w);
          merge(a.x, a.y, c.x, c.y);
          merge(a.x, a.y, c.z, c.w);
          const uint32_t m1 = __reduce_min_sync(~0u, a.x);
          const uint32_t m2 = __reduce_min_sync(~0u, a.x == m1 ? a.y : a.x);
          bool bad = m1 != k1 || m2 != k2 || hw.x == ~0u || hw.y == ~0u;
#pragma unroll
          for (int i = 0; i < 4; i++) bad |= unset(hv[i]);
          bad = __any_sync(~0u, bad);
          if (all && !bad) break;
          if (n > (1u << 15)) { SETERR(4); break; }
          if (bad) { k1 = m1; k2 = m2; h_load(); }
        }
        PSTAMP(32, 60);
        {
          const uint32_t ha = sb + SM_T + T_H + (lane >> 4) * 1152 + (lane & 15) * 16;
#pragma unroll
          for (int i = 0; i < 4; i++) sts128(ha + i * 256, hv[i]);
          asm volatile("st.shared.v2.b32 [%0], {%1,%2};" ::"r"(ha + 1024 - (lane & 15) * 8), "r"(hw.x), "r"(hw.y) : "memory");
        }
        if (lane == 0) asm volatile("st.shared.v2.b32 [%0], {%1,%2};" ::"r"(sb + SM_T + 128), "r"(~k1), "r"(~k2) : "memory");
        __syncwarp();
        if (lane == 0) mbar_arrive(sBar + B_G3);
        PSTAMP(32, 61);
      } else {
#pragma unroll
        for (int i = 0; i < 4; i++) sts128(sb + SM_FILL + i * 512 + lane * 16, make_uint4(~0u, ~0u, ~0u, ~0u));
        fence_async();
        __syncwarp();
        const int lane = get_lane();
        const uint32_t dump = sb + SM_RED + 64 + lane * 4;
        auto touch128 = [&](const void* q) { asm volatile("cp.async.ca.shared.global.L2::128B [%0], [%1], 4;" ::"r"(dump), "l"(q) : "memory"); };
        auto touch256 = [&](const void* q) { asm volatile("cp.async.ca.shared.global.L2::256B [%0], [%1], 4;" ::"r"(dump), "l"(q) : "memory"); };
#pragma unroll 1
        for (int p = 2; p < FILLP; p++) {
          if (*reinterpret_cast<volatile uint32_t*>(smem_raw + SM_ZERO + 12) < p) mbar_wait(sBar + B_FULLA, p & 1);
          if (lane == 0) {
            if ((p & 7) == 3 && p < 24) bulk_prefetch(kvp + (size_t)((p >> 3) + 1) * SK * DH, 32768);
            if (p == 16 + QPF) {
              cnt_wait1((C_Q + b) * 32 + 2, 8);
              asm volatile("fence.acq_rel.gpu;" ::: "memory");
              mbar_arrive(sBar + B_QH);
            }
            if (!(TCH & 2) && (p & 7) == QPF && p < 24) bulk_prefetch(g_q + ((size_t)b * 4 + (p >> 3) + 1) * 2048, 32768);
            if (!(TCH & 4) && p == FILLP - 1) bulk_prefetch(prm.x + (size_t)(qt * 128 + hg * 16) * DM, 16 * DM * 2);
            if (p == WOP) bulk_prefetch(prm.wo + ((size_t)kg * 1024 + (b & 31) * 32) * DM, 32 * DM * 2);
            if (p >= PF0 && p < PF0 + 9) {
              const int i = p - PF0, m = PFO ? 2 - i / 3 : i / 3;
              bulk_prefetch((m == 0 ? prm.wg : m == 1 ? prm.wu : prm.wd) + (size_t)(b * 3 + i % 3) * (DM * 12), DM * 24);
            }
          }
          __syncwarp();
          if ((TCH & 2) && (p & 7) == QPF && p < 24) {
#pragma unroll
            for (int i = 0; i < 4; i++) touch256(g_q + ((size_t)b * 4 + (p >> 3) + 1) * 2048 + (i * 32 + lane) * 16);
          }
          if ((TCH & 1) && p >= TF0 && p < TF0 + 9) {
            const int i = p - TF0, c0 = (b * 36) & ~7;
#pragma unroll
            for (int j = 0; j < (FAKEB ? 0 : 4); j++) {
              const int r = i * 64 + (j & 1) * 32 + lane;
              const bf16* q = ((j & 2) ? prm.wu : prm.wg) + (size_t)r * FF + c0;
              touch128(q);
              if ((c0 & 63) > 24) touch128(q + 38);
            }
            if (lane < 20) touch256(prm.wd + min(b * 162 + i * 20 + lane, 128 * 162 - 1) * 128);
          }
          if ((TCH & 16) && p >= TF0 && p < TF0 + 9 / TN) {
            const int i = (p - TF0) * TN, c0 = (b * 36) & ~7;
#pragma unroll
            for (int j = 0; j < TN; j++) {
              const bf16* q = prm.wu + (size_t)(144 + (i + j) * 32 + lane) * FF + c0;
              touch128(q);
              if ((c0 & 63) > 24) touch128(q + 38);
              if (lane < 20) touch256(prm.wd + min(b * 162 + (i + j) * 20 + lane, 128 * 162 - 1) * 128);
            }
          }
          if ((TCH & 4) && p >= FILLP - 3 && lane < 24) touch256(prm.x + (size_t)(qt * 128 + hg * 16) * DM + ((p - FILLP + 3) * 24 + lane) * 128);
          if ((TCH & 8) && p >= TW0 && p < TW0 + TWN) {
            const int i = (qt * TWN + p - TW0) * 144 % 2304;
#pragma unroll
            for (int j = 0; j < 5; j++)
              if (j < 4 || lane < 16) touch256(prm.wo + (size_t)(hcol + i / 576 * 256) * DM + (i % 576 + j * 32 + lane) * 128);
          }
          if (p >= FILL0)
#pragma unroll 1
          for (int z = 0; z < (FGAP ? FGN : 1); z++) {
            if (FGAP && z) __nanosleep(FGAP);
            const int i = lane >= 16 ? lane - 16 : (p - FILL0) * FILLN + lane + 5;
            if ((lane >= 16 ? p == FILLS && i < 5 : lane < FILLN && i < FILLMAX) && (!FGAP || (lane & (FGN - 1)) == z)) {
              uint4* const fp = g_ones + (i < 5 ? b * 640 : F_PART - 640 + b * 5120) + i * 128;
              if (EF & 32) asm volatile("cp.async.bulk.global.shared::cta.bulk_group.L2::cache_hint [%0], [%1], 2048, %2;" ::"l"(fp), "r"(sb + SM_FILL), "l"(pol_first()) : "memory");
              else asm volatile("cp.async.bulk.global.shared::cta.bulk_group [%0], [%1], 2048;" ::"l"(fp), "r"(sb + SM_FILL) : "memory");
            }
          }
        }
        asm volatile("cp.async.bulk.commit_group;\ncp.async.bulk.wait_group 0;" ::: "memory");
        if (SIDEF & 2) asm volatile("fence.acq_rel.gpu;" ::: "memory");
        __syncwarp();
        PSTAMP(64, 51);
        if (lane == 0) {
          cnt_arrive(C_SIDE);
          PSTAMP(64, 52);
          cnt_wait(C_SIDE, 128 + 72);
          PSTAMP(64, 53);
          asm volatile("mbarrier.arrive.shared::cta.b64 _, [%0];" ::"r"(sBar + B_X) : "memory");
        }
        __syncwarp();
        if (lane == 0) {
          asm volatile("prefetch.tensormap [%0];\nprefetch.tensormap [%1];\nprefetch.tensormap [%2];\nprefetch.tensormap [%3];" ::"l"(&mWo), "l"(&mWg), "l"(&mWu), "l"(&mWd) : "memory");
          mbar_wait(sBar + B_ST, 0);
          mbar_expect_tx(sBar + B_MD, 5760);
          bulk_load(sb + SM_MD, g_mod2, 4608, sBar + B_MD);
          bulk_load(sb + SM_MD + 4608, prm.w_r, 1152, sBar + B_MD);
        }
        __syncwarp();
        {
          mbar_wait(sBar + B_MD, 0);
          float sA = 0.f, sB = 0.f;
#pragma unroll 1
          for (int i = lane; i < 288; i += 32) {
            const uint4 m = lds128(sb + SM_MD + i * 16);
            const uint32_t w = *reinterpret_cast<const uint32_t*>(smem_raw + SM_MD + 4608 + i * 4);
            const float a0 = bf_lo(m.z) * bf_lo(w), a1 = bf_hi(m.z) * bf_hi(w);
            const uint32_t hi = pack_bf16(a0, a1);
            *reinterpret_cast<uint2*>(smem_raw + SM_MOD + i * 8) = make_uint2(pack_bf16(a0 - bf_lo(hi), a1 - bf_hi(hi)), hi);
            sA += a0 + a1;
            sB = fmaf(bf_lo(m.y), bf_lo(w), fmaf(bf_hi(m.y), bf_hi(w), sB));
          }
          sA = warp_sum(sA); sB = warp_sum(sB);
          *reinterpret_cast<float2*>(smem_raw + SM_ZERO + 16) = make_float2(sA, sB);
          __syncwarp();
          if (lane == 0) mbar_arrive(sBar + B_TB);
        }
        if (lane == 0) {
#pragma unroll 1
          for (int r = 0, fb = 0; r < 4; r++) {
#pragma unroll 1
            for (const int fe = (FFNS >> (r * 4)) & 15; fb < fe; fb++) ffn_box(fb == 5 ? 7 : fb);
            if (r < 3) mbar_wait(sBar + B_EMPTYO + 16, r & 1);
          }
        }
        __syncwarp();
        const uint32_t* const tsu = reinterpret_cast<const uint32_t*>(smem_raw + SM_T);
        const int row = qt * 128 + hg * 16 + lane;
        auto out_row = [&]() {
          asm volatile("cp.async.bulk.global.shared::cta.bulk_group [%0], [%1], 1152;" ::"l"(prm.out + (size_t)row * DM), "r"(sb + SM_X2 + lane * 1168) : "memory");
        };
        bar_sync(11, 288);
        fence_async();
        const bool top = (*(volatile const uint32_t*)(tsu + 34) >> lane) & 1;
        if (lane < 16 && !top) out_row();
        mbar_wait(sBar + B_G3, 0);
        if (top && row != (int)(~*(volatile const uint32_t*)(tsu + 32) & (SQ - 1)) && row != (int)(~*(volatile const uint32_t*)(tsu + 33) & (SQ - 1))) out_row();
        asm volatile("cp.async.bulk.commit_group;\ncp.async.bulk.wait_group.read 0;" ::: "memory");
      }
    }
  } else {
    const int cw = (warp >> 2) - 1;
    const int w8 = warp - 4;
    const int ct = tid - 128;
    const int lane = get_lane(), g = lane >> 2, t4 = lane & 3;
    uint32_t relBar;
    auto release = [&](int off) {
      if (lane < 2) mbar_arrive_cl(relBar + off);
    };
    auto release1 = [&](int off) {
      if (lane == 0) mbar_arrive_cl(relBar + off);
    };
    auto turn_begin = [&]() {
      asm volatile("{\n.reg .pred p;\nsetp.eq.b32 p, %0, 0;\n@p bar.sync 1, 288;\n@!p bar.sync 2, 256;\n}\n" ::"r"(cw) : "memory");
      wgmma_fence();
    };
    auto turn_end = [&]() { asm volatile("{\n.reg .pred p;\nsetp.eq.b32 p, %0, 0;\n@p bar.arrive 2, 256;\n@!p bar.arrive 1, 288;\n}\n" ::"r"(cw) : "memory"); };
    asm volatile("{\n.reg .pred p;\nsetp.eq.u64 p, %0, 0;\n@p trap;\n}\n" :: "l"(g_q) : "memory");
    ESC(7);
    asm volatile("setmaxnreg.inc.sync.aligned.u32 232;");
    float S[64], O[64];
    uint32_t P[32], Qf[32];
    constexpr uint32_t dB_k = mk_desc(SM_BASE, 16);
    constexpr uint32_t dB_n16 = mk_desc(SM_BASE, 16384);
    uint4* qpark;
    {
      uint32_t A[144];
      const uint32_t la = sb + cw * QG + (w8 & 2) * (QG / 4) + ((w8 & 1) * 16 + ((lane & 15) ^ (rank * 8))) * 128 + (((lane >> 4) ^ (lane & 7)) << 4);
      ESC(19);
      mbar_wait(sBar + B_X + cw * 8, 0);
      ESC(1);
      ln_rows(A, la, lane, [&]() { if (lane < 2) mbar_arrive(sBar + B_EMPTYQ + cw * 8); });
      CL_WAIT();
      ESC(2);
      bar_sync(3 + cw, 224);
      ESC(3);
      modulate(A, sb + SM_MT + t4 * 16);
      ESC(4);
      float qa[32];
      asm volatile("mapa.shared::cluster.u32 %0, %1, %2;" : "=r"(relBar) : "r"(sBar), "r"(rank ^ (get_lane() & 1)));
      qpark = g_q + (b * (4 * 8 * 256) + w8 * 32 + get_lane());
      if (cw == 0) { mbar_wait(sBar + B_FULLQ + 16, 0); ESC(9); }
#pragma unroll 1
      for (int hh = 2, gr = 2;; hh++) {
        asm volatile("{\n.reg .pred p, q;\nsetp.eq.b32 p, %0, 0;\nsetp.gt.and.s32 q, %1, 2, p;\n@q bar.sync 1, 288;\n@!p bar.sync 2, 256;\n}\n" ::"r"(cw), "r"(hh) : "memory");
        wgmma_fence();
        q_mma(qa, A, dB_k + gr * (QG >> 4));
        turn_end();
        wgmma_wait<0>();
        if (hh < 6) release1(B_EMPTYQ + gr * 8);
        else if (hh < 9) { release(B_EMPTYA + gr * 16); release(B_EMPTYA + gr * 16 + 8); }
        if (++gr == 3) gr = 0;
#pragma unroll
        for (int j = 0; j < 32; j++) qa[j] *= Q_SCALE;
#pragma unroll
        for (int j = 0; j < 4; j++)
          qpark[((hh & 7) * 4 + j) * 256] = make_uint4(pack_bf16(qa[8 * j], qa[8 * j + 1]), pack_bf16(qa[8 * j + 2], qa[8 * j + 3]),
                                                       pack_bf16(qa[8 * j + 4], qa[8 * j + 5]), pack_bf16(qa[8 * j + 6], qa[8 * j + 7]));
        if (hh == 9) break;
        if (hh == 6) hh++;
      }
#pragma unroll
      for (int j = 0; j < 4; j++) {
        const uint4 v = __ldcg(qpark + j * 256);
        Qf[4 * j] = v.x; Qf[4 * j + 1] = v.y; Qf[4 * j + 2] = v.z; Qf[4 * j + 3] = v.w;
      }
#pragma unroll
      for (int j = 0; j < 16; j++) Qf[16 + j] = pack_bf16(qa[2 * j], qa[2 * j + 1]);
    }
    STAMP(5); GSTAMP(65); STAMP(0); GSTAMP(90);
    float mb0 = 0.f, mb1 = 0.f, l0 = 0.f, l1 = 0.f;
    int nz = 0;
    float i0 = 0.f, i1 = 0.f;
    auto o_scale = [&]() {
      float a0 = l0, a1 = l1;
      a0 += __shfl_xor_sync(~0u, a0, 1); a0 += __shfl_xor_sync(~0u, a0, 2);
      a1 += __shfl_xor_sync(~0u, a1, 1); a1 += __shfl_xor_sync(~0u, a1, 2);
      i0 = rcp(a0); i1 = rcp(a1);
    };
    auto o_frag = [&](int i) {
      return make_uint4(pack_bf16(O[i * 8] * i0, O[i * 8 + 1] * i0), pack_bf16(O[i * 8 + 2] * i1, O[i * 8 + 3] * i1),
                        pack_bf16(O[i * 8 + 4] * i0, O[i * 8 + 5] * i0), pack_bf16(O[i * 8 + 6] * i1, O[i * 8 + 7] * i1));
    };
    auto row_max = [&](float& x0, float& x1) {
      float y0 = fmaxf(S[0], S[1]), y1 = fmaxf(S[2], S[3]), z0 = fmaxf(S[4], S[5]), z1 = fmaxf(S[6], S[7]);
#pragma unroll
      for (int j = 2; j < 16; j += 2) {
        y0 = fmaxf(y0, fmaxf(S[j * 4], S[j * 4 + 1])); y1 = fmaxf(y1, fmaxf(S[j * 4 + 2], S[j * 4 + 3]));
        z0 = fmaxf(z0, fmaxf(S[j * 4 + 4], S[j * 4 + 5])); z1 = fmaxf(z1, fmaxf(S[j * 4 + 6], S[j * 4 + 7]));
      }
      x0 = fmaxf(y0, z0); x1 = fmaxf(y1, z1);
      x0 = fmaxf(x0, __shfl_xor_sync(~0u, x0, 1)); x1 = fmaxf(x1, __shfl_xor_sync(~0u, x1, 1));
      x0 = fmaxf(x0, __shfl_xor_sync(~0u, x0, 2)); x1 = fmaxf(x1, __shfl_xor_sync(~0u, x1, 2));
    };
    float s0, s1;
    auto shift = [&]() {
#pragma unroll
      for (int i = 0; i < 64; i++) S[i] -= (i & 2) ? mb1 : mb0;
    };
    auto exps = [&](int j0, int j1) {
#pragma unroll
      for (int j = j0; j < j1; j++) {
        S[j * 4] = ex2(S[j * 4]); S[j * 4 + 1] = ex2(S[j * 4 + 1]);
        S[j * 4 + 2] = ex2(S[j * 4 + 2]); S[j * 4 + 3] = ex2(S[j * 4 + 3]);
        if (HS == 0 || (HS == 2 && j < 8)) { s0 += S[j * 4] + S[j * 4 + 1]; s1 += S[j * 4 + 2] + S[j * 4 + 3]; }
      }
    };
    auto cvtP = [&]() {
#pragma unroll
      for (int i = 0; i < 32; i++) {
        if (HS & 1) asm volatile("cvt.rn.bf16x2.f32 %0, %1, %2;" : "=r"(P[i]) : "f"(S[2 * i + 1]), "f"(S[2 * i]));
        else P[i] = pack_bf16(S[2 * i], S[2 * i + 1]);
      }
      if (HS) {
        uint32_t t[16];
#pragma unroll
        for (int i = 0; i < 16; i++) t[i] = hadd2(P[(i >> 1) * 4 + (i & 1)], P[(i >> 1) * 4 + (i & 1) + 2]);
#pragma unroll
        for (int i = 0; i < 8; i++) t[i] = hadd2(t[(i >> 1) * 4 + (i & 1)], t[(i >> 1) * 4 + (i & 1) + 2]);
#pragma unroll
        for (int i = 0; i < 4; i++) t[i] = hadd2(t[(i >> 1) * 4 + (i & 1)], t[(i >> 1) * 4 + (i & 1) + 2]);
        if (HS == 1) {
          t[0] = hadd2(t[0], t[2]); t[1] = hadd2(t[1], t[3]);
          s0 = bf_lo(t[0]) + bf_hi(t[0]); s1 = bf_lo(t[1]) + bf_hi(t[1]);
        } else if (HS == 2) {
          s0 += bf_lo(t[2]) + bf_hi(t[2]); s1 += bf_lo(t[3]) + bf_hi(t[3]);
        } else {
          s0 = (bf_lo(t[0]) + bf_hi(t[0])) + (bf_lo(t[2]) + bf_hi(t[2])); s1 = (bf_lo(t[1]) + bf_hi(t[1])) + (bf_lo(t[3]) + bf_hi(t[3]));
        }
      }
    };
    auto issue_qk = [&](uint32_t db) {
#pragma unroll
      for (int kk = 0; kk < 8; kk++)
        wgmma128_rs<0>(S, Qf[kk * 4], Qf[kk * 4 + 1], Qf[kk * 4 + 2], Qf[kk * 4 + 3], db + (kk >> 2) * 1024 + (kk & 3) * 2, kk != 0);
    };
    auto issue_pv = [&](uint32_t db, int first) {
#pragma unroll
      for (int kk = 0; kk < 8; kk++) {
        if (kk == TE_POS) turn_end();
        wgmma128_rs<1>(O, P[kk * 4], P[kk * 4 + 1], P[kk * 4 + 2], P[kk * 4 + 3], db + kk * 128, kk ? 1 : !first);
      }
      wgmma_commit();
      if (TE_POS == 8) turn_end();
    };
    auto sched_fence = [&]() {
      if (HS & 1) asm volatile("st.shared.v2.f32 [%0], {%1,%2};" ::"r"(sb + SM_RED), "f"(S[EH * 4 - 2]), "f"(S[EH * 4 - 1]) : "memory");
      else asm volatile("st.shared.v2.f32 [%0], {%1,%2};" ::"r"(sb + SM_RED), "f"(s0), "f"(s1) : "memory");
    };
    {
      STAMP(6);
      turn_begin();
      issue_qk(dB_k);
      wgmma_commit();
      turn_end();
      wgmma_wait<0>();
      release(B_EMPTYA);
      bool redo = sb >> 31;
#pragma unroll 1
      do {
        if (__builtin_expect(redo, 0)) {
          row_max(mb0, mb1);
          shift();
          nz = 1;
        }
        l0 = 0.f; l1 = 0.f;
#pragma unroll
        for (int i = 0; i < 32; i++) {
          const float e0 = ex2(S[2 * i]), e1 = ex2(S[2 * i + 1]);
          P[i] = pack_bf16(e0, e1);
          if (i & 1) l1 += e0 + e1; else l0 += e0 + e1;
        }
        redo = __any_sync(~0u, !(l0 <= LAZY_LIMIT && l1 <= LAZY_LIMIT && l0 >= LAZY_LOW && l1 >= LAZY_LOW)) && !redo;
      } while (__builtin_expect(redo, 0));
    }
    const uint4* qn = qpark + 8 * 256;
    asm volatile("" : "+l"(qn));
    uint32_t kd = dB_k + 4096;
#pragma unroll 1
    for (int t = 1; t < 64; t++, kd ^= 4096) {
      const int j = t & 15, h = t >> 4;
      const int ks = (t & 1) * 2, vs = 3 - ks;
      turn_begin();
      issue_qk(kd);
      wgmma_commit();
      if (__builtin_expect(j == 1 && h, 0)) {
#pragma unroll
        for (int i = RS0; i < 8; i++) sts128(sb + SM_STASH + (h - 1) * 32768 + i * 4096 + ct * 16, o_frag(i));
        wgmma_fence();
      }
      if (cw == 0) bar_sync(10, 160);
      issue_pv(kd ^ (dB_k ^ (dB_n16 + 6144)), j == 1);
      wgmma_wait<1>();
      release(B_EMPTYA + ks * 8);
      if (j == 15 && h < 3) {
#pragma unroll
        for (int i = 0; i < 8; i++) {
          uint4 v;
          if (EF & 4) asm volatile("ld.global.cg.L2::cache_hint.v4.u32 {%0,%1,%2,%3}, [%4], %5;" : "=r"(v.x), "=r"(v.y), "=r"(v.z), "=r"(v.w) : "l"(qn + i * 256), "l"(pol_first()));
          else v = __ldcg(qn + i * 256);
          Qf[4 * i] = v.x; Qf[4 * i + 1] = v.y; Qf[4 * i + 2] = v.z; Qf[4 * i + 3] = v.w;
        }
        qn += 8 * 256;
      }
      if (__builtin_expect(nz, 0)) shift();
      s0 = 0.f; s1 = 0.f;
      exps(0, EH);
      sched_fence();
      wgmma_wait<0>();
      release(B_EMPTYA + vs * 8);
      float lo = 0.f;
      if (__builtin_expect(j == 0, 0)) {
        o_scale();
        l0 = 0.f; l1 = 0.f;
        lo = LAZY_LOW;
      }
#if !(HS & 1)
      bool bad = __any_sync(~0u, !(s0 <= LAZY_LIMIT && s1 <= LAZY_LIMIT));
#endif
      if (__builtin_expect(!bad, 1)) {
        exps(EH, 16);
        cvtP();
        bad = __any_sync(~0u, !(s0 <= LAZY_LIMIT && s1 <= LAZY_LIMIT && s0 >= lo && s1 >= lo));
      }
      if (__builtin_expect(bad, 0)) {
        const uint32_t* kp = reinterpret_cast<const uint32_t*>(prm.k + ((size_t)kg * 4 * SK + t * 128 + g) * DH) + t4;
        const uint4* qp = qpark + h * (8 * 256);
        float4 tmp[16];
        uint4 qf[8];
#pragma unroll
        for (int kk = 0; kk < 8; kk++) qf[kk] = __ldcg(qp + kk * 256);
#pragma unroll 1
        for (int jn = 0; jn < 16; jn++) {
          float c[4] = {0.f, 0.f, 0.f, 0.f};
#pragma unroll
          for (int kk = 0; kk < 8; kk++) mma16816(c, qf[kk].x, qf[kk].y, qf[kk].z, qf[kk].w, __ldg(kp + jn * 512 + kk * 8), __ldg(kp + jn * 512 + kk * 8 + 4));
          tmp[jn] = make_float4(c[0], c[1], c[2], c[3]);
        }
#pragma unroll
        for (int jn = 0; jn < 16; jn++) { const float4 c = tmp[jn]; S[jn * 4] = c.x; S[jn * 4 + 1] = c.y; S[jn * 4 + 2] = c.z; S[jn * 4 + 3] = c.w; }
        float x0, x1;
        row_max(x0, x1);
        const float n0 = j ? fmaxf(mb0, x0) : x0, n1 = j ? fmaxf(mb1, x1) : x1;
        const float f0 = j ? ex2(mb0 - n0) : 1.f, f1 = j ? ex2(mb1 - n1) : 1.f;
        mb0 = n0; mb1 = n1;
        l0 *= f0; l1 *= f1;
#pragma unroll
        for (int i = 0; i < 16; i++) { O[i * 4] *= f0; O[i * 4 + 1] *= f0; O[i * 4 + 2] *= f1; O[i * 4 + 3] *= f1; }
        s0 = 0.f; s1 = 0.f;
        shift();
        nz = 1;
        exps(0, 16);
        cvtP();
      }
      if (RS0 && __builtin_expect(j == 0, 0)) {
#pragma unroll
        for (int i = 0; i < RS0; i++) sts128(sb + SM_STASH + (h - 1) * 32768 + i * 4096 + ct * 16, o_frag(i));
      }
      l0 += s0; l1 += s1;
    }
    STAMP(70); GSTAMP(66);
    int nc = 0;
    uint32_t ra[7], rb[7], ld[16];
    const uint32_t* const ap = reinterpret_cast<const uint32_t*>(g_ones + F_PART) + (qt * 8 + hg) * 20480 + w8 * 32 + get_lane();
    auto ld_sum = [&](uint32_t& a, uint32_t& c, const uint32_t* w) {
      a = pack_bf16((bf_lo(w[0]) + bf_lo(w[2])) + (bf_lo(w[4]) + bf_lo(w[6])), (bf_hi(w[0]) + bf_hi(w[2])) + (bf_hi(w[4]) + bf_hi(w[6])));
      c = pack_bf16((bf_lo(w[1]) + bf_lo(w[3])) + (bf_lo(w[5]) + bf_lo(w[7])), (bf_hi(w[1]) + bf_hi(w[3])) + (bf_hi(w[5]) + bf_hi(w[7])));
    };
    {
      const int lane = get_lane();
      uint32_t A[128];
      float c0[32], kp[16];
      auto ld_a = [&](int i0, int i1) {
#pragma unroll
        for (int i = i0; i < i1; i++) {
          const uint4 v = lds128(sb + SM_STASH + i * 4096 + ct * 16);
          A[i * 4] = v.x; A[i * 4 + 1] = v.y; A[i * 4 + 2] = v.z; A[i * 4 + 3] = v.w;
        }
      };
      ld_a(MG == 2 ? 8 : 0, MGL);
      turn_begin();
#pragma unroll
      for (int kk = 0; kk < 8; kk++) wgmma128_rs<1>(O, P[kk * 4], P[kk * 4 + 1], P[kk * 4 + 2], P[kk * 4 + 3], dB_n16 + 6144 + kk * 128, 1);
      wgmma_commit();
      ld_a(MG == 2 && MGL < 8 ? 8 : MGL, 16);
      if (cw == 0) bar_sync(10, 160);
      wgmma_fence();
#pragma unroll
      for (int kk = 0; kk < 16; kk++) wgmma64_rs(c0, A[kk * 4], A[kk * 4 + 1], A[kk * 4 + 2], A[kk * 4 + 3], dB_k + kk * 128, kk != 0);
      wgmma_commit();
      turn_end();
      o_scale();
      wgmma_wait<1>();
#pragma unroll
      for (int i = 16; i < 24; i++) {
        const uint4 v = lds128(sb + SM_STASH + i * 4096 + ct * 16);
        A[i * 4] = v.x; A[i * 4 + 1] = v.y; A[i * 4 + 2] = v.z; A[i * 4 + 3] = v.w;
      }
#pragma unroll
      for (int i = 0; i < 8; i++) {
        const uint4 v = o_frag(i);
        A[96 + i * 4] = v.x; A[96 + i * 4 + 1] = v.y; A[96 + i * 4 + 2] = v.z; A[96 + i * 4 + 3] = v.w;
      }
      if (__any_sync(~0u, A[95] != 0x12345678u || A[64] != 0x9abcdef0u || lane == 0)) {
        release(B_EMPTYA + 24);
        release1(B_ST);
      }
      STAMP(71);
      uint32_t xb = w8 * 1024 + lane * 16;
      const uint32_t peer = __shfl_sync(~0u, relBar, 1) - sBar;
      int gr = MG ? 2 : 0;
      wgmma_wait<0>();
      release1(B_EMPTYO);
#pragma unroll
      for (int i = 0; i < 8; i++) ld[i] = ~0u;
#pragma unroll
      for (int i = 0; i < 5; i++) ra[i] = rb[i] = 0;
      auto ld_take = [&]() {
        uint32_t a, d;
        ld_sum(a, d, ld);
#pragma unroll
        for (int i = 0; i < 5; i++)
          if (nc == i) { ra[i] = a; rb[i] = d; }
        nc += !__any_sync(~0u, nan2(hadd2(a, d)));
      };
      uint32_t* dp = reinterpret_cast<uint32_t*>(g_ones + F_PART) + (qt * 8 + w8) * 20480 + kg * 512 + rank * 256 + lane;
      auto recv = [&]() {
        uint4 u[2];
#pragma unroll
        for (int j = 0; j < 2; j++) u[j] = lds128(sb + SM_XCH + xb + j * 512);
#pragma unroll
        for (int j = 0; j < 2; j++) {
          str1(dp + j * 128, pack_bf16(kp[j * 8] + bf_lo(u[j].x), kp[j * 8 + 1] + bf_hi(u[j].x)));
          str1(dp + j * 128 + 32, pack_bf16(kp[j * 8 + 2] + bf_lo(u[j].y), kp[j * 8 + 3] + bf_hi(u[j].y)));
          str1(dp + j * 128 + 64, pack_bf16(kp[j * 8 + 4] + bf_lo(u[j].z), kp[j * 8 + 5] + bf_hi(u[j].z)));
          str1(dp + j * 128 + 96, pack_bf16(kp[j * 8 + 6] + bf_lo(u[j].w), kp[j * 8 + 7] + bf_hi(u[j].w)));
        }
        dp += 2048;
        xb ^= 8192;
      };
#pragma unroll 1
      for (int c = 0;; c++) {
#pragma unroll
        for (int hd = 0; hd < 4; hd++) {
          if (MG && hd < 2 && c == 0) continue;
          if (!(hd & 1)) turn_begin();
          const uint32_t db = dB_k + (gr + (hd & 1)) * 1024;
#pragma unroll
          for (int kk = 0; kk < 8; kk++)
            wgmma64_rs(c0, A[hd * 32 + kk * 4], A[hd * 32 + kk * 4 + 1], A[hd * 32 + kk * 4 + 2], A[hd * 32 + kk * 4 + 3], db + kk * 128, (hd | kk) != 0);
          if (hd & 1) {
            wgmma_commit();
            if (hd == 1 || c < 8 || cw == 0) turn_end();
            if (hd == 1 ? c == 8 : (c & 7) != 0) {
              if (hd == 1) mbar_wait(sBar + B_XF + 8, 1);
              recv();
            }
            if (hd == 1 && c >= 3 && c < 8) {
              ld_take();
#pragma unroll
              for (int i = 0; i < 8; i++) ld[i] = ldr1(ap + nc * 2048 + i * 256);
            }
            if (hd == HINTH && c == 8 && cw == HINTW) bar_arrive(8, 160);
            if (hd == 3 && c == 8) {
              ld_take();
#pragma unroll
              for (int i = 0; i < 16; i++) ld[i] = ldr1(ap + 5 * 2048 + i * 256);
            }
            wgmma_wait<0>();
            release1(B_EMPTYO + gr * 4);
            gr = (gr + 2) & 7;
          }
        }
        if (c == 8) break;
        if (c == 0) mbar_wait(sBar + B_EMPTYA + 24, 0);
#pragma unroll
        for (int j = 0; j < 2; j++)
          asm volatile("st.async.shared::cluster.mbarrier::complete_tx::bytes.v4.b32 [%0], {%1,%2,%3,%4}, [%5];" ::"r"(sb + SM_XCH + xb + peer + j * 512),
                       "r"(pack_bf16(c0[j * 16 + 2], c0[j * 16 + 3])), "r"(pack_bf16(c0[j * 16 + 6], c0[j * 16 + 7])), "r"(pack_bf16(c0[j * 16 + 10], c0[j * 16 + 11])),
                       "r"(pack_bf16(c0[j * 16 + 14], c0[j * 16 + 15])), "r"(sBar + B_XF + (c & 1) * 8 + peer) : "memory");
#pragma unroll
        for (int j = 0; j < 16; j++) kp[j] = c0[(j >> 1) * 4 + (j & 1)];
      }
      STAMP(72); GSTAMP(67);
      uint2* const dst = reinterpret_cast<uint2*>(g_ones + F_PART) + ((qt * 8 + w8) * 40 + 32 + rank * 4 + kg) * 256 + lane;
#pragma unroll
      for (int jb = 0; jb < 8; jb++)
        asm volatile("st.relaxed.gpu.global.v2.u32 [%0], {%1,%2};" ::"l"(dst + jb * 32), "r"(pack_bf16(c0[jb * 4], c0[jb * 4 + 1])), "r"(pack_bf16(c0[jb * 4 + 2], c0[jb * 4 + 3])) : "memory");
    }
    STAMP(73);
    {
    const int lane = get_lane(), g = lane >> 2, t4 = lane & 3;
    uint32_t* const tsu = reinterpret_cast<uint32_t*>(smem_raw + SM_T);
    float* const tsf = reinterpret_cast<float*>(smem_raw + SM_T);
    const int row0 = qt * 128 + hg * 16;
    const int kq = w8 >> 1;
    uint32_t bg[9][10], bd[9][5];
    auto ld_bg = [&](int k0, int k1) {
      if (k0 == 0) mbar_wait(sBar + B_FFN, 0);
      const uint32_t wa = sb + (w8 == 3 || w8 == 5 ? -11520 : (w8 & 1) ? SM_WG + 46080 : SM_WG) + (kq * 144 + (lane & 15)) * 80 + (lane >> 4) * 16;
#pragma unroll
      for (int ks = k0; ks < k1; ks++) {
        uint32_t b0[4], b1[4], b2[2];
        ldsm4t(b0, wa + ks * 1280); ldsm4t(b1, wa + ks * 1280 + 32); ldsm2t(b2, wa + ks * 1280 + 64 - (lane >> 4) * 16);
#pragma unroll
        for (int i = 0; i < 4; i++) { bg[ks][i] = b0[i]; bg[ks][4 + i] = b1[i]; }
        bg[ks][8] = b2[0]; bg[ks][9] = b2[1];
      }
    };
    uint32_t xs[9], *xp;
    auto st_x = [&]() {
#pragma unroll
      for (int i = 0; i < 9; i++)
        if (xp) str1(xp + i * 32, xs[i]);
    };
    {
      uint32_t xa[9], xb[9], wb[9];
      uint4 md[9];
      float av[2][4];
      uint2 pv[12];
      const uint32_t ident = (g >> 1) == t4 ? 0x3f80u << ((g & 1) * 16) : 0u;
      auto ld_late = [&]() {
        bool bad = false;
#pragma unroll
        for (int s = 0; s < 12; s++)
          if (pv[s].x == ~0u || pv[s].y == ~0u) {
            bad = true;
            if (s < 4) { pv[s].x = ldr1(ap + (28 + s) * 512); pv[s].y = ldr1(ap + (28 + s) * 512 + 256); }
            else pv[s] = ldr2(ap + (28 + s) * 512 + w8 * 32 + lane);
          }
        return bad;
      };
#pragma unroll
      for (int s = 0; s < 12; s++) pv[s] = make_uint2(~0u, ~0u);
      uint32_t* const tr = reinterpret_cast<uint32_t*>(smem_raw + SM_X2) + g * 292 + w8 * 4 + t4;
      float sx[4] = {0.f, 0.f, 0.f, 0.f}, qa[4] = {0.f, 0.f, 0.f, 0.f}, qb[4] = {0.f, 0.f, 0.f, 0.f};
      auto stat = [&](int i, uint32_t a, uint32_t c) {
        xa[i] = hfma2(md[i].x, a, xa[i]);
        xb[i] = hfma2(md[i].x, c, xb[i]);
        mma1688(sx, xa[i], xb[i], wb[i]);
        mma1688(qa, xa[i], xb[i], xa[i]);
        mma1688(qb, xa[i], xb[i], xb[i]);
      };
      mbar_wait(sBar + B_TB, 0);
#pragma unroll
      for (int i = 0; i < 9; i++) {
        md[i] = lds128(sb + SM_MD + (i * 32 + w8 * 4 + t4) * 16);
        const uint32_t w = *reinterpret_cast<const uint32_t*>(smem_raw + SM_MOD + (i * 32 + w8 * 4 + t4) * 8 + (g & 1) * 4);
        wb[i] = g == 0 ? 0x3f803f80u : g < 3 ? w : 0u;
      }
      mbar_wait(sBar + B_XR, 0);
#pragma unroll
      for (int i = 0; i < 9; i++) { xa[i] = tr[i * 32]; xb[i] = tr[8 * 292 + i * 32]; }
      mbar_wait(sBar + B_EMPTYO, 0);
      STAMP(74);
      {
        uint32_t need = 0x7fu & (~0u << nc);
        int c1 = 5, c2 = 6;
        ra[5] = rb[5] = ra[6] = rb[6] = 0;
#pragma unroll 1
        for (uint32_t n = 0;; n++) {
          uint32_t a1, d1, a2, d2;
          ld_sum(a1, d1, ld);
          ld_sum(a2, d2, ld + 8);
#pragma unroll
          for (int i = 0; i < 7; i++) {
            if (c1 == i) { ra[i] = a1; rb[i] = d1; }
            if (c2 == i) { ra[i] = a2; rb[i] = d2; }
          }
          auto max8 = [](const uint32_t* w) { return __vimax3_u32(__vimax3_u32(w[0], w[1], w[2]), __vimax3_u32(w[3], w[4], w[5]), max(w[6], w[7])); };
          if (!__any_sync(~0u, max8(ld) == ~0u)) need &= ~(1u << c1);
          if (!__any_sync(~0u, max8(ld + 8) == ~0u)) need &= ~(1u << c2);
          if (__builtin_expect(!need || n > (1u << 15), 1)) break;
          c1 = __ffs(need) - 1;
          c2 = 31 - __clz(need);
          if (FX == 2 && (need & (need - 1))) c2 = __ffs(need & (need - 1)) - 1;
#pragma unroll
          for (int i = 0; i < 8; i++) { ld[i] = ldr1(ap + c1 * 2048 + i * 256); ld[8 + i] = ldr1(ap + c2 * 2048 + i * 256); }
        }
      }
      STAMP(69);
      mbar_wait(sBar + B_G2, 0);
      STAMP(48);
#pragma unroll 1
      for (uint32_t n = 0;; n++) {
        const bool bad = ld_late();
        if (!__any_sync(~0u, bad) || n > (1u << 15)) break;
        if (n == 0) {
#pragma unroll
          for (int i = 0; i < 7; i++) stat(i, ra[i], rb[i]);
          if (BGE) ld_bg(0, BGE);
        }
      }
      STAMP(77);
      if (lane == 0) mbar_arrive(sBar + B_G1);
#pragma unroll
      for (int i = 0; i < 8; i++) av[i >> 2][i & 3] = 0.f;
#pragma unroll
      for (int s = 0; s < 4; s++) {
        if (s & 1) mma16816(av[0], pv[s - 1].x, pv[s - 1].y, pv[s].x, pv[s].y, ident, ident);
        mma16816(av[1], pv[4 + s].x, pv[4 + s].y, pv[8 + s].y, pv[8 + s].x, ident, ident);
      }
#pragma unroll
      for (int i = 0; i < 2; i++) stat(7 + i, pack_bf16(av[i][0], av[i][1]), pack_bf16(av[i][2], av[i][3]));
      STAMP(40);
      float* const ps = reinterpret_cast<float*>(smem_raw + SM_PS);
      if (t4 < 2) {
        *reinterpret_cast<float2*>(ps + w8 * 32 + g * 4 + t4 * 2) = make_float2(sx[0], sx[1]);
        *reinterpret_cast<float2*>(ps + 256 + w8 * 32 + g * 4 + t4 * 2) = make_float2(sx[2], sx[3]);
      }
      if (ident) {
        ps[512 + w8 * 32 + g] = (g & 1) ? qa[1] : qa[0];
        ps[512 + w8 * 32 + g + 8] = (g & 1) ? qb[3] : qb[2];
      }
      bar_sync(5, 256);
      STAMP(44);
      float mean = 0.f, dot = 0.f, m2 = 0.f;
#pragma unroll
      for (int i = 0; i < 4; i++) {
        const float4 q = *reinterpret_cast<const float4*>(ps + (lane & 8) * 32 + (lane & 16) * 8 + i * 32 + (lane & 7) * 4);
        mean += q.x; dot += q.y + q.z; m2 += ps[512 + (lane & 16) * 8 + i * 32 + (lane & 15)];
      }
      const float2 sab = *reinterpret_cast<const float2*>(smem_raw + SM_ZERO + 16);
      mean += __shfl_xor_sync(~0u, mean, 16);
      dot += __shfl_xor_sync(~0u, dot, 16);
      m2 += __shfl_xor_sync(~0u, m2, 16);
      mean *= 1.f / DM;
      const float rs = rcp(bfr(sqrt_a(bfr(bfr(fmaxf(fmaf(m2, 1.f / DM, -mean * mean), 0.f)) + 1e-5f))));
      const uint32_t nm = pack_bf16(-mean, -mean);
      uint32_t u = pack_bf16(0.f, fmaf(rs, fmaf(bf_lo(nm), sab.x, dot), sab.y));
      u = ((u & 0x7fff0000u) > 0x7f800000u) ? 0u : (u ^ ((u >> 31) ? 0xffff0000u : 0x80000000u));
      u |= 0xffffu - (row0 + (lane & 15));
      const uint32_t m1 = __reduce_max_sync(~0u, u), m2k = __reduce_max_sync(~0u, u == m1 ? 0u : u);
      if (w8 == 7) asm volatile("st.relaxed.gpu.global.v2.u32 [%0], {%1,%2};" ::"l"(reinterpret_cast<uint2*>(g_ones + F_KEY) + lane * 128 + b), "r"(~m1), "r"(~m2k) : "memory");
      STAMP(41);
      const int r1 = ~m1 & 15, r2 = ~m2k & 15;
      const uint32_t r2t = pack_bf16(rs, rs - bfr(rs));
      const uint32_t rA = __shfl_sync(~0u, r2t, g), rB = __shfl_sync(~0u, r2t, g + 8);
      const uint32_t nmA = __shfl_sync(~0u, nm, g), nmB = __shfl_sync(~0u, nm, g + 8);
      const uint32_t hA = __byte_perm(rA, 0, 0x1010), lA = __byte_perm(rA, 0, 0x3232), hB = __byte_perm(rB, 0, 0x1010), lB = __byte_perm(rB, 0, 0x3232);
      uint32_t* const hx = reinterpret_cast<uint32_t*>(g_ones + F_HX + b * 288) + w8 * 4 + t4;
      const bool topA = g == r1 || g == r2, topB = g + 8 == r1 || g + 8 == r2;
      uint32_t* const pA = hx + (g == r2 ? 576 : 0);
      uint32_t* const pB = hx + (g + 8 == r2 ? 576 : 0);
      uint32_t* const pS = topA ? pA : pB;
#pragma unroll
      for (int i = 0; i < 9; i++) {
        const uint32_t da = hadd2(xa[i], nmA), db = hadd2(xb[i], nmB);
        const uint32_t ha = hfma2(hfma2(da, hA, hmul2(da, lA)), md[i].z, md[i].y), hb = hfma2(hfma2(db, hB, hmul2(db, lB)), md[i].z, md[i].y);
        if (topA || topB) str1(pS + i * 32, topA ? ha : hb);
        tr[i * 32] = hfma2(md[i].w, ha, xa[i]);
        tr[8 * 292 + i * 32] = hfma2(md[i].w, hb, xb[i]);
        md[i].x = hb;
        xs[i] = topA ? xa[i] : xb[i];
      }
      if (__builtin_expect((r1 ^ r2) == 8, 0) && topB) {
#pragma unroll
        for (int i = 0; i < 9; i++) { str1(pB + i * 32, md[i].x); str1(pB + 288 + i * 32, xb[i]); }
      }
      __syncwarp();
      xp = topA || topB ? pS + 288 : nullptr;
      if (HX == 2) st_x();
      if (tid == 128) tsu[34] = (1u << r1) | (1u << r2);
      bar_arrive(11, 288);
    }
    STAMP(75);
    ld_bg(BGE, 9);
    mbar_wait(sBar + B_FD, 0);
    STAMP(42);
    {
      const uint32_t a = sb + SM_WD + lane * 128 + (((w8 ^ lane) & 7) << 4);
#pragma unroll
      for (int i = 0; i < 9; i++) {
        uint32_t b0[4];
        ldsm4t(b0, a + i * 5120);
        asm volatile("ldmatrix.sync.aligned.m8n8.x1.trans.shared.b16 {%0}, [%1];" : "=r"(bd[i][4]) : "r"(a + i * 5120 + 4096) : "memory");
#pragma unroll
        for (int j = 0; j < 4; j++) bd[i][j] = b0[j];
      }
    }
    if (HX == 3) st_x();
    STAMP(43);
    mbar_wait(sBar + B_G3, 0);
    STAMP(76);
    {
      float c[2][3][4];
#pragma unroll
      for (int i = 0; i < 6; i++) c[i & 1][i >> 1][0] = c[i & 1][i >> 1][1] = c[i & 1][i >> 1][2] = c[i & 1][i >> 1][3] = 0.f;
      uint32_t hb[5][4];
#pragma unroll
      for (int i = 0; i < 5; i++) ldsm4(hb[i], sb + SM_T + T_H + (lane & 1) * 1152 + kq * 288 + (lane >> 3) * 16 + i * 64);
#pragma unroll
      for (int ks = 0; ks < 9; ks++) {
        const uint32_t h0 = hb[ks >> 1][(ks & 1) * 2], h1 = hb[ks >> 1][(ks & 1) * 2 + 1];
        mma16816(c[ks & 1][0], bg[ks][0], bg[ks][2], bg[ks][1], bg[ks][3], h0, h1);
        mma16816(c[ks & 1][1], bg[ks][4], bg[ks][6], bg[ks][5], bg[ks][7], h0, h1);
        mma16816(c[ks & 1][2], bg[ks][8], 0u, bg[ks][9], 0u, h0, h1);
      }
      float* const part = tsf + 64;
      const bool u1 = lane & 1, u2 = lane & 2;
#pragma unroll
      for (int i = 0; i < 3; i++) {
        const float v = (u2 ? (u1 ? c[0][i][3] : c[0][i][2]) : (u1 ? c[0][i][1] : c[0][i][0])) + (u2 ? (u1 ? c[1][i][3] : c[1][i][2]) : (u1 ? c[1][i][1] : c[1][i][0]));
        if (i < 2 || !u2) part[w8 * 80 + (t4 & 1) * 40 + i * 16 + (t4 >> 1) * 8 + g] = v;
      }
      STAMP(45);
      bar_sync(5, 256);
      STAMP(46);
      auto act2 = [&](int f) {
        const float2* pp = reinterpret_cast<const float2*>(part + (g & 1) * 40 + f + (b & 1) * 4);
        const float2 g0 = pp[0], g1 = pp[80], g2 = pp[160], g3 = pp[240], u0 = pp[40], u1 = pp[120], u2 = pp[200], u3 = pp[280];
        return pack_bf16(silu_bf(bfr((g0.x + g1.x) + (g2.x + g3.x))) * bfr((u0.x + u1.x) + (u2.x + u3.x)),
                         silu_bf(bfr((g0.y + g1.y) + (g2.y + g3.y))) * bfr((u0.y + u1.y) + (u2.y + u3.y)));
      };
      const uint32_t v0 = act2((g >> 1) * 8 + t4 * 2), v1 = act2(32 + (t4 & 1) * 2);
      uint32_t a6[5];
#pragma unroll
      for (int i = 0; i < 4; i++) a6[i] = __shfl_sync(~0u, v0, i * 8 + (lane & 7));
      a6[4] = t4 < 2 ? v1 : 0u;
      STAMP(47);
      float* const yp = reinterpret_cast<float*>(g_ones + F_YP) + b * 64 + g * 2;
      float y[5][4];
#pragma unroll
      for (int i = 0; i < 5; i++) {
        y[i][0] = y[i][1] = y[i][2] = y[i][3] = 0.f;
        mma16816(y[i], bd[2 * i][0], i < 4 ? bd[(2 * i + 1) % 9][0] : 0u, bd[2 * i][1], i < 4 ? bd[(2 * i + 1) % 9][1] : 0u, a6[0], a6[1]);
      }
#pragma unroll
      for (int i = 0; i < 5; i++) mma16816(y[i], bd[2 * i][2], i < 4 ? bd[(2 * i + 1) % 9][2] : 0u, bd[2 * i][3], i < 4 ? bd[(2 * i + 1) % 9][3] : 0u, a6[2], a6[3]);
#pragma unroll
      for (int i = 0; i < 5; i++) mma1688(y[i], bd[2 * i][4], i < 4 ? bd[(2 * i + 1) % 9][4] : 0u, a6[4]);
#pragma unroll
      for (int m = 0; m < 2; m++) {
        const float y0 = u2 ? (u1 ? y[2 * m + 1][2] : y[2 * m + 1][0]) : (u1 ? y[2 * m][2] : y[2 * m][0]);
        const float y1 = u2 ? (u1 ? y[2 * m + 1][3] : y[2 * m + 1][1]) : (u1 ? y[2 * m][3] : y[2 * m][1]);
        asm volatile("st.relaxed.gpu.global.v2.f32 [%0], {%1,%2};" ::"l"(yp + (m * 8 + w8) * 8192 + t4 * 16), "f"(y0), "f"(y1) : "memory");
      }
      if (t4 == 0) asm volatile("st.relaxed.gpu.global.v2.f32 [%0], {%1,%2};" ::"l"(yp + (16 + (w8 >> 2)) * 8192 + (w8 & 3) * 16), "f"(y[4][0]), "f"(y[4][1]) : "memory");
    }
    if (HX == 1) st_x();
    STAMP(78);
    if (b < 72) {
      const uint4* pp = g_ones + F_YP + (b >> 2) * 2048 + (w8 * 16 + g) * 16 + (b & 3) * 4 + t4;
      const uint4 none = make_uint4(~0u, ~0u, ~0u, ~0u);
      uint4 r0 = none, r1 = none, q[FK][2];
      PSTAMP(352, 62);
#pragma unroll
      for (int j = 0; j < FK; j++) {
        if (j) delay(FD);
        q[j][0] = ldr4(pp); q[j][1] = ldr4(pp + 128);
      }
      float gb, hv, sg;
      uint16_t xv = 0;
      bf16* op;
      if (w8 == 7) {
        const uint32_t k1 = tsu[32], k2 = tsu[33];
        const int row1 = ~k1 & (SQ - 1), row2 = ~k2 & (SQ - 1);
        const int tok = lane & 1, col = (b < 64 ? ((b >> 5) * 4 + (b & 3)) * 64 + (b & 28) * 2 : b * 8) + ((lane >> 1) & 7);
        const uint32_t key = tok ? k2 : k1;
        const int row = tok ? row2 : row1;
        const int c1 = ((row1 >> 5) & 3) * 32 + (row1 >> 7) * 2 + ((row1 >> 4) & 1), cr = ((row >> 5) & 3) * 32 + (row >> 7) * 2 + ((row >> 4) & 1);
        const uint16_t* xp = reinterpret_cast<const uint16_t*>(g_ones + F_HX + cr * 288 + (tok && c1 == cr ? 144 : 0) + 72) + col;
        gb = __uint_as_float((uint32_t)reinterpret_cast<const uint16_t*>(smem_raw + SM_MD)[(col >> 1) * 8 + 6 + (col & 1)] << 16);
        hv = __uint_as_float((uint32_t)reinterpret_cast<const uint16_t*>(smem_raw + SM_T + T_H)[tok * DM + col] << 16);
        sg = bfr(rcp(1.f + __expf(-__uint_as_float((key & 0xffff0000u) ^ ((key >> 31) ? 0x80000000u : 0xffff0000u)))));
        op = prm.out + (size_t)row * DM + col;
#pragma unroll 1
        for (uint32_t n = 0; n < (1u << 15); n++) {
          asm volatile("ld.relaxed.gpu.global.u16 %0, [%1];" : "=h"(xv) : "l"(xp) : "memory");
          if (xv != 0xffff) break;
        }
        __syncwarp();
      }
#pragma unroll 1
      for (uint32_t n = 0;; n++) {
        bool done = false;
#pragma unroll
        for (int j = 0; j < FK; j++) {
          if (unset(r0)) r0 = q[j][0];
          if (unset(r1)) r1 = q[j][1];
          const bool m0 = unset(r0), m1 = unset(r1);
          if (!__any_sync(~0u, m0 || m1)) { done = true; break; }
          if (m0) q[j][0] = ldr4(pp);
          if (m1) q[j][1] = ldr4(pp + 128);
        }
        if (done) break;
        if (n > (1u << 14)) { SETERR(32); break; }
      }
      PSTAMP(352, 63);
      float s[4] = {__uint_as_float(r0.x) + __uint_as_float(r1.x), __uint_as_float(r0.y) + __uint_as_float(r1.y),
                    __uint_as_float(r0.z) + __uint_as_float(r1.z), __uint_as_float(r0.w) + __uint_as_float(r1.w)};
      const bool u4 = lane & 4, u8 = lane & 8;
#pragma unroll
      for (int i = 0; i < 2; i++) { const float snd = u4 ? s[i] : s[i + 2], kp = u4 ? s[i + 2] : s[i]; s[i] = kp + __shfl_xor_sync(~0u, snd, 4); }
      { const float snd = u8 ? s[0] : s[1], kp = u8 ? s[1] : s[0]; s[0] = kp + __shfl_xor_sync(~0u, snd, 8); }
      s[0] += __shfl_xor_sync(~0u, s[0], 16);
      float* const fs = reinterpret_cast<float*>(smem_raw + SM_PS);
      if (lane < 16) fs[(t4 * 4 + (g & 1) * 2 + (g >> 1)) * 8 + w8] = s[0];
      if (w8 < 7) bar_arrive(5, 256);
      else {
        bar_sync(5, 256);
        const float4 a = *reinterpret_cast<const float4*>(fs + (lane & 15) * 8), c = *reinterpret_cast<const float4*>(fs + (lane & 15) * 8 + 4);
        const float hh = bfr(hv + bfr(bfr(((a.x + a.y) + (a.z + a.w)) + ((c.x + c.y) + (c.z + c.w))) * sg));
        if (lane < 16) *op = __float2bfloat16(__uint_as_float((uint32_t)xv << 16) + bfr(gb * hh));
      }
      PSTAMP(352, 49);
    }
    if (w8 == 5 && lane < 9) g_mod1[b * 9 + lane] = make_uint4(0u, 0u, 0u, 0u);
    if (w8 == 5 && lane == 9) *reinterpret_cast<uint4*>(&g_cnt[(C_Q + b) * 32]) = make_uint4(0u, 0u, 0u, 0u);
    if (w8 == 5 && lane == 10 && b == 0) g_cnt[C_SIDE * 32] = 0;
    STAMP(79); GSTAMP(91);
    }
  }
}

typedef CUresult (*PFN_enc)(CUtensorMap*, CUtensorMapDataType, cuuint32_t, void*, const cuuint64_t*, const cuuint64_t*,
                            const cuuint32_t*, const cuuint32_t*, CUtensorMapInterleave, CUtensorMapSwizzle,
                            CUtensorMapL2promotion, CUtensorMapFloatOOBfill);
static PFN_enc g_enc = nullptr;
static uint4* g_mod1_p = nullptr;
static CUtensorMap mk_map(const void* p, uint64_t cols, uint64_t rows, uint32_t bc, uint32_t br, bool swz = true) {
  CUtensorMap m;
  cuuint64_t dims[2] = {cols, rows};
  cuuint64_t strides[1] = {cols * 2};
  cuuint32_t box[2] = {bc, br}, es[2] = {1, 1};
  g_enc(&m, CU_TENSOR_MAP_DATA_TYPE_BFLOAT16, 2, const_cast<void*>(p), dims, strides, box, es, CU_TENSOR_MAP_INTERLEAVE_NONE,
        swz ? CU_TENSOR_MAP_SWIZZLE_128B : CU_TENSOR_MAP_SWIZZLE_NONE, swz ? CU_TENSOR_MAP_L2_PROMOTION_L2_128B : CU_TENSOR_MAP_L2_PROMOTION_NONE,
        CU_TENSOR_MAP_FLOAT_OOB_FILL_NONE);
  return m;
}

static CUtensorMap mk_map_n(const void* p, int n, const cuuint64_t* dims, const cuuint64_t* strides, const cuuint32_t* box) {
  CUtensorMap m;
  cuuint32_t es[4] = {1, 1, 1, 1};
  g_enc(&m, CU_TENSOR_MAP_DATA_TYPE_BFLOAT16, n, const_cast<void*>(p), dims, strides, box, es, CU_TENSOR_MAP_INTERLEAVE_NONE,
        CU_TENSOR_MAP_SWIZZLE_128B, CU_TENSOR_MAP_L2_PROMOTION_L2_128B, CU_TENSOR_MAP_FLOAT_OOB_FILL_NONE);
  return m;
}

extern "C" void kernel_launch(void* const* d_in, const int* in_sizes, int n_in, void* d_out, int out_size) {
  if (!g_enc) {
    cudaDriverEntryPointQueryResult st;
    cudaGetDriverEntryPoint("cuTensorMapEncodeTiled", (void**)&g_enc, cudaEnableDefault, &st);
    cudaFuncSetAttribute(k_mega, cudaFuncAttributeMaxDynamicSharedMemorySize, SM_TOTAL);
    cudaGetSymbolAddress((void**)&g_mod1_p, g_mod1);
  }
  const cuuint64_t xd[3] = {64, SQ, 9}, xs[2] = {DM * 2, 128};
  const cuuint32_t xb[3] = {64, 32, 9};
  CUtensorMap mX = mk_map_n(d_in[0], 3, xd, xs, xb);
  CUtensorMap mWq = mk_map(d_in[3], HQ * DH, DM, 64, 144);
  CUtensorMap mK = mk_map(d_in[1], DH, HKV * SK, 64, 128);
  CUtensorMap mV = mk_map(d_in[2], DH, HKV * SK, 64, 128);
  const cuuint64_t od[4] = {DM, DH, 2, HKV}, os[3] = {DM * 2, DH * DM * 2, 2 * DH * DM * 2};
  const cuuint32_t ob[4] = {64, DH, 1, 2};
  CUtensorMap mWo = mk_map_n(d_in[4], 4, od, os, ob);
  CUtensorMap mWg = mk_map(d_in[7], FF, DM, 40, 144, false);
  CUtensorMap mWu = mk_map(d_in[8], FF, DM, 40, 144, false);
  const cuuint64_t dd[3] = {64, FF, 9}, ds[2] = {DM * 2, 128};
  const cuuint32_t db[3] = {64, 40, 9};
  CUtensorMap mWd = mk_map_n(d_in[9], 3, dd, ds, db);
  CUtensorMap mM = mk_map(d_in[11], 6 * DM, DM, 16, 192, false);
  Params prm;
  prm.x = (const bf16*)d_in[0]; prm.k = (const bf16*)d_in[1]; prm.v = (const bf16*)d_in[2]; prm.wo = (const bf16*)d_in[4]; prm.wq = (const bf16*)d_in[3];
  prm.w_r = (const bf16*)d_in[6]; prm.c = (const bf16*)d_in[10]; prm.w_mod = (const bf16*)d_in[11];
  prm.wg = (const bf16*)d_in[7]; prm.wu = (const bf16*)d_in[8]; prm.wd = (const bf16*)d_in[9];
  prm.out = (bf16*)d_out;
  prm.mod1 = g_mod1_p;
  cudaLaunchConfig_t cfg = {};
  cfg.gridDim = dim3(132); cfg.blockDim = dim3(384); cfg.dynamicSmemBytes = SM_TOTAL; cfg.stream = cudaStreamPerThread;
  cudaLaunchAttribute at[1];
  at[0].id = cudaLaunchAttributeClusterDimension;
  at[0].val.clusterDim.x = 2; at[0].val.clusterDim.y = 1; at[0].val.clusterDim.z = 1;
  cfg.attrs = at; cfg.numAttrs = 1;
  cudaLaunchKernelEx(&cfg, k_mega, prm, mX, mWq, mK, mV, mWo, mWg, mWu, mWd, mM);
}
```

```cpp
#include <cuda_runtime.h>
#include <cuda_bf16.h>
#include <cuda.h>
#include <stdint.h>

typedef __nv_bfloat16 bf16;

constexpr int SQ = 2048, DM = 576, HQ = 32, HKV = 16, SK = 2048, DH = 128, FF = 4608;

#define TCH 20
#define TF0 26
#define TW0 16
#define TWN 4
#define FAKEB 0
#define FILLS 30
#define WOMC 0
#define FFNS 0x6420
#define ORD 1
#define FIXS 0
#define HINTH 1
#define HINTW 1
#define PFO 1
#define TN 3
#define FGAP 0
#define FGN 8
#define BGE 5
#define FPRED 1
#define XD 500
#define CV 1
#define WARM 0
#define XT 0
#define CT 0
#define TMP 1
#define XO 0
#define RS0 0
#define CL 0
#define PM 0
#define PN 4
#define MM 31
#define XW 1
#define GP 0
#define FX 1
#define MG 1
#define MGL 0
#define HX 1
#define N2 1
#define HS 0
#define EH 8
#define XD1 1000
#define PW 0
#define QW 0
#define B7 1
#define LN_LIMIT 0.0625f
#define TG 9
#define TL 1
#define KICK 0
#define MT 1
#define MWARM 0
#define PE 0
#define PD 0
#define FK 1
#define FD 300
#define XPF 0
#define WQPF0 0
#define WQPF1 0xff
#define FFNQ 2
#define WQPF2 0
#define QTH 4
#define MPF 1
#define FILLP 31
#define FILL0 25
#define FFN0 20
#define FILLN 8
#define FFNB 6
#define PF0 20
#define FFNR 1
#define FFND 1
#define KV0 16
#define KVS 2
#define QPF 6
#define EF 31
#define WOP 99
#define TLBW 0
#define NOFFN 0
#define FLATE 0
#define RELF 1
#define REL_FENCE() asm volatile("fence.acq_rel.gpu;" ::: "memory")
#define FILLMIN 0
#define FWS 100
#define FW 0
#define GX 0
#define XQ 0
#define XS 0
#define OSP 0
#define XG 0
#define DS 0
#define AO 3072
#define KVP 99
#define NQP 1
#define PFM 7
#define QL 1
#define IS 0
#define AL 1
#define FILLMAX 45
#define XN 4
#define MODB 0
#define QPV 0
#define LATEG 0
#define RETL 1
#define HINTA 15
#define SIDEF 3
#define FFNE 15
#define TE_POS 8
#define LAZY_LIMIT 1.8446744e19f
#define LAZY_LOW 5.4210109e-20f
__device__ uint4 g_mod1[8 * 144];
__device__ uint4 g_mod2[288];
#define g_q (g_ones + F_PART - AO)
constexpr int PS = AL ? 8192 : 5120;
constexpr int F_HX = 0;
constexpr int F_YP = 128 * 288;
constexpr int F_KEY = 128 * 576;
constexpr int F_PART = 128 * 640 + AO;
constexpr int F_N = 640 + PS;
__device__ uint4 g_ones[128 * F_N];
__device__ __align__(128) unsigned int g_cnt[136 * 32];
__device__ unsigned int g_err;
#define HAS_ERR
enum { C_SIDE = 1, C_Q = 8 };

#define STAMP(i)
#define KSTAMP(i)
#define GSTAMP(i)
#define SETERR(v)
#define ES(t, w, i)
#define ESC(i)
#define PSTAMP(t, i)

__device__ __forceinline__ int get_lane() {
  int l;
  asm volatile("mov.u32 %0, %%laneid;" : "=r"(l));
  __builtin_assume(l >= 0 && l < 32);
  return l;
}
__device__ __forceinline__ uint32_t clk() { uint32_t c; asm volatile("mov.u32 %0, %%clock;" : "=r"(c) :: "memory"); return c; }
__device__ __forceinline__ void delay(uint32_t n) { const uint32_t t0 = clk(); while (clk() - t0 < n) {} }
__device__ __forceinline__ uint32_t smem_u32(const void* p) { return (uint32_t)__cvta_generic_to_shared(p); }
__device__ __forceinline__ void mbar_init(uint32_t a, uint32_t cnt) { asm volatile("mbarrier.init.shared::cta.b64 [%0], %1;" ::"r"(a), "r"(cnt)); }
__device__ __forceinline__ void mbar_expect_tx(uint32_t a, uint32_t bytes) { asm volatile("mbarrier.arrive.expect_tx.shared::cta.b64 _, [%0], %1;" ::"r"(a), "r"(bytes) : "memory"); }
__device__ __forceinline__ void mbar_arrive(uint32_t a) { asm volatile("mbarrier.arrive.shared::cta.b64 _, [%0];" ::"r"(a) : "memory"); }
__device__ __forceinline__ void mbar_arrive_cl(uint32_t a_cluster) { asm volatile("mbarrier.arrive.shared::cluster.b64 _, [%0];" ::"r"(a_cluster) : "memory"); }
__device__ __forceinline__ void mbar_wait(uint32_t a, uint32_t parity) {
  asm volatile(
      "{\n.reg .pred p;\n.reg .u32 n;\nmov.u32 n, 0;\n"
      "WAIT_LOOP:\n"
      "mbarrier.try_wait.parity.shared::cta.b64 p, [%0], %1;\n"
      "@p bra WAIT_DONE;\n"
      "add.u32 n, n, 1;\n"
      "setp.lt.u32 p, n, 65536;\n"
      "@p bra WAIT_LOOP;\n"
      "WAIT_DONE:\n}\n" ::"r"(a), "r"(parity), "l"(&g_err) : "memory");
}
__device__ __forceinline__ void cnt_wait(int idx, unsigned target) {
  for (uint32_t n = 0;; n++) {
    unsigned v;
    asm volatile("ld.relaxed.gpu.global.u32 %0, [%1];" : "=r"(v) : "l"(&g_cnt[idx * 32]) : "memory");
    if (v >= target) break;
    if (n > (1u << 15)) { SETERR(2); break; }
  }
}
__device__ __forceinline__ void cnt_wait1(int word, unsigned target) {
  for (uint32_t n = 0;; n++) {
    unsigned v;
    asm volatile("ld.relaxed.gpu.global.u32 %0, [%1];" : "=r"(v) : "l"(&g_cnt[word]) : "memory");
    if (v >= target) break;
    if (n > (1u << 15)) { SETERR(2); break; }
  }
}
__device__ __forceinline__ void cnt_arrive(int idx) {
  asm volatile("red.relaxed.gpu.global.add.u32 [%0], 1;" ::"l"(&g_cnt[idx * 32]) : "memory");
}
__device__ __forceinline__ uint4 poll4(const uint4* p) {
  uint4 v;
  uint32_t n = 0;
  while (true) {
    asm volatile("ld.relaxed.gpu.global.v4.u32 {%0,%1,%2,%3}, [%4];" : "=r"(v.x), "=r"(v.y), "=r"(v.z), "=r"(v.w) : "l"(p) : "memory");
    if (v.x && v.y && v.z && v.w) break;
    if (++n > (1u << 15)) { SETERR(4); break; }
  }
  return v;
}
__device__ __forceinline__ void poll8(const uint4* p, const uint4* q, uint4& v, uint4& w) {
  uint32_t n = 0;
#pragma unroll 1
  while (true) {
    asm volatile("ld.relaxed.gpu.global.v4.u32 {%0,%1,%2,%3}, [%4];" : "=r"(v.x), "=r"(v.y), "=r"(v.z), "=r"(v.w) : "l"(p) : "memory");
    asm volatile("ld.relaxed.gpu.global.v4.u32 {%0,%1,%2,%3}, [%4];" : "=r"(w.x), "=r"(w.y), "=r"(w.z), "=r"(w.w) : "l"(q) : "memory");
    if (v.x && v.y && v.z && v.w && w.x && w.y && w.z && w.w) break;
    if (++n > (1u << 15)) { SETERR(4); break; }
  }
}
__device__ __forceinline__ uint4 ldr4(const void* p) {
  uint4 v;
  asm volatile("ld.relaxed.gpu.global.v4.u32 {%0,%1,%2,%3}, [%4];" : "=r"(v.x), "=r"(v.y), "=r"(v.z), "=r"(v.w) : "l"(p) : "memory");
  return v;
}
__device__ __forceinline__ uint2 ldr2(const void* p) {
  uint2 v;
  asm volatile("ld.relaxed.gpu.global.v2.u32 {%0,%1}, [%2];" : "=r"(v.x), "=r"(v.y) : "l"(p) : "memory");
  return v;
}
__device__ __forceinline__ uint32_t ldr1(const void* p) {
  uint32_t v;
  asm volatile("ld.relaxed.gpu.global.u32 %0, [%1];" : "=r"(v) : "l"(p) : "memory");
  return v;
}
__device__ __forceinline__ void str1(void* p, uint32_t v) { asm volatile("st.relaxed.gpu.global.u32 [%0], %1;" ::"l"(p), "r"(v) : "memory"); }
__device__ __forceinline__ bool unset(uint4 v) { return v.x == ~0u || v.y == ~0u || v.z == ~0u || v.w == ~0u; }
__device__ __forceinline__ bool nan2(uint32_t v) {
  uint32_t r;
  asm("{\n.reg .pred p, q;\nsetp.nan.bf16x2 p|q, %1, %1;\nor.pred p, p, q;\nselp.u32 %0, 1, 0, p;\n}\n" : "=r"(r) : "r"(v));
  return r != 0;
}
__device__ __forceinline__ uint32_t hmul2(uint32_t a, uint32_t b) { uint32_t r; asm("mul.rn.bf16x2 %0, %1, %2;" : "=r"(r) : "r"(a), "r"(b)); return r; }
__device__ __forceinline__ uint32_t hadd2(uint32_t a, uint32_t b) { uint32_t r; asm("add.rn.bf16x2 %0, %1, %2;" : "=r"(r) : "r"(a), "r"(b)); return r; }
__device__ __forceinline__ uint32_t hfma2(uint32_t a, uint32_t b, uint32_t c) { uint32_t r; asm("fma.rn.bf16x2 %0, %1, %2, %3;" : "=r"(r) : "r"(a), "r"(b), "r"(c)); return r; }
__device__ __forceinline__ void mma16816(float (&c)[4], uint32_t a0, uint32_t a1, uint32_t a2, uint32_t a3, uint32_t b0, uint32_t b1) {
  asm volatile("mma.sync.aligned.m16n8k16.row.col.f32.bf16.bf16.f32 {%0,%1,%2,%3}, {%4,%5,%6,%7}, {%8,%9}, {%0,%1,%2,%3};"
               : "+f"(c[0]), "+f"(c[1]), "+f"(c[2]), "+f"(c[3]) : "r"(a0), "r"(a1), "r"(a2), "r"(a3), "r"(b0), "r"(b1));
}
__device__ __forceinline__ void mma1688(float (&c)[4], uint32_t a0, uint32_t a1, uint32_t b0) {
  asm volatile("mma.sync.aligned.m16n8k8.row.col.f32.bf16.bf16.f32 {%0,%1,%2,%3}, {%4,%5}, {%6}, {%0,%1,%2,%3};"
               : "+f"(c[0]), "+f"(c[1]), "+f"(c[2]), "+f"(c[3]) : "r"(a0), "r"(a1), "r"(b0));
}
__device__ __forceinline__ void ldsm4t(uint32_t (&r)[4], uint32_t a) {
  asm volatile("ldmatrix.sync.aligned.m8n8.x4.trans.shared.b16 {%0,%1,%2,%3}, [%4];" : "=r"(r[0]), "=r"(r[1]), "=r"(r[2]), "=r"(r[3]) : "r"(a) : "memory");
}
__device__ __forceinline__ void ldsm4(uint32_t (&r)[4], uint32_t a) {
  asm volatile("ldmatrix.sync.aligned.m8n8.x4.shared.b16 {%0,%1,%2,%3}, [%4];" : "=r"(r[0]), "=r"(r[1]), "=r"(r[2]), "=r"(r[3]) : "r"(a) : "memory");
}
__device__ __forceinline__ void ldsm2t(uint32_t (&r)[2], uint32_t a) {
  asm volatile("ldmatrix.sync.aligned.m8n8.x2.trans.shared.b16 {%0,%1}, [%2];" : "=r"(r[0]), "=r"(r[1]) : "r"(a) : "memory");
}
__device__ __forceinline__ float warp_sum(float v) {
#pragma unroll
  for (int o = 16; o; o >>= 1) v += __shfl_xor_sync(~0u, v, o);
  return v;
}
__device__ __forceinline__ void tma_load_2d(uint32_t dst, const CUtensorMap* map, uint32_t mbar, int c0, int c1) {
  asm volatile("cp.async.bulk.tensor.2d.shared::cluster.global.mbarrier::complete_tx::bytes [%0], [%1, {%3, %4}], [%2];"
               ::"r"(dst), "l"(map), "r"(mbar), "r"(c0), "r"(c1) : "memory");
}
__device__ __forceinline__ void tma_load_2d_mc(uint32_t dst, const CUtensorMap* map, uint32_t mbar, int c0, int c1) {
  asm volatile("cp.async.bulk.tensor.2d.shared::cluster.global.mbarrier::complete_tx::bytes.multicast::cluster [%0], [%1, {%3, %4}], [%2], %5;"
               ::"r"(dst), "l"(map), "r"(mbar), "r"(c0), "r"(c1), "h"((uint16_t)3) : "memory");
}
__device__ __forceinline__ uint64_t pol_first() {
  uint64_t p;
  asm("createpolicy.fractional.L2::evict_first.b64 %0, 1.0;" : "=l"(p));
  return p;
}
__device__ __forceinline__ void tma_load_2d_h(uint32_t dst, const CUtensorMap* map, uint32_t mbar, int c0, int c1, uint64_t pol) {
  asm volatile("cp.async.bulk.tensor.2d.shared::cluster.global.mbarrier::complete_tx::bytes.L2::cache_hint [%0], [%1, {%3, %4}], [%2], %5;"
               ::"r"(dst), "l"(map), "r"(mbar), "r"(c0), "r"(c1), "l"(pol) : "memory");
}
__device__ __forceinline__ void tma_load_2d_mc_h(uint32_t dst, const CUtensorMap* map, uint32_t mbar, int c0, int c1, uint64_t pol) {
  asm volatile("cp.async.bulk.tensor.2d.shared::cluster.global.mbarrier::complete_tx::bytes.multicast::cluster.L2::cache_hint [%0], [%1, {%3, %4}], [%2], %5, %6;"
               ::"r"(dst), "l"(map), "r"(mbar), "r"(c0), "r"(c1), "h"((uint16_t)3), "l"(pol) : "memory");
}
__device__ __forceinline__ void tma_load_3d(uint32_t dst, const CUtensorMap* map, uint32_t mbar, int c0, int c1, int c2) {
  asm volatile("cp.async.bulk.tensor.3d.shared::cluster.global.mbarrier::complete_tx::bytes [%0], [%1, {%3, %4, %5}], [%2];"
               ::"r"(dst), "l"(map), "r"(mbar), "r"(c0), "r"(c1), "r"(c2) : "memory");
}
__device__ __forceinline__ void tma_load_3d_mc(uint32_t dst, const CUtensorMap* map, uint32_t mbar, int c0, int c1, int c2) {
  asm volatile("cp.async.bulk.tensor.3d.shared::cluster.global.mbarrier::complete_tx::bytes.multicast::cluster [%0], [%1, {%3, %4, %5}], [%2], %6;"
               ::"r"(dst), "l"(map), "r"(mbar), "r"(c0), "r"(c1), "r"(c2), "h"((uint16_t)3) : "memory");
}
__device__ __forceinline__ void tma_load_4d_h(uint32_t dst, const CUtensorMap* map, uint32_t mbar, int c0, int c1, int c2, int c3, uint64_t pol) {
  asm volatile("cp.async.bulk.tensor.4d.shared::cluster.global.mbarrier::complete_tx::bytes.L2::cache_hint [%0], [%1, {%3, %4, %5, %6}], [%2], %7;"
               ::"r"(dst), "l"(map), "r"(mbar), "r"(c0), "r"(c1), "r"(c2), "r"(c3), "l"(pol) : "memory");
}
__device__ __forceinline__ void tma_prefetch_2d(const CUtensorMap* map, int c0, int c1) {
  asm volatile("cp.async.bulk.prefetch.tensor.2d.L2.global.tile [%0, {%1, %2}];" ::"l"(map), "r"(c0), "r"(c1) : "memory");
}
__device__ __forceinline__ void bulk_prefetch(const void* p, uint32_t bytes) {
  asm volatile("cp.async.bulk.prefetch.L2.global [%0], %1;" ::"l"(p), "r"(bytes) : "memory");
}
__device__ __forceinline__ void bulk_prefetch_f(const void* p, uint32_t bytes) {
  asm volatile("cp.async.bulk.prefetch.L2.global.L2::cache_hint [%0], %1, %2;" ::"l"(p), "r"(bytes), "l"(pol_first()) : "memory");
}
__device__ __forceinline__ void bulk_load(uint32_t dst, const void* src, uint32_t bytes, uint32_t mbar) {
  asm volatile("cp.async.bulk.shared::cluster.global.mbarrier::complete_tx::bytes [%0], [%1], %2, [%3];"
               ::"r"(dst), "l"(src), "r"(bytes), "r"(mbar) : "memory");
}
__device__ __forceinline__ void wgmma_fence() { asm volatile("wgmma.fence.sync.aligned;" ::: "memory"); }
__device__ __forceinline__ void wgmma_commit() { asm volatile("wgmma.commit_group.sync.aligned;" ::: "memory"); }
template <int N> __device__ __forceinline__ void wgmma_wait() { asm volatile("wgmma.wait_group.sync.aligned %0;" ::"n"(N) : "memory"); }
__device__ __forceinline__ void fence_async() { asm volatile("fence.proxy.async.shared::cta;" ::: "memory"); }
__device__ __forceinline__ void bar_sync(int id, int n) { asm volatile("bar.sync %0, %1;" ::"r"(id), "r"(n) : "memory"); }
__device__ __forceinline__ void bar_arrive(int id, int n) { asm volatile("bar.arrive %0, %1;" ::"r"(id), "r"(n) : "memory"); }

constexpr uint32_t SM_BASE = 1024;
__host__ __device__ constexpr uint32_t mk_desc(uint32_t addr, uint32_t lbo_bytes) { return ((addr & 0x3FFFF) >> 4) | ((lbo_bytes >> 4) << 16); }

#define R32(d) \
  "+f"(d[0]), "+f"(d[1]), "+f"(d[2]), "+f"(d[3]), "+f"(d[4]), "+f"(d[5]), "+f"(d[6]), "+f"(d[7]), \
  "+f"(d[8]), "+f"(d[9]), "+f"(d[10]), "+f"(d[11]), "+f"(d[12]), "+f"(d[13]), "+f"(d[14]), "+f"(d[15]), \
  "+f"(d[16]), "+f"(d[17]), "+f"(d[18]), "+f"(d[19]), "+f"(d[20]), "+f"(d[21]), "+f"(d[22]), "+f"(d[23]), \
  "+f"(d[24]), "+f"(d[25]), "+f"(d[26]), "+f"(d[27]), "+f"(d[28]), "+f"(d[29]), "+f"(d[30]), "+f"(d[31])
#define R64(d) R32(d), \
  "+f"(d[32]), "+f"(d[33]), "+f"(d[34]), "+f"(d[35]), "+f"(d[36]), "+f"(d[37]), "+f"(d[38]), "+f"(d[39]), \
  "+f"(d[40]), "+f"(d[41]), "+f"(d[42]), "+f"(d[43]), "+f"(d[44]), "+f"(d[45]), "+f"(d[46]), "+f"(d[47]), \
  "+f"(d[48]), "+f"(d[49]), "+f"(d[50]), "+f"(d[51]), "+f"(d[52]), "+f"(d[53]), "+f"(d[54]), "+f"(d[55]), \
  "+f"(d[56]), "+f"(d[57]), "+f"(d[58]), "+f"(d[59]), "+f"(d[60]), "+f"(d[61]), "+f"(d[62]), "+f"(d[63])
#define S32 \
  "{%0,%1,%2,%3,%4,%5,%6,%7,%8,%9,%10,%11,%12,%13,%14,%15,%16,%17,%18,%19,%20,%21,%22,%23,%24,%25,%26,%27,%28,%29,%30,%31}"
#define S64 \
  "{%0,%1,%2,%3,%4,%5,%6,%7,%8,%9,%10,%11,%12,%13,%14,%15,%16,%17,%18,%19,%20,%21,%22,%23,%24,%25,%26,%27,%28,%29,%30,%31," \
  "%32,%33,%34,%35,%36,%37,%38,%39,%40,%41,%42,%43,%44,%45,%46,%47,%48,%49,%50,%51,%52,%53,%54,%55,%56,%57,%58,%59,%60,%61,%62,%63}"

template <int TB>
__device__ __forceinline__ void wgmma128_rs(float (&d)[64], uint32_t a0, uint32_t a1, uint32_t a2, uint32_t a3, uint32_t db, int scale_d) {
  asm volatile("{\n.reg .pred p;\n.reg .b64 q;\nsetp.ne.b32 p, %69, 0;\nmov.b64 q, {%68, 0x40000040};\n"
               "wgmma.mma_async.sync.aligned.m64n128k16.f32.bf16.bf16 " S64 ", {%64,%65,%66,%67}, q, p, 1, 1, %70;\n}\n"
               : R64(d) : "r"(a0), "r"(a1), "r"(a2), "r"(a3), "r"(db), "r"(scale_d), "n"(TB));
}
__device__ __forceinline__ void wgmma64_rs(float (&d)[32], uint32_t a0, uint32_t a1, uint32_t a2, uint32_t a3, uint32_t db, int scale_d) {
  asm volatile("{\n.reg .pred p;\n.reg .b64 q;\nsetp.ne.b32 p, %37, 0;\nmov.b64 q, {%36, 0x40000040};\n"
               "wgmma.mma_async.sync.aligned.m64n64k16.f32.bf16.bf16 " S32 ", {%32,%33,%34,%35}, q, p, 1, 1, 1;\n}\n"
               : R32(d) : "r"(a0), "r"(a1), "r"(a2), "r"(a3), "r"(db), "r"(scale_d));
}
__device__ __forceinline__ uint32_t pack_bf16(float a, float b) {
  uint32_t r;
  asm("cvt.rn.bf16x2.f32 %0, %1, %2;" : "=r"(r) : "f"(b), "f"(a));
  return r;
}
__device__ __forceinline__ float ex2(float x) { float y; asm("ex2.approx.ftz.f32 %0, %1;" : "=f"(y) : "f"(x)); return y; }
__device__ __forceinline__ float bfr(float x) { return __bfloat162float(__float2bfloat16(x)); }
__device__ __forceinline__ float bf_lo(uint32_t u) { return __uint_as_float(u << 16); }
__device__ __forceinline__ float bf_hi(uint32_t u) { return __uint_as_float(u & 0xffff0000u); }
__device__ __forceinline__ uint4 lds128(uint32_t a) {
  uint4 v;
  asm volatile("ld.shared.v4.b32 {%0,%1,%2,%3}, [%4];" : "=r"(v.x), "=r"(v.y), "=r"(v.z), "=r"(v.w) : "r"(a) : "memory");
  return v;
}
__device__ __forceinline__ void sts128(uint32_t a, uint4 v) {
  asm volatile("st.shared.v4.b32 [%0], {%1,%2,%3,%4};" ::"r"(a), "r"(v.x), "r"(v.y), "r"(v.z), "r"(v.w) : "memory");
}
__device__ __forceinline__ void red_add_v4(float4* p, float a, float b, float c, float d) {
  asm volatile("red.global.add.v4.f32 [%0], {%1,%2,%3,%4};" ::"l"(p), "f"(a), "f"(b), "f"(c), "f"(d) : "memory");
}
__device__ __forceinline__ float rcp(float x) { float y; asm("rcp.approx.ftz.f32 %0, %1;" : "=f"(y) : "f"(x)); return y; }
__device__ __forceinline__ float sqrt_a(float x) { float y; asm("sqrt.approx.ftz.f32 %0, %1;" : "=f"(y) : "f"(x)); return y; }
__device__ __forceinline__ float silu_f(float v) { return v * rcp(1.f + __expf(-v)); }
__device__ __forceinline__ float silu_bf(float v) { return bfr(v * rcp(1.f + __expf(-v))); }

constexpr int SM_STASH = 131072;
constexpr int QG = 73728;
constexpr int SM_STG = 3 * QG - 18432;
constexpr int SM_MT = 3 * QG;
constexpr int SM_MB = SM_MT + 4608;
constexpr int SM_XCH = 196608;
constexpr int SM_MISC = 229376;
constexpr int SM_TOTAL = 232448;
constexpr int B_FULLQ = 0, B_TB = 24, B_G2 = 32, B_G3 = 40, B_QH = 48, B_FULLA = 64, B_XR = 96, B_FULLO = 184, B_FFN = 160, B_FD = 168, B_MD = 176, B_X = 2944, B_X1 = 2952, B_MM = 2984,
              B_EMPTYQ = 280, B_G1 = 304, B_EMPTYO = 328, B_ST = 392,
              B_EMPTYA = 400, B_M = 432, B_XF = 144;
constexpr int SM_MOD = SM_MISC + 448;
constexpr int SM_FILL = SM_MISC + 512;
constexpr int SM_M2 = SM_MISC + 2560;
constexpr int SM_RED = SM_MISC + 2752;
constexpr int SM_ZERO = SM_MISC + 3040;
constexpr int SM_WG = 137216;
constexpr int SM_X2 = 65536;
constexpr int SM_WD = 84992;
constexpr int SM_T = 23040;
constexpr int T_H = 2816;
constexpr int SM_PS = SM_T + 5120;
constexpr int SM_OUT = SM_MISC - 16384;
constexpr int SM_MD = SM_STASH;

template <class F>
__device__ __forceinline__ void ln_rows(uint32_t (&A)[144], uint32_t la, int lane, F done) {
  float mA = 0.f, mB = 0.f, vA, vB;
  bool redo = la >> 31;
#pragma unroll 1
  do {
    if (__builtin_expect(redo, 0)) {
      const uint32_t n2 = __shfl_sync(~0u, pack_bf16(mA, mB), (lane & 7) * 4);
      const uint32_t n = __byte_perm(n2, 0, (lane & 8) ? 0x3232 : 0x1010);
#pragma unroll 1
      for (int k = 0; k < 36; k++) {
        const uint32_t a = (la ^ ((k & 3) << 5)) + (k >> 2) * 4096;
        const uint4 v = lds128(a);
        sts128(a, make_uint4(hadd2(v.x, n), hadd2(v.y, n), hadd2(v.z, n), hadd2(v.w, n)));
      }
      fence_async();
      __syncwarp();
    }
    const uint32_t one = 0x3f803f80u;
    float c[3][4], q[3][4];
#pragma unroll
    for (int i = 0; i < 12; i++) c[i >> 2][i & 3] = q[i >> 2][i & 3] = 0.f;
#pragma unroll
    for (int k = 0; k < 36; k++) {
      uint32_t a[4];
      ldsm4(a, (la ^ ((k & 3) << 5)) + (k >> 2) * 4096);
      A[k * 4] = a[0]; A[k * 4 + 1] = a[1]; A[k * 4 + 2] = a[2]; A[k * 4 + 3] = a[3];
    }
#pragma unroll
    for (int k = 0; k < 36; k++) {
      mma16816(c[k % 3], A[k * 4], A[k * 4 + 1], A[k * 4 + 2], A[k * 4 + 3], one, one);
      mma16816(q[k % 3], hmul2(A[k * 4], A[k * 4]), hmul2(A[k * 4 + 1], A[k * 4 + 1]), hmul2(A[k * 4 + 2], A[k * 4 + 2]), hmul2(A[k * 4 + 3], A[k * 4 + 3]), one, one);
    }
    mA = (c[0][0] + c[1][0] + c[2][0]) * (-1.f / DM); mB = (c[0][2] + c[1][2] + c[2][2]) * (-1.f / DM);
    vA = fmaf(-mA, mA, (q[0][0] + q[1][0] + q[2][0]) * (1.f / DM)); vB = fmaf(-mB, mB, (q[0][2] + q[1][2] + q[2][2]) * (1.f / DM));
    redo = __any_sync(~0u, !(mA * mA <= LN_LIMIT * vA && mB * mB <= LN_LIMIT * vB)) && !redo;
  } while (__builtin_expect(redo, 0));
  done();
  const float rA = rsqrtf(fmaxf(vA, 0.f) + 1e-5f), rB = rsqrtf(fmaxf(vB, 0.f) + 1e-5f);
  const uint32_t hA = pack_bf16(rA, rA), hB = pack_bf16(rB, rB);
  const uint32_t lA = pack_bf16(rA - bf_lo(hA), rA - bf_lo(hA)), lB = pack_bf16(rB - bf_lo(hB), rB - bf_lo(hB));
  const uint32_t oA = pack_bf16(mA * rA, mA * rA), oB = pack_bf16(mB * rB, mB * rB);
#pragma unroll
  for (int i = 0; i < 144; i++) A[i] = hfma2(A[i], (i & 1) ? hB : hA, N2 ? ((i & 1) ? oB : oA) : hfma2(A[i], (i & 1) ? lB : lA, (i & 1) ? oB : oA));
}
__device__ __forceinline__ void modulate(uint32_t (&A)[144], uint32_t mt) {
#pragma unroll
  for (int k = 0; k < 36; k++) {
    const uint4 m = lds128(mt + k * 64);
    A[k * 4] = hfma2(A[k * 4], m.y, m.x); A[k * 4 + 1] = hfma2(A[k * 4 + 1], m.y, m.x);
    A[k * 4 + 2] = hfma2(A[k * 4 + 2], m.w, m.z); A[k * 4 + 3] = hfma2(A[k * 4 + 3], m.w, m.z);
  }
}
__device__ __forceinline__ void q_mma(float (&qa)[32], const uint32_t (&A)[144], uint32_t db) {
#pragma unroll
  for (int k = 0; k < 36; k++) wgmma64_rs(qa, A[k * 4], A[k * 4 + 1], A[k * 4 + 2], A[k * 4 + 3], db + k * 128, k != 0);
  wgmma_commit();
}
constexpr float Q_SCALE = 0.08838834764831845f * 1.4426950408889634f;

struct Params {
  uint4* mod1;
  const bf16 *c, *w_mod, *x, *k, *v, *wq, *w_r, *wo, *wg, *wu, *wd;
  bf16* out;
};

__global__ void __cluster_dims__(2, 1, 1) __launch_bounds__(384, 1)
k_mega(const Params prm, const __grid_constant__ CUtensorMap mX, const __grid_constant__ CUtensorMap mWq,
       const __grid_constant__ CUtensorMap mK, const __grid_constant__ CUtensorMap mV,
       const __grid_constant__ CUtensorMap mWo, const __grid_constant__ CUtensorMap mWg,
       const __grid_constant__ CUtensorMap mWu, const __grid_constant__ CUtensorMap mWd, const __grid_constant__ CUtensorMap mM) {
  extern __shared__ __align__(1024) uint8_t smem_raw[];
#define ECLK(x)
  const uint32_t sb = smem_u32(smem_raw);
  if ((sb & 0x3FFFF) != SM_BASE) __trap();
  const uint32_t sBar = sb + SM_MISC;
  const int tid = threadIdx.x;
  const int lane = get_lane();
  const int warp = __shfl_sync(~0u, tid >> 5, 0);
  const int b = blockIdx.x, rank = b & 1, qt = (b >> 1) & 15, kg = b >> 5, hg = kg * 2 + rank;
  const int hcol = (kg * 8 + rank) * DH;
#define CL_ARRIVE() asm volatile("barrier.cluster.arrive.relaxed.aligned;" ::: "memory")
#define CL_WAIT() asm volatile("barrier.cluster.wait.acquire.aligned;" ::: "memory")
  if (__builtin_expect(b >= 128, 0)) {
    if (tid == 0) {
#pragma unroll
      for (int i = 0; i < 6; i++) mbar_init(sBar + i * 8, i < 3 ? 1 : 8);
      asm volatile("fence.mbarrier_init.release.cluster;" ::: "memory");
    }
    __syncthreads();
    if (warp < 4) {
      asm volatile("setmaxnreg.dec.sync.aligned.u32 40;");
      if (tid == 0) {
#pragma unroll 1
        for (int n = 0, g = 0, ph = 1, m = 0, row = (b - 128) * 512; n < 40; n++) {
          if (n >= 3) mbar_wait(sBar + 24 + g * 8, ph);
          mbar_expect_tx(sBar + g * 8, QG);
          if (m < 2) {
            tma_load_3d(sb + g * QG, &mX, sBar + g * 8, 0, row, 0);
            tma_load_3d(sb + g * QG + QG / 2, &mX, sBar + g * 8, 0, row + 32, 0);
            row += 64;
          } else {
#pragma unroll 1
            for (int i = 0; i < 4; i++) tma_load_2d(sb + g * QG + i * 18432, &mWq, sBar + g * 8, (((m - 2) >> 1) * 8 + (m & 1) + 6) * DH + 64, i * 144);
          }
          if (++g == 3) { g = 0; ph ^= 1; }
          if (++m == 10) m = 0;
        }
      } else if (warp > 0) {
        if (tid < 104) {
          uint4 v, w;
          poll8(prm.mod1 + tid - 32, prm.mod1 + tid + 40, v, w);
          uint2* const mt = reinterpret_cast<uint2*>(smem_raw + SM_MT) + ((tid - 32) >> 1) * 8 + (tid & 1);
          mt[0] = make_uint2(~v.x, ~w.x); mt[2] = make_uint2(~v.y, ~w.y); mt[4] = make_uint2(~v.z, ~w.z); mt[6] = make_uint2(~v.w, ~w.w);
        }
        __syncwarp();
        bar_arrive(3, 352);
      }
    } else {
      asm volatile("setmaxnreg.inc.sync.aligned.u32 232;");
      const int cw = (warp >> 2) - 1, w8 = warp - 4;
      bar_sync(3, 352);
      if (cw == 0) bar_arrive(1, 256);
#pragma unroll 1
      for (int it = 0, n = 0; it < 4; it++) {
        uint32_t A[144];
        {
          const int g = (n + cw) % 3;
          mbar_wait(sBar + g * 8, ((n + cw) / 3) & 1);
          ln_rows(A, sb + g * QG + (w8 & 2) * (QG / 4) + ((w8 & 1) * 16 + (lane & 15)) * 128 + (((lane >> 4) ^ (lane & 7)) << 4), lane,
                  [&]() { if (lane < 2) mbar_arrive(sBar + 24 + g * 8); });
          modulate(A, sb + SM_MT + (lane & 3) * 16);
        }
        n += 2;
        const int b0 = ((b - 128) * 4 + it) * 2;
#pragma unroll 1
        for (int d = 0; d < 8; d++, n++) {
          const int g = n % 3;
          float qa[32];
          mbar_wait(sBar + g * 8, (n / 3) & 1);
          bar_sync(1 + cw, 256);
          wgmma_fence();
          q_mma(qa, A, mk_desc(SM_BASE, 16) + g * (QG >> 4));
          if (n + cw < 40) bar_arrive(2 - cw, 256);
          wgmma_wait<0>();
          if (lane == 0) mbar_arrive(sBar + 24 + g * 8);
          uint4* const qp = g_q + (((d >> 1) * 32 + b0 + (d & 1)) * (4 * 8 * 256) + 28 * 256 + w8 * 32 + lane);
#pragma unroll
          for (int j = 0; j < 4; j++) {
            uint32_t u[4];
#pragma unroll
            for (int i = 0; i < 4; i++) u[i] = pack_bf16(qa[8 * j + 2 * i] * Q_SCALE, qa[8 * j + 2 * i + 1] * Q_SCALE);
            qp[j * 256] = (d & 1) ? make_uint4(u[1], u[0], u[3], u[2]) : make_uint4(u[0], u[1], u[2], u[3]);
          }
        }
        asm volatile("fence.acq_rel.gpu;" ::: "memory");
        __syncwarp();
        if (lane < 8) asm volatile("red.relaxed.gpu.global.add.u32 [%0], 1;" ::"l"(&g_cnt[(C_Q + (lane >> 1) * 32 + b0 + (lane & 1)) * 32 + 2]) : "memory");
      }
    }
    return;
  }
  uint32_t cv[3];
  auto ld_c = [&]() {
#pragma unroll
    for (int i = 0; i < 3; i++) asm volatile("ld.volatile.global.u32 %0, [%1];" : "=r"(cv[i]) : "l"(reinterpret_cast<const uint32_t*>(prm.c) + (warp - 1) * 96 + i * 32 + lane) : "memory");
  };
  if (warp < 4 && warp > 0 && b < 72) {
    if (CL == 0) ld_c();
    if (lane == 0) {
      mbar_init(sBar + B_X1 + warp * 8, 1);
      asm volatile("fence.mbarrier_init.release.cluster;" ::: "memory");
      tma_load_2d(sb + SM_STG + (warp - 1) * 6144, &mM, sBar + B_X1 + warp * 8, b * 16, (warp - 1) * 192);
      mbar_expect_tx(sBar + B_X1 + warp * 8, 6144);
    }
    if (CL == 2) { __syncwarp(); ld_c(); }
  }
  if (tid == 0) {
    if (TMP) asm volatile("prefetch.tensormap [%0];" ::"l"(&mX) : "memory");
    mbar_init(sBar + B_X, 1);
    mbar_init(sBar + B_X1, 1);
#pragma unroll
    for (int i = 0; i < __builtin_popcount(MM); i++) mbar_init(sBar + B_MM + i * 8, 1);
    asm volatile("fence.mbarrier_init.release.cluster;" ::: "memory");
  }
  __syncwarp();
  ECLK(e1);
  CL_ARRIVE();
  ECLK(e2);
  if (warp < 4) asm volatile("setmaxnreg.dec.sync.aligned.u32 40;");
  if (warp == 0) {
    CL_WAIT();
    ECLK(e3);
    CL_ARRIVE();
    bar_sync(9, 288);
    if (lane == 0) {
      if (XD) delay(XD);
      tma_load_3d_mc(sb + rank * (QG / 2), &mX, sBar + B_X, 0, qt * 128 + rank * 32, 0);
      mbar_expect_tx(sBar + B_X, QG);
      if (!XO) {
        if (XD1) delay(XD1);
        tma_load_3d_mc(sb + QG + rank * (QG / 2), &mX, sBar + B_X1, 0, qt * 128 + 64 + rank * 32, 0);
        mbar_expect_tx(sBar + B_X1, QG);
      }
    }
    __syncwarp();
    ECLK(e4);
  } else if (warp < 4) {
    ECLK(e3);
    if (b < 72) {
      if (CL == 1) ld_c();
      const int g = lane >> 2, t4 = lane & 3;
      uint32_t se[3] = {0u, 0u, 0u}, so[3] = {0u, 0u, 0u};
#pragma unroll 1
      for (int live = !MWARM; live < 2; live++) {
        if (live) {
#pragma unroll
          for (int i = 0; i < 3; i++) {
            const uint32_t u = __shfl_sync(~0u, cv[i], lane);
            const uint32_t v = pack_bf16(silu_f(bf_lo(u)), silu_f(bf_hi(u)));
            se[i] = (g & 1) ? 0u : v; so[i] = (g & 1) ? v : 0u;
          }
          ECLK(e4);
          mbar_wait(sBar + B_X1 + warp * 8, 0);
          ES(32, 0, 93);
        }
        float a[4][4];
#pragma unroll
        for (int i = 0; i < 16; i++) a[i >> 2][i & 3] = 0.f;
        const uint32_t la = sb + SM_STG + ((lane >> 3) & 1) * 16 + ((warp - 1) * 192 + (lane & 7) + (lane >> 4) * 8) * 32;
#pragma unroll
        for (int i = 0; i < 12; i++) {
          uint32_t w[4];
          ldsm4t(w, la + i * 512);
          mma16816(a[i & 3], w[0], w[1], w[2], w[3], se[i >> 2], so[i >> 2]);
        }
        float v0 = (t4 & 2) ? ((t4 & 1) ? a[3][0] + a[3][1] : a[2][0] + a[2][1]) : ((t4 & 1) ? a[1][0] + a[1][1] : a[0][0] + a[0][1]);
        float v1 = (t4 & 2) ? ((t4 & 1) ? a[3][2] + a[3][3] : a[2][2] + a[2][3]) : ((t4 & 1) ? a[1][2] + a[1][3] : a[0][2] + a[0][3]);
        float* const red = reinterpret_cast<float*>(smem_raw + SM_MT + 2560 + live * 768);
        red[g * 12 + (warp - 1) * 4 + t4] = v0;
        red[g * 12 + 96 + (warp - 1) * 4 + t4] = v1;
        ES(32, 0, 94);
        bar_sync(6, 96);
        const float4* rp = reinterpret_cast<const float4*>(red + (lane & 7) * 24);
        const float4 x0 = rp[0], x1 = rp[1], x2 = rp[2], y0 = rp[3], y1 = rp[4], y2 = rp[5];
        uint32_t w = pack_bf16((((x0.x + x0.y) + (x0.z + x0.w)) + ((x1.x + x1.y) + (x1.z + x1.w))) + ((x2.x + x2.y) + (x2.z + x2.w)),
                               (((y0.x + y0.y) + (y0.z + y0.w)) + ((y1.x + y1.y) + (y1.z + y1.w))) + ((y2.x + y2.y) + (y2.z + y2.w)));
        if (b >= 36) w = hadd2(w, 0x3f803f80u);
        if (live && tid < 96)
          asm volatile("st.relaxed.gpu.global.u32 [%0], %1;" ::"l"(reinterpret_cast<uint32_t*>(prm.mod1) + ((tid - 32) >> 3) * 576 + b * 8 + (lane & 7)), "r"(~w) : "memory");
      }
    } else if (PD) delay(PD);
    ES(32, 0, 89);
    CL_WAIT();
    CL_ARRIVE();
    CL_WAIT();
    if (lane == 0) mbar_arrive(sBar + B_M);
    if (tid < 104) {
      uint4 v, w;
      if (PW) mbar_wait(sBar + B_X, 0);
      bool ok = false;
#pragma unroll 1
      for (int i = 0; i < __builtin_popcount(MM) && !ok; i++) {
        mbar_wait(sBar + B_MM + i * 8, 0);
        v = lds128(sb + SM_MB + (tid - 32) * 16);
        w = lds128(sb + SM_MB + (tid + 40) * 16);
        ok = v.x && v.y && v.z && v.w && w.x && w.y && w.z && w.w;
      }
      if (!ok) poll8(prm.mod1 + (b & 7) * 144 + tid - 32, prm.mod1 + (b & 7) * 144 + tid + 40, v, w);
      uint2* const mt = reinterpret_cast<uint2*>(smem_raw + SM_MT) + ((tid - 32) >> 1) * 8 + (tid & 1);
      mt[0] = make_uint2(~v.x, ~w.x); mt[2] = make_uint2(~v.y, ~w.y); mt[4] = make_uint2(~v.z, ~w.z); mt[6] = make_uint2(~v.w, ~w.w);
    }
    __syncwarp();
    ES(32, 0, 92);
    bar_arrive(3, 224);
    bar_arrive(4, 224);
    if (lane == 0) mbar_arrive(sBar + B_M + 8);
  } else {
    if (lane == 0) {
      if (MPF && warp < 10 && b < 96) bulk_prefetch(prm.w_mod + (size_t)(b * 6 + warp - 4) * (6 * DM), 2 * DM * 2);
      const int c0 = warp < 9 ? 1 : 8, c1 = warp < 11 ? c0 : 16, c2 = warp < 11 ? c0 : 3;
#pragma unroll
      for (int j = 0; j < 7; j++) mbar_init(sBar + (warp - 4) * 56 + j * 8, j == 0 ? c0 : j < 5 ? c1 : c2);
      *reinterpret_cast<uint4*>(smem_raw + SM_ZERO) = make_uint4(0u, 0u, 0u, 0u);
      asm volatile("fence.mbarrier_init.release.cluster;" ::: "memory");
    }
    __syncwarp();
    CL_WAIT();
    CL_ARRIVE();
    bar_sync(9, 288);
  }
  if (warp < 4) {
    auto ffn_box = [&](int fb) {
      tma_load_2d(sb + (fb == 5 || fb == 6 ? -57600 : SM_WG) + fb * 11520, fb >= 4 ? &mWu : &mWg, sBar + B_FFN, (b * 36) & ~7, (fb & 3) * 144);
    };
    if (__shfl_sync(~0u, tid, 0) == 0) {
     if (lane == 0) {
      const uint64_t pol = pol_first();
      auto kv_load = [&](int t) {
        const int s = t & 3;
        mbar_wait(sBar + B_EMPTYA + s * 8, (t >> 2) & 1);
        mbar_expect_tx(sBar + B_FULLA + s * 8, 32768);
        if (EF & 1) tma_load_2d_mc_h(sb + s * 32768 + rank * 16384, (t & 1) ? &mV : &mK, sBar + B_FULLA + s * 8, rank * 64, kg * 4 * SK + (t >> 1) * 128, pol);
        else tma_load_2d_mc(sb + s * 32768 + rank * 16384, (t & 1) ? &mV : &mK, sBar + B_FULLA + s * 8, rank * 64, kg * 4 * SK + (t >> 1) * 128);
      };
#pragma unroll 1
      for (int i = 0, g = 2; i < 28; i++) {
        const int hh = (i >> 2) + 2 + (i >= 20);
        if (XO && i == XO) {
          tma_load_3d_mc(sb + QG + rank * (QG / 2), &mX, sBar + B_X1, 0, qt * 128 + 64 + rank * 32, 0);
          mbar_expect_tx(sBar + B_X1, QG);
        }
        if (XW && i == XW - 1) mbar_wait(sBar + B_X, 0);
        if (i < 7 && ((MM >> i) & 1)) {
          const uint32_t mb = sBar + B_MM + __popc(MM & ((1 << i) - 1)) * 8;
          bulk_load(sb + SM_MB, prm.mod1 + (b & 7) * 144, 2304, mb);
          mbar_expect_tx(mb, 2304);
        }
        if (i == 3) mbar_wait(sBar + B_M, 0);
        if (i == QTH) mbar_wait(sBar + B_M + 8, 0);
        if (!(i & 3)) {
          if (i) mbar_wait(sBar + B_EMPTYQ + g * 8, i >= 16);
          else if (QW) mbar_wait(sBar + B_X, 0);
          mbar_expect_tx(sBar + B_FULLQ + g * 8, QG);
        }
        if (EF & 2) tma_load_2d_h(sb + g * QG + (i & 3) * 18432, &mWq, sBar + B_FULLQ + g * 8, hcol + (hh & 6) * 128 + (hh & 1) * 64, (i & 3) * 144, pol);
        else tma_load_2d(sb + g * QG + (i & 3) * 18432, &mWq, sBar + B_FULLQ + g * 8, hcol + (hh & 6) * 128 + (hh & 1) * 64, (i & 3) * 144);
        if ((i & 3) == 3 && ++g == 3) g = 0;
      }
#pragma unroll 1
      for (int u = 0; u < 128; u++) kv_load(u < 5 || u == 127 ? u : (u & 1) ? u + 1 : u - 1);
      if (!GX) mbar_wait(sBar + B_X, 1);
      {
        mbar_expect_tx(sBar + B_FFN, 2 * DM * 80);
        mbar_expect_tx(sBar + B_FD, 9 * 5120);
#pragma unroll 1
        for (int i = 0; i < 18; i++) {
          const int g = i & 3;
          mbar_wait(sBar + (i < 4 ? B_EMPTYA : B_EMPTYO) + g * 8, i >= 8 && !(i & 4));
          KSTAMP(270 + i);
          mbar_expect_tx(sBar + B_FULLO + g * 8, 32768);
          tma_load_4d_h(sb + g * 32768, &mWo, sBar + B_FULLO + g * 8, (i >> 1) * 64, 0, rank, kg * 4 + (i & 1) * 2, pol);
        }
        mbar_expect_tx(sBar + B_XR, 16 * 1152);
      }
     }
     __syncwarp();
     CL_WAIT();
     {
        const int lane = get_lane();
        mbar_wait(sBar + B_EMPTYO + 16, 1);
        if (lane < 16) bulk_load(sb + SM_X2 + lane * 1168, prm.x + (size_t)(qt * 128 + hg * 16 + lane) * DM, 1152, sBar + B_XR);
        __syncwarp();
        if (lane == 0) {
          mbar_wait(sBar + B_EMPTYO + 24, 1);
          if (LATEG & 4) mbar_wait(sBar + B_G1, 0);
          tma_load_3d(sb + SM_WD, &mWd, sBar + B_FD, 0, b * 36, 0);
          mbar_wait(sBar + B_EMPTYO, 0);
          if (LATEG & 2) mbar_wait(sBar + B_G1, 0);
          ffn_box(5); ffn_box(6);
        }
      }
    } else if (warp == 3) {
#pragma unroll 1
      for (int i = 1, g = 0; i < 7; i++) {
        mbar_wait(sBar + B_FULLQ + g * 8, i >= 3 && i < 6);
        if (++g == 3) g = 0;
        if (i == 0) { ES(96, 0, 9); } else { KSTAMP(170 + i * 2); } bar_sync(1, 288); if (i == 0) { ES(96, 0, 10); } else { KSTAMP(171 + i * 2); }
      }
      long long nxt = 0;
#pragma unroll 1
      for (int u = 0; u < 128; u++) {
        const int t = (u == 0 || u == 127) ? u : (u & 1) ? u + 1 : u - 1;
        mbar_wait(sBar + B_FULLA + (t & 3) * 8, (t >> 2) & 1);
        if (QL ? (t & 31) == 30 && t < 96 : t == 94) mbar_wait(sBar + B_QH, QL ? (t >> 5) & 1 : 0);
        if (!(t & 3)) *reinterpret_cast<volatile uint32_t*>(smem_raw + SM_ZERO + 12) = t >> 2;
        if (!(t & 1) || t == 127) { KSTAMP((t + 1) & ~1);
          bar_sync(1, 288); KSTAMP(((t + 1) & ~1) + 1); }
        else { bar_sync(10, 160); }
      }
      if (lane < 2) mbar_expect_tx(sBar + B_XF + lane * 8, 8192);
#pragma unroll 1
      for (int i = 0; i < 18; i++) {
        if (XG != 1) mbar_wait(sBar + B_FULLO + (i & 3) * 8, (i >> 2) & 1);
        KSTAMP(190 + i);
        if (XG == 2) { KSTAMP(130 + i * 2); if (MG && i == 0) bar_sync(10, 160); else bar_sync(1, 288); KSTAMP(131 + i * 2); }
        if (GX && i == 3) mbar_wait(sBar + B_X, 1);
        if ((i & 1) && i > 1 && i < 17) {
          const uint32_t xf = sBar + B_XF + ((i - 2) & 2) * 4;
          KSTAMP(260 + (i >> 1));
          mbar_wait(xf, ((i - 2) >> 2) & 1);
          __syncwarp();
          if (lane == 0) mbar_expect_tx(xf, 8192);
        }
        if (XG == 1) mbar_wait(sBar + B_FULLO + (i & 3) * 8, (i >> 2) & 1);
        if (XG != 2) { KSTAMP(130 + i * 2); if (MG && i == 0) bar_sync(10, 160); else bar_sync(1, 288); KSTAMP(131 + i * 2); }
      }
    } else if (warp > 0) {
      const int st = tid - 32;
      mbar_wait(sBar + B_FULLQ + 16, 0);
      mbar_wait(sBar + B_FULLQ + 16, 1);
      const bf16* const kvp = (rank ? prm.v : prm.k) + ((size_t)kg * 4 * SK + qt * 128) * DH;
      if (st == 0) bulk_prefetch(kvp, 32768);
      mbar_wait(sBar + B_FULLA, 0);
      mbar_wait(sBar + B_FULLA, 1);
      if (warp == 1) {
#pragma unroll 1
        for (int grp = b < 72 ? b : 288; grp < 288; grp += 72) {
          float a[8];
#pragma unroll
          for (int i = 0; i < 8; i++) a[i] = 0.f;
#pragma unroll 2
          for (int r = lane; r < DM; r += 32) {
            uint4 v;
            if (EF & 16) asm("ld.global.nc.L2::cache_hint.v4.u32 {%0,%1,%2,%3}, [%4], %5;" : "=r"(v.x), "=r"(v.y), "=r"(v.z), "=r"(v.w) : "l"(prm.w_mod + (size_t)r * (6 * DM) + 2 * DM + grp * 8), "l"(pol_first()));
            else v = __ldg(reinterpret_cast<const uint4*>(prm.w_mod + (size_t)r * (6 * DM) + 2 * DM + grp * 8));
            float s = silu_bf(__bfloat162float(prm.c[r]));
            a[0] += s * bf_lo(v.x); a[1] += s * bf_hi(v.x); a[2] += s * bf_lo(v.y); a[3] += s * bf_hi(v.y);
            a[4] += s * bf_lo(v.z); a[5] += s * bf_hi(v.z); a[6] += s * bf_lo(v.w); a[7] += s * bf_hi(v.w);
          }
#pragma unroll
          for (int i = 0; i < 8; i++) a[i] = warp_sum(a[i]);
          if (lane == 0) {
            const int kind = grp / 72;
#pragma unroll
            for (int i = 0; i < 4; i++) {
              uint32_t w = pack_bf16(a[2 * i], a[2 * i + 1]);
              if (kind == 2) w = hadd2(w, 0x3f803f80u);
              reinterpret_cast<uint32_t*>(smem_raw + SM_M2)[i * 4 + kind] = w;
            }
            if (kind == 3) {
              fence_async();
              asm volatile("cp.async.bulk.global.shared::cta.bulk_group [%0], [%1], 64;" ::"l"(g_mod2 + b * 4), "r"(sb + SM_M2) : "memory");
              asm volatile("cp.async.bulk.commit_group;\ncp.async.bulk.wait_group 0;" ::: "memory");
              if (SIDEF & 1) asm volatile("fence.acq_rel.gpu;" ::: "memory");
              cnt_arrive(C_SIDE);
            }
          }
        }
        __syncwarp();
        bar_sync(8, 160);
        if (lane < 8) asm volatile("red.relaxed.gpu.global.add.u32 [%0], 1;" ::"l"(&g_cnt[(C_Q + qt * 8 + lane) * 32 + 1]) : "memory");
        PSTAMP(32, 56);
        const int lane = get_lane();
        PSTAMP(32, 57);
        cnt_wait1((C_Q + qt * 8 + hg) * 32 + 1, 8);
        PSTAMP(32, 59);
        if (lane == 0) mbar_arrive(sBar + B_G2);
        uint32_t k1 = ~0u, k2 = ~0u;
        uint4 hv[4];
        uint2 hw = make_uint2(0u, 0u);
        auto h_load = [&]() {
          const int r1 = k1 & (SQ - 1), r2 = k2 & (SQ - 1);
          const int r = lane < 16 ? r1 : r2;
          const int c = ((r >> 5) & 3) * 32 + (r >> 7) * 2 + ((r >> 4) & 1);
          const uint4* p = g_ones + F_HX + (c * 288 + (lane >= 16 && (r1 >> 4) == (r2 >> 4) ? 144 : 0) + (lane & 15));
#pragma unroll
          for (int i = 0; i < 4; i++) hv[i] = ldr4(p + i * 16);
          hw = ldr2(reinterpret_cast<const uint2*>(p + 64) - (lane & 15));
        };
#pragma unroll
        for (int i = 0; i < 4; i++) hv[i] = make_uint4(0u, 0u, 0u, 0u);
        const uint4* kp = g_ones + F_KEY + (b & 31) * 64 + lane * 2;
        auto merge = [](uint32_t& m1, uint32_t& m2, uint32_t n1, uint32_t n2) { m2 = min(max(m1, n1), min(m2, n2)); m1 = min(m1, n1); };
#pragma unroll 1
        for (uint32_t n = 0;; n++) {
          uint4 a, c;
          asm volatile("ld.relaxed.gpu.global.v4.u32 {%0,%1,%2,%3}, [%8];\nld.relaxed.gpu.global.v4.u32 {%4,%5,%6,%7}, [%8+16];"
                       : "=r"(a.x), "=r"(a.y), "=r"(a.z), "=r"(a.w), "=r"(c.x), "=r"(c.y), "=r"(c.z), "=r"(c.w) : "l"(kp) : "memory");
          const bool all = !__any_sync(~0u, unset(a) || unset(c));
          merge(a.x, a.y, a.z, a.w);
          merge(a.x, a.y, c.x, c.y);
          merge(a.x, a.y, c.z, c.w);
          const uint32_t m1 = __reduce_min_sync(~0u, a.x);
          const uint32_t m2 = __reduce_min_sync(~0u, a.x == m1 ? a.y : a.x);
          bool bad = m1 != k1 || m2 != k2 || hw.x == ~0u || hw.y == ~0u;
#pragma unroll
          for (int i = 0; i < 4; i++) bad |= unset(hv[i]);
          bad = __any_sync(~0u, bad);
          if (all && !bad) break;
          if (n > (1u << 15)) { SETERR(4); break; }
          if (bad) { k1 = m1; k2 = m2; h_load(); if (FW == 4) asm volatile("st.volatile.shared.b32 [%0], %1;" ::"r"(sb + SM_ZERO), "r"(~k2) : "memory"); }
        }
        PSTAMP(32, 60);
        {
          const uint32_t ha = sb + SM_T + T_H + (lane >> 4) * 1152 + (lane & 15) * 16;
#pragma unroll
          for (int i = 0; i < 4; i++) sts128(ha + i * 256, hv[i]);
          asm volatile("st.shared.v2.b32 [%0], {%1,%2};" ::"r"(ha + 1024 - (lane & 15) * 8), "r"(hw.x), "r"(hw.y) : "memory");
        }
        if (lane == 0) asm volatile("st.shared.v2.b32 [%0], {%1,%2};" ::"r"(sb + SM_T + 128), "r"(~k1), "r"(~k2) : "memory");
        __syncwarp();
        if (lane == 0) mbar_arrive(sBar + B_G3);
        PSTAMP(32, 61);
      } else {
#pragma unroll
        for (int i = 0; i < 4; i++) sts128(sb + SM_FILL + i * 512 + lane * 16, make_uint4(~0u, ~0u, ~0u, ~0u));
        fence_async();
        __syncwarp();
        const int lane = get_lane();
        const uint32_t dump = sb + SM_RED + 64 + lane * 4;
        auto touch128 = [&](const void* q) { asm volatile("cp.async.ca.shared.global.L2::128B [%0], [%1], 4;" ::"r"(dump), "l"(q) : "memory"); };
        auto touch256 = [&](const void* q) { asm volatile("cp.async.ca.shared.global.L2::256B [%0], [%1], 4;" ::"r"(dump), "l"(q) : "memory"); };
#pragma unroll 1
        for (int p = 2; p < FILLP; p++) {
          if (*reinterpret_cast<volatile uint32_t*>(smem_raw + SM_ZERO + 12) < p) mbar_wait(sBar + B_FULLA, p & 1);
          if (lane == 0) {
            if ((p & 7) == KVP && p < 24) {
              if (EF & 64) bulk_prefetch_f(kvp + (size_t)((p >> 3) + 1) * SK * DH, 32768);
              else bulk_prefetch(kvp + (size_t)((p >> 3) + 1) * SK * DH, 32768);
            }
            if (p == 16 + QPF) {
              cnt_wait1((C_Q + b) * 32 + 2, 8);
              asm volatile("fence.acq_rel.gpu;" ::: "memory");
              if (!QL) mbar_arrive(sBar + B_QH);
            }
            if (QL && (p & 7) == QPF && p < 24) {
              asm volatile("fence.proxy.async.global;" ::: "memory");
              mbar_expect_tx(sBar + B_QH, 32768);
              bulk_load(sb + SM_STASH + (p >> 3) * 32768, g_q + (b * 4 + (p >> 3) + 1) * 2048, 32768, sBar + B_QH);
            }
            if (!(TCH & 2) && XQ < 3 && !NQP && (p & 7) == QPF && p < 24) bulk_prefetch(g_q + ((size_t)b * 4 + (p >> 3) + 1) * 2048, 32768);
            if (!(TCH & 4) && p == FILLP - 1) bulk_prefetch(prm.x + (size_t)(qt * 128 + hg * 16) * DM, 16 * DM * 2);
            if (p == WOP) bulk_prefetch(prm.wo + ((size_t)kg * 1024 + (b & 31) * 32) * DM, 32 * DM * 2);
            if (p >= PF0 && p < PF0 + 9) {
              const int i = p - PF0, m = PFO ? 2 - i / 3 : i / 3;
              if (((PFM >> m) & 1) && !((PFM & 8) && m == 1 && b >= 32 && b < 96))
              bulk_prefetch((m == 0 ? prm.wg : m == 1 ? prm.wu : prm.wd) + (size_t)(b * 3 + i % 3) * (DM * 12), DM * 24);
            }
          }
          __syncwarp();
          if ((TCH & 2) && (p & 7) == QPF && p < 24) {
#pragma unroll
            for (int i = 0; i < 4; i++) touch256(g_q + ((size_t)b * 4 + (p >> 3) + 1) * 2048 + (i * 32 + lane) * 16);
          }
          if ((TCH & 1) && p >= TF0 && p < TF0 + 9) {
            const int i = p - TF0, c0 = (b * 36) & ~7;
#pragma unroll
            for (int j = 0; j < (FAKEB ? 0 : 4); j++) {
              const int r = i * 64 + (j & 1) * 32 + lane;
              const bf16* q = ((j & 2) ? prm.wu : prm.wg) + (size_t)r * FF + c0;
              touch128(q);
              if ((c0 & 63) > 24) touch128(q + 38);
            }
            if (lane < 20) touch256(prm.wd + min(b * 162 + i * 20 + lane, 128 * 162 - 1) * 128);
          }
          if ((TCH & 16) && p >= TF0 && p < TF0 + 9 / TN) {
            const int i = (p - TF0) * TN, c0 = (b * 36) & ~7;
#pragma unroll
            for (int j = 0; j < TN; j++) {
              const bf16* q = prm.wu + (size_t)(144 + (i + j) * 32 + lane) * FF + c0;
              touch128(q);
              if ((c0 & 63) > 24) touch128(q + 38);
              if (lane < 20) touch256(prm.wd + min(b * 162 + (i + j) * 20 + lane, 128 * 162 - 1) * 128);
            }
          }
          if ((TCH & 4) && p >= FILLP - 3 && lane < 24) touch256(prm.x + (size_t)(qt * 128 + hg * 16) * DM + ((p - FILLP + 3) * 24 + lane) * 128);
          if ((TCH & 8) && p >= TW0 && p < TW0 + TWN) {
            const int i = (qt * TWN + p - TW0) * 144 % 2304;
#pragma unroll
            for (int j = 0; j < 5; j++)
              if (j < 4 || lane < 16) touch256(prm.wo + (size_t)(hcol + i / 576 * 256) * DM + (i % 576 + j * 32 + lane) * 128);
          }
          if (p >= FILL0)
#pragma unroll 1
          for (int z = 0; z < (FGAP ? FGN : 1); z++) {
            if (FGAP && z) __nanosleep(FGAP);
            const int i = lane >= 16 ? lane - 16 : (p - FILL0) * FILLN + lane + 5;
            if ((lane >= 16 ? p == FILLS && i < 5 : lane < FILLN && i < FILLMAX && i >= FILLMIN) && (!FGAP || (lane & (FGN - 1)) == z)) {
              uint4* const fp = g_ones + (i < 5 ? b * 640 : F_PART - 640 + b * PS) + i * 128;
              if (EF & 32) asm volatile("cp.async.bulk.global.shared::cta.bulk_group.L2::cache_hint [%0], [%1], 2048, %2;" ::"l"(fp), "r"(sb + SM_FILL), "l"(pol_first()) : "memory");
              else asm volatile("cp.async.bulk.global.shared::cta.bulk_group [%0], [%1], 2048;" ::"l"(fp), "r"(sb + SM_FILL) : "memory");
            }
          }
        }
        asm volatile("cp.async.bulk.commit_group;\ncp.async.bulk.wait_group 0;" ::: "memory");
        if (SIDEF & 2) asm volatile("fence.acq_rel.gpu;" ::: "memory");
        __syncwarp();
        PSTAMP(64, 51);
        if (lane == 0) {
          cnt_arrive(C_SIDE);
          PSTAMP(64, 52);
          cnt_wait(C_SIDE, 128 + 72);
          PSTAMP(64, 53);
          asm volatile("mbarrier.arrive.shared::cta.b64 _, [%0];" ::"r"(sBar + B_X) : "memory");
        }
        __syncwarp();
        if (lane == 0) {
          asm volatile("prefetch.tensormap [%0];\nprefetch.tensormap [%1];\nprefetch.tensormap [%2];\nprefetch.tensormap [%3];" ::"l"(&mWo), "l"(&mWg), "l"(&mWu), "l"(&mWd) : "memory");
          mbar_wait(sBar + B_ST, 0);
          mbar_expect_tx(sBar + B_MD, 5760);
          bulk_load(sb + SM_MD, g_mod2, 4608, sBar + B_MD);
          bulk_load(sb + SM_MD + 4608, prm.w_r, 1152, sBar + B_MD);
        }
        __syncwarp();
        {
          mbar_wait(sBar + B_MD, 0);
          float sA = 0.f, sB = 0.f;
#pragma unroll 1
          for (int i = lane; i < 288; i += 32) {
            const uint4 m = lds128(sb + SM_MD + i * 16);
            const uint32_t w = *reinterpret_cast<const uint32_t*>(smem_raw + SM_MD + 4608 + i * 4);
            const float a0 = bf_lo(m.z) * bf_lo(w), a1 = bf_hi(m.z) * bf_hi(w);
            const uint32_t hi = pack_bf16(a0, a1);
            *reinterpret_cast<uint2*>(smem_raw + SM_MOD + i * 8) = make_uint2(pack_bf16(a0 - bf_lo(hi), a1 - bf_hi(hi)), hi);
            sA += a0 + a1;
            sB = fmaf(bf_lo(m.y), bf_lo(w), fmaf(bf_hi(m.y), bf_hi(w), sB));
          }
          sA = warp_sum(sA); sB = warp_sum(sB);
          *reinterpret_cast<float2*>(smem_raw + SM_ZERO + 16) = make_float2(sA, sB);
          __syncwarp();
          if (lane == 0) mbar_arrive(sBar + B_TB);
        }
        if (lane == 0) {
#pragma unroll 1
          for (int r = 0, fb = 0; r < 4; r++) {
#pragma unroll 1
            for (const int fe = (FFNS >> (r * 4)) & 15; fb < fe; fb++) ffn_box(fb == 5 ? 7 : fb);
            if (r < 3) mbar_wait(sBar + B_EMPTYO + 16, r & 1);
          }
        }
        __syncwarp();
        const uint32_t* const tsu = reinterpret_cast<const uint32_t*>(smem_raw + SM_T);
        const int row = qt * 128 + hg * 16 + lane;
        auto out_row = [&]() {
          asm volatile("cp.async.bulk.global.shared::cta.bulk_group [%0], [%1], 1152;" ::"l"(prm.out + (size_t)row * DM), "r"(sb + SM_X2 + lane * 1168) : "memory");
        };
        bar_sync(11, 288);
        fence_async();
        const bool top = (*(volatile const uint32_t*)(tsu + 34) >> lane) & 1;
        if (lane < 16 && (FW == 2 || !top)) out_row();
        mbar_wait(sBar + B_G3, 0);
        if (FW != 2 && FW != 3 && top && row != (int)(~*(volatile const uint32_t*)(tsu + 32) & (SQ - 1)) && row != (int)(~*(volatile const uint32_t*)(tsu + 33) & (SQ - 1))) out_row();
        asm volatile("cp.async.bulk.commit_group;\ncp.async.bulk.wait_group.read 0;" ::: "memory");
      }
    }
  } else {
    const int cw = (warp >> 2) - 1;
    const int w8 = warp - 4;
    const int ct = tid - 128;
    const int lane = get_lane(), g = lane >> 2, t4 = lane & 3;
    uint32_t relBar;
    auto release = [&](int off) {
      if (lane < 2) mbar_arrive_cl(relBar + off);
    };
    auto release1 = [&](int off) {
      if (lane == 0) mbar_arrive_cl(relBar + off);
    };
    auto turn_begin = [&]() {
      asm volatile("{\n.reg .pred p;\nsetp.eq.b32 p, %0, 0;\n@p bar.sync 1, 288;\n@!p bar.sync 2, 256;\n}\n" ::"r"(cw) : "memory");
      wgmma_fence();
    };
    auto turn_end = [&]() { asm volatile("{\n.reg .pred p;\nsetp.eq.b32 p, %0, 0;\n@p bar.arrive 2, 256;\n@!p bar.arrive 1, 288;\n}\n" ::"r"(cw) : "memory"); };
    asm volatile("{\n.reg .pred p;\nsetp.eq.u64 p, %0, 0;\n@p trap;\n}\n" :: "l"(g_q) : "memory");
    ESC(7);
    asm volatile("setmaxnreg.inc.sync.aligned.u32 232;");
    float S[64], O[64];
    uint32_t P[32], Qf[32];
    constexpr uint32_t dB_k = mk_desc(SM_BASE, 16);
    constexpr uint32_t dB_n16 = mk_desc(SM_BASE, 16384);
    uint4* qpark;
    {
      uint32_t A[144];
      const uint32_t la = sb + cw * QG + (w8 & 2) * (QG / 4) + ((w8 & 1) * 16 + ((lane & 15) ^ (rank * 8))) * 128 + (((lane >> 4) ^ (lane & 7)) << 4);
      ESC(19);
      mbar_wait(sBar + B_X + cw * 8, 0);
      ESC(1);
      ln_rows(A, la, lane, [&]() { if (lane < 2) mbar_arrive(sBar + B_EMPTYQ + cw * 8); });
      CL_WAIT();
      ESC(2);
      bar_sync(3 + cw, 224);
      ESC(3);
      modulate(A, sb + SM_MT + t4 * 16);
      ESC(4);
      float qa[32];
      asm volatile("mapa.shared::cluster.u32 %0, %1, %2;" : "=r"(relBar) : "r"(sBar), "r"(rank ^ (get_lane() & 1)));
      qpark = g_q + (b * (4 * 8 * 256) + w8 * 32 + get_lane());
      if (cw == 0) { mbar_wait(sBar + B_FULLQ + 16, 0); ESC(9); }
#pragma unroll 1
      for (int hh = 2, gr = 2;; hh++) {
        asm volatile("{\n.reg .pred p, q;\nsetp.eq.b32 p, %0, 0;\nsetp.gt.and.s32 q, %1, 2, p;\n@q bar.sync 1, 288;\n@!p bar.sync 2, 256;\n}\n" ::"r"(cw), "r"(hh) : "memory");
        wgmma_fence();
        q_mma(qa, A, dB_k + gr * (QG >> 4));
        turn_end();
        wgmma_wait<0>();
        if (hh < 6) release1(B_EMPTYQ + gr * 8);
        else if (hh < 9) { release(B_EMPTYA + gr * 16); release(B_EMPTYA + gr * 16 + 8); }
        if (++gr == 3) gr = 0;
#pragma unroll
        for (int j = 0; j < 32; j++) qa[j] *= Q_SCALE;
#pragma unroll
        for (int j = 0; j < 4; j++) {
          const uint4 v = make_uint4(pack_bf16(qa[8 * j], qa[8 * j + 1]), pack_bf16(qa[8 * j + 2], qa[8 * j + 3]),
                                     pack_bf16(qa[8 * j + 4], qa[8 * j + 5]), pack_bf16(qa[8 * j + 6], qa[8 * j + 7]));
          if (EF & 256) {
            uint64_t pn;
            asm("createpolicy.fractional.L2::evict_normal.b64 %0, 1.0;" : "=l"(pn));
            asm volatile("st.global.L2::cache_hint.v4.u32 [%0], {%1,%2,%3,%4}, %5;" ::"l"(qpark + ((hh & 7) * 4 + j) * 256), "r"(v.x), "r"(v.y), "r"(v.z), "r"(v.w), "l"(hh >= 8 ? pol_first() : pn) : "memory");
          } else qpark[((hh & 7) * 4 + j) * 256] = v;
        }
        if (hh == 9) break;
        if (hh == 6) hh++;
      }
#pragma unroll
      for (int j = 0; j < 4; j++) {
        const uint4 v = __ldcg(qpark + j * 256);
        Qf[4 * j] = v.x; Qf[4 * j + 1] = v.y; Qf[4 * j + 2] = v.z; Qf[4 * j + 3] = v.w;
      }
#pragma unroll
      for (int j = 0; j < 16; j++) Qf[16 + j] = pack_bf16(qa[2 * j], qa[2 * j + 1]);
    }
    STAMP(5); GSTAMP(65); STAMP(0); GSTAMP(90);
    float mb0 = 0.f, mb1 = 0.f, l0 = 0.f, l1 = 0.f;
    int nz = 0;
    float i0 = 0.f, i1 = 0.f;
    auto o_scale = [&]() {
      float a0 = l0, a1 = l1;
      a0 += __shfl_xor_sync(~0u, a0, 1); a0 += __shfl_xor_sync(~0u, a0, 2);
      a1 += __shfl_xor_sync(~0u, a1, 1); a1 += __shfl_xor_sync(~0u, a1, 2);
      i0 = rcp(a0); i1 = rcp(a1);
    };
    auto o_frag = [&](int i) {
      return make_uint4(pack_bf16(O[i * 8] * i0, O[i * 8 + 1] * i0), pack_bf16(O[i * 8 + 2] * i1, O[i * 8 + 3] * i1),
                        pack_bf16(O[i * 8 + 4] * i0, O[i * 8 + 5] * i0), pack_bf16(O[i * 8 + 6] * i1, O[i * 8 + 7] * i1));
    };
    auto row_max = [&](float& x0, float& x1) {
      float y0 = fmaxf(S[0], S[1]), y1 = fmaxf(S[2], S[3]), z0 = fmaxf(S[4], S[5]), z1 = fmaxf(S[6], S[7]);
#pragma unroll
      for (int j = 2; j < 16; j += 2) {
        y0 = fmaxf(y0, fmaxf(S[j * 4], S[j * 4 + 1])); y1 = fmaxf(y1, fmaxf(S[j * 4 + 2], S[j * 4 + 3]));
        z0 = fmaxf(z0, fmaxf(S[j * 4 + 4], S[j * 4 + 5])); z1 = fmaxf(z1, fmaxf(S[j * 4 + 6], S[j * 4 + 7]));
      }
      x0 = fmaxf(y0, z0); x1 = fmaxf(y1, z1);
      x0 = fmaxf(x0, __shfl_xor_sync(~0u, x0, 1)); x1 = fmaxf(x1, __shfl_xor_sync(~0u, x1, 1));
      x0 = fmaxf(x0, __shfl_xor_sync(~0u, x0, 2)); x1 = fmaxf(x1, __shfl_xor_sync(~0u, x1, 2));
    };
    float s0, s1;
    auto shift = [&]() {
#pragma unroll
      for (int i = 0; i < 64; i++) S[i] -= (i & 2) ? mb1 : mb0;
    };
    auto exps = [&](int j0, int j1) {
#pragma unroll
      for (int j = j0; j < j1; j++) {
        S[j * 4] = ex2(S[j * 4]); S[j * 4 + 1] = ex2(S[j * 4 + 1]);
        S[j * 4 + 2] = ex2(S[j * 4 + 2]); S[j * 4 + 3] = ex2(S[j * 4 + 3]);
        if (HS == 0 || (HS == 2 && j < 8)) { s0 += S[j * 4] + S[j * 4 + 1]; s1 += S[j * 4 + 2] + S[j * 4 + 3]; }
      }
    };
    auto cvtP = [&]() {
#pragma unroll
      for (int i = 0; i < 32; i++) {
        if (HS & 1) asm volatile("cvt.rn.bf16x2.f32 %0, %1, %2;" : "=r"(P[i]) : "f"(S[2 * i + 1]), "f"(S[2 * i]));
        else P[i] = pack_bf16(S[2 * i], S[2 * i + 1]);
      }
      if (HS) {
        uint32_t t[16];
#pragma unroll
        for (int i = 0; i < 16; i++) t[i] = hadd2(P[(i >> 1) * 4 + (i & 1)], P[(i >> 1) * 4 + (i & 1) + 2]);
#pragma unroll
        for (int i = 0; i < 8; i++) t[i] = hadd2(t[(i >> 1) * 4 + (i & 1)], t[(i >> 1) * 4 + (i & 1) + 2]);
#pragma unroll
        for (int i = 0; i < 4; i++) t[i] = hadd2(t[(i >> 1) * 4 + (i & 1)], t[(i >> 1) * 4 + (i & 1) + 2]);
        if (HS == 1) {
          t[0] = hadd2(t[0], t[2]); t[1] = hadd2(t[1], t[3]);
          s0 = bf_lo(t[0]) + bf_hi(t[0]); s1 = bf_lo(t[1]) + bf_hi(t[1]);
        } else if (HS == 2) {
          s0 += bf_lo(t[2]) + bf_hi(t[2]); s1 += bf_lo(t[3]) + bf_hi(t[3]);
        } else {
          s0 = (bf_lo(t[0]) + bf_hi(t[0])) + (bf_lo(t[2]) + bf_hi(t[2])); s1 = (bf_lo(t[1]) + bf_hi(t[1])) + (bf_lo(t[3]) + bf_hi(t[3]));
        }
      }
    };
    auto issue_qk = [&](uint32_t db) {
#pragma unroll
      for (int kk = 0; kk < 8; kk++)
        wgmma128_rs<0>(S, Qf[kk * 4], Qf[kk * 4 + 1], Qf[kk * 4 + 2], Qf[kk * 4 + 3], db + (kk >> 2) * 1024 + (kk & 3) * 2, kk != 0);
    };
    auto issue_pv = [&](uint32_t db, int first) {
#pragma unroll
      for (int kk = 0; kk < 8; kk++) {
        if (kk == TE_POS) turn_end();
        wgmma128_rs<1>(O, P[kk * 4], P[kk * 4 + 1], P[kk * 4 + 2], P[kk * 4 + 3], db + kk * 128, kk ? 1 : !first);
      }
      wgmma_commit();
      if (TE_POS == 8) turn_end();
    };
    auto sched_fence = [&]() {
      if (HS & 1) asm volatile("st.shared.v2.f32 [%0], {%1,%2};" ::"r"(sb + SM_RED), "f"(S[EH * 4 - 2]), "f"(S[EH * 4 - 1]) : "memory");
      else asm volatile("st.shared.v2.f32 [%0], {%1,%2};" ::"r"(sb + SM_RED), "f"(s0), "f"(s1) : "memory");
    };
    {
      STAMP(6);
      turn_begin();
      issue_qk(dB_k);
      wgmma_commit();
      turn_end();
      wgmma_wait<0>();
      release(B_EMPTYA);
      bool redo = sb >> 31;
#pragma unroll 1
      do {
        if (__builtin_expect(redo, 0)) {
          row_max(mb0, mb1);
          shift();
          nz = 1;
        }
        l0 = 0.f; l1 = 0.f;
#pragma unroll
        for (int i = 0; i < 32; i++) {
          const float e0 = ex2(S[2 * i]), e1 = ex2(S[2 * i + 1]);
          P[i] = pack_bf16(e0, e1);
          if (i & 1) l1 += e0 + e1; else l0 += e0 + e1;
        }
        redo = __any_sync(~0u, !(l0 <= LAZY_LIMIT && l1 <= LAZY_LIMIT && l0 >= LAZY_LOW && l1 >= LAZY_LOW)) && !redo;
      } while (__builtin_expect(redo, 0));
    }
    const uint4* qn = qpark + 8 * 256;
    if (!QL) asm volatile("" : "+l"(qn));
    uint32_t kd = dB_k + 4096;
#pragma unroll 1
    for (int t = 1; t < 64; t++, kd ^= 4096) {
      const int j = t & 15, h = t >> 4;
      const int ks = (t & 1) * 2, vs = 3 - ks;
      turn_begin();
      issue_qk(kd);
      wgmma_commit();
      if (__builtin_expect(j == 1 && h > XS, 0)) {
#pragma unroll
        for (int i = RS0; i < 8; i++) sts128(sb + SM_STASH + (h - 1) * 32768 + i * 4096 + ct * 16, o_frag(i));
        wgmma_fence();
      }
      if (cw == 0) bar_sync(10, 160);
      issue_pv(kd ^ (dB_k ^ (dB_n16 + 6144)), j == 1);
      wgmma_wait<1>();
      release(B_EMPTYA + ks * 8);
      if (j == 15 && h < 3 - XQ) {
#pragma unroll
        for (int i = 0; i < 8; i++) {
          uint4 v;
          if (QL) v = lds128(sb + SM_STASH + h * 32768 + i * 4096 + ct * 16);
          else if (EF & 4) asm volatile("ld.global.cg.L2::cache_hint.v4.u32 {%0,%1,%2,%3}, [%4], %5;" : "=r"(v.x), "=r"(v.y), "=r"(v.z), "=r"(v.w) : "l"(qn + i * 256), "l"(pol_first()));
          else v = __ldcg(qn + i * 256);
          Qf[4 * i] = v.x; Qf[4 * i + 1] = v.y; Qf[4 * i + 2] = v.z; Qf[4 * i + 3] = v.w;
        }
        qn += 8 * 256;
      }
      if (__builtin_expect(nz, 0)) shift();
      s0 = 0.f; s1 = 0.f;
      exps(0, EH);
      sched_fence();
      wgmma_wait<0>();
      release(B_EMPTYA + vs * 8);
      float lo = 0.f;
      if (__builtin_expect(j == 0, 0)) {
        o_scale();
        l0 = 0.f; l1 = 0.f;
        lo = LAZY_LOW;
      }
#if !(HS & 1)
      bool bad = __any_sync(~0u, !(s0 <= LAZY_LIMIT && s1 <= LAZY_LIMIT));
#endif
      if (__builtin_expect(!bad, 1)) {
        exps(EH, 16);
        cvtP();
        bad = __any_sync(~0u, !(s0 <= LAZY_LIMIT && s1 <= LAZY_LIMIT && s0 >= lo && s1 >= lo));
      }
      if (__builtin_expect(bad, 0)) {
        const uint32_t* kp = reinterpret_cast<const uint32_t*>(prm.k + ((size_t)kg * 4 * SK + t * 128 + g) * DH) + t4;
        const uint4* qp = qpark + h * (8 * 256);
        float4 tmp[16];
        uint4 qf[8];
#pragma unroll
        for (int kk = 0; kk < 8; kk++) qf[kk] = h < 3 ? __ldcg(qp + kk * 256) : make_uint4(Qf[4 * kk], Qf[4 * kk + 1], Qf[4 * kk + 2], Qf[4 * kk + 3]);
#pragma unroll 1
        for (int jn = 0; jn < 16; jn++) {
          float c[4] = {0.f, 0.f, 0.f, 0.f};
#pragma unroll
          for (int kk = 0; kk < 8; kk++) mma16816(c, qf[kk].x, qf[kk].y, qf[kk].z, qf[kk].w, __ldg(kp + jn * 512 + kk * 8), __ldg(kp + jn * 512 + kk * 8 + 4));
          tmp[jn] = make_float4(c[0], c[1], c[2], c[3]);
        }
#pragma unroll
        for (int jn = 0; jn < 16; jn++) { const float4 c = tmp[jn]; S[jn * 4] = c.x; S[jn * 4 + 1] = c.y; S[jn * 4 + 2] = c.z; S[jn * 4 + 3] = c.w; }
        float x0, x1;
        row_max(x0, x1);
        const float n0 = j ? fmaxf(mb0, x0) : x0, n1 = j ? fmaxf(mb1, x1) : x1;
        const float f0 = j ? ex2(mb0 - n0) : 1.f, f1 = j ? ex2(mb1 - n1) : 1.f;
        mb0 = n0; mb1 = n1;
        l0 *= f0; l1 *= f1;
#pragma unroll
        for (int i = 0; i < 16; i++) { O[i * 4] *= f0; O[i * 4 + 1] *= f0; O[i * 4 + 2] *= f1; O[i * 4 + 3] *= f1; }
        s0 = 0.f; s1 = 0.f;
        shift();
        nz = 1;
        exps(0, 16);
        cvtP();
      }
      if (RS0 && __builtin_expect(j == 0, 0)) {
#pragma unroll
        for (int i = 0; i < RS0; i++) sts128(sb + SM_STASH + (h - 1) * 32768 + i * 4096 + ct * 16, o_frag(i));
      }
      l0 += s0; l1 += s1;
    }
    STAMP(70); GSTAMP(66);
    int nc = 0;
    uint32_t ra[7], rb[7], ld[16];
    const uint32_t* const ap = reinterpret_cast<const uint32_t*>(g_ones + F_PART) + (qt * 8 + hg) * (PS * 4) + w8 * 32 + get_lane();
    auto ld_sum = [&](uint32_t& a, uint32_t& c, const uint32_t* w) {
      a = pack_bf16((bf_lo(w[0]) + bf_lo(w[2])) + (bf_lo(w[4]) + bf_lo(w[6])), (bf_hi(w[0]) + bf_hi(w[2])) + (bf_hi(w[4]) + bf_hi(w[6])));
      c = pack_bf16((bf_lo(w[1]) + bf_lo(w[3])) + (bf_lo(w[5]) + bf_lo(w[7])), (bf_hi(w[1]) + bf_hi(w[3])) + (bf_hi(w[5]) + bf_hi(w[7])));
    };
    {
      const int lane = get_lane();
      uint32_t A[128];
      float c0[32], kp[16];
      auto ld_a = [&](int i0, int i1) {
#pragma unroll
        for (int i = i0; i < i1; i++) {
          const uint4 v = lds128(sb + SM_STASH + i * 4096 + ct * 16);
          A[i * 4] = v.x; A[i * 4 + 1] = v.y; A[i * 4 + 2] = v.z; A[i * 4 + 3] = v.w;
        }
      };
      ld_a(MG == 2 ? 8 : 0, MGL);
      if (OSP == 1) { o_scale(); asm volatile("st.shared.v2.f32 [%0], {%1,%2};" ::"r"(sb + SM_RED), "f"(i0), "f"(i1) : "memory"); }
      turn_begin();
#pragma unroll
      for (int kk = 0; kk < 8; kk++) wgmma128_rs<1>(O, P[kk * 4], P[kk * 4 + 1], P[kk * 4 + 2], P[kk * 4 + 3], dB_n16 + 6144 + kk * 128, 1);
      wgmma_commit();
      ld_a(MG == 2 && MGL < 8 ? 8 : MGL, 16);
      if (cw == 0) bar_sync(10, 160);
      wgmma_fence();
#pragma unroll
      for (int kk = 0; kk < 16; kk++) wgmma64_rs(c0, A[kk * 4], A[kk * 4 + 1], A[kk * 4 + 2], A[kk * 4 + 3], dB_k + kk * 128, kk != 0);
      wgmma_commit();
      turn_end();
      if (OSP == 2) {
        float z;
        asm volatile("ld.shared.f32 %0, [%1];" : "=f"(z) : "r"(sb + SM_ZERO) : "memory");
        l0 += z; l1 += z;
      }
      if (OSP != 1) o_scale();
      wgmma_wait<1>();
#pragma unroll
      for (int i = 16; i < 24; i++) {
        const uint4 v = lds128(sb + SM_STASH + i * 4096 + ct * 16);
        A[i * 4] = v.x; A[i * 4 + 1] = v.y; A[i * 4 + 2] = v.z; A[i * 4 + 3] = v.w;
      }
#pragma unroll
      for (int i = 0; i < 8; i++) {
        const uint4 v = o_frag(i);
        A[96 + i * 4] = v.x; A[96 + i * 4 + 1] = v.y; A[96 + i * 4 + 2] = v.z; A[96 + i * 4 + 3] = v.w;
      }
      if (__any_sync(~0u, A[95] != 0x12345678u || A[64] != 0x9abcdef0u || lane == 0)) {
        release(B_EMPTYA + 24);
        release1(B_ST);
      }
      STAMP(71);
      uint32_t xb = w8 * 1024 + lane * 16;
      const uint32_t peer = __shfl_sync(~0u, relBar, 1) - sBar;
      int gr = MG ? 2 : 0;
      wgmma_wait<0>();
      release1(B_EMPTYO);
#pragma unroll
      for (int i = 0; i < 8; i++) ld[i] = ~0u;
#pragma unroll
      for (int i = 0; i < 5; i++) ra[i] = rb[i] = 0;
      auto ld_take = [&]() {
        uint32_t a, d;
        ld_sum(a, d, ld);
#pragma unroll
        for (int i = 0; i < 5; i++)
          if (nc == i) { ra[i] = a; rb[i] = d; }
        nc += !__any_sync(~0u, nan2(hadd2(a, d)));
      };
      uint32_t* dp = reinterpret_cast<uint32_t*>(g_ones + F_PART) + (qt * 8 + w8) * (PS * 4) + kg * 512 + rank * 256 + lane;
      auto recv = [&]() {
        uint4 u[2];
#pragma unroll
        for (int j = 0; j < 2; j++) u[j] = lds128(sb + SM_XCH + xb + j * 512);
#pragma unroll
        for (int j = 0; j < 2; j++) {
          str1(dp + j * 128, pack_bf16(kp[j * 8] + bf_lo(u[j].x), kp[j * 8 + 1] + bf_hi(u[j].x)));
          str1(dp + j * 128 + 32, pack_bf16(kp[j * 8 + 2] + bf_lo(u[j].y), kp[j * 8 + 3] + bf_hi(u[j].y)));
          str1(dp + j * 128 + 64, pack_bf16(kp[j * 8 + 4] + bf_lo(u[j].z), kp[j * 8 + 5] + bf_hi(u[j].z)));
          str1(dp + j * 128 + 96, pack_bf16(kp[j * 8 + 6] + bf_lo(u[j].w), kp[j * 8 + 7] + bf_hi(u[j].w)));
        }
        dp += 2048;
        xb ^= 8192;
      };
#pragma unroll 1
      for (int c = 0;; c++) {
#pragma unroll
        for (int hd = 0; hd < 4; hd++) {
          if (MG && hd < 2 && c == 0) continue;
          if (!(hd & 1)) turn_begin();
          const uint32_t db = dB_k + (gr + (hd & 1)) * 1024;
#pragma unroll
          for (int kk = 0; kk < 8; kk++)
            wgmma64_rs(c0, A[hd * 32 + kk * 4], A[hd * 32 + kk * 4 + 1], A[hd * 32 + kk * 4 + 2], A[hd * 32 + kk * 4 + 3], db + kk * 128, (hd | kk) != 0);
          if (hd & 1) {
            wgmma_commit();
            if (hd == 1 || c < 8 || cw == 0) turn_end();
            if (hd == 1 ? c == 8 : (c & 7) != 0) {
              if (hd == 1) mbar_wait(sBar + B_XF + 8, 1);
              else if (XG == 2) mbar_wait(sBar + B_XF + (~c & 1) * 8, ((c - 1) >> 1) & 1);
              recv();
            }
            if (hd == 1 && c >= 3 && c < 8) {
              ld_take();
#pragma unroll
              for (int i = 0; i < 8; i++) ld[i] = ldr1(ap + nc * 2048 + i * 256);
            }
            if (hd == HINTH && c == 8 && cw == HINTW) bar_arrive(8, 160);
            if (hd == 3 && c == 8) {
              ld_take();
#pragma unroll
              for (int i = 0; i < 16; i++) ld[i] = ldr1(ap + 5 * 2048 + i * 256);
            }
            wgmma_wait<0>();
            release1(B_EMPTYO + gr * 4);
            gr = (gr + 2) & 7;
          }
        }
        if (c == 8) break;
        if (c == 0) mbar_wait(sBar + B_EMPTYA + 24, 0);
#pragma unroll
        for (int j = 0; j < 2; j++)
          asm volatile("st.async.shared::cluster.mbarrier::complete_tx::bytes.v4.b32 [%0], {%1,%2,%3,%4}, [%5];" ::"r"(sb + SM_XCH + xb + peer + j * 512),
                       "r"(pack_bf16(c0[j * 16 + 2], c0[j * 16 + 3])), "r"(pack_bf16(c0[j * 16 + 6], c0[j * 16 + 7])), "r"(pack_bf16(c0[j * 16 + 10], c0[j * 16 + 11])),
                       "r"(pack_bf16(c0[j * 16 + 14], c0[j * 16 + 15])), "r"(sBar + B_XF + (c & 1) * 8 + peer) : "memory");
#pragma unroll
        for (int j = 0; j < 16; j++) kp[j] = c0[(j >> 1) * 4 + (j & 1)];
      }
      STAMP(72); GSTAMP(67);
      uint2* const dst = reinterpret_cast<uint2*>(g_ones + F_PART) + ((qt * 8 + w8) * (PS / 128) + 32 + rank * 4 + kg) * 256 + lane;
#pragma unroll
      for (int jb = 0; jb < 8; jb++)
        asm volatile("st.relaxed.gpu.global.v2.u32 [%0], {%1,%2};" ::"l"(dst + jb * 32), "r"(pack_bf16(c0[jb * 4], c0[jb * 4 + 1])), "r"(pack_bf16(c0[jb * 4 + 2], c0[jb * 4 + 3])) : "memory");
    }
    STAMP(73);
    {
    const int lane = get_lane(), g = lane >> 2, t4 = lane & 3;
    uint32_t* const tsu = reinterpret_cast<uint32_t*>(smem_raw + SM_T);
    float* const tsf = reinterpret_cast<float*>(smem_raw + SM_T);
    const int row0 = qt * 128 + hg * 16;
    const int kq = w8 >> 1;
    uint32_t bg[9][10], bd[9][5];
    auto ld_bg = [&](int k0, int k1) {
      if (k0 == 0) mbar_wait(sBar + B_FFN, 0);
      const uint32_t wa = sb + (w8 == 3 || w8 == 5 ? -11520 : (w8 & 1) ? SM_WG + 46080 : SM_WG) + (kq * 144 + (lane & 15)) * 80 + (lane >> 4) * 16;
#pragma unroll
      for (int ks = k0; ks < k1; ks++) {
        uint32_t b0[4], b1[4], b2[2];
        ldsm4t(b0, wa + ks * 1280); ldsm4t(b1, wa + ks * 1280 + 32); ldsm2t(b2, wa + ks * 1280 + 64 - (lane >> 4) * 16);
#pragma unroll
        for (int i = 0; i < 4; i++) { bg[ks][i] = b0[i]; bg[ks][4 + i] = b1[i]; }
        bg[ks][8] = b2[0]; bg[ks][9] = b2[1];
      }
    };
    uint32_t xs[9], *xp;
    auto st_x = [&]() {
#pragma unroll
      for (int i = 0; i < 9; i++)
        if (xp) str1(xp + i * 32, xs[i]);
    };
    {
      uint32_t xa[9], xb[9], wb[9];
      uint4 md[9];
      float av[2][4];
      uint2 pv[12];
      const uint32_t ident = (g >> 1) == t4 ? 0x3f80u << ((g & 1) * 16) : 0u;
      auto ld_late = [&]() {
        bool bad = false;
#pragma unroll
        for (int s = 0; s < 12; s++)
          if (pv[s].x == ~0u || pv[s].y == ~0u) {
            bad = true;
            if (s < 4) { pv[s].x = ldr1(ap + (28 + s) * 512); pv[s].y = ldr1(ap + (28 + s) * 512 + 256); }
            else pv[s] = ldr2(ap + (28 + s) * 512 + w8 * 32 + lane);
          }
        return bad;
      };
#pragma unroll
      for (int s = 0; s < 12; s++) pv[s] = make_uint2(~0u, ~0u);
      uint32_t* const tr = reinterpret_cast<uint32_t*>(smem_raw + SM_X2) + g * 292 + w8 * 4 + t4;
      float sx[4] = {0.f, 0.f, 0.f, 0.f}, qa[4] = {0.f, 0.f, 0.f, 0.f}, qb[4] = {0.f, 0.f, 0.f, 0.f};
      auto stat = [&](int i, uint32_t a, uint32_t c) {
        xa[i] = hfma2(md[i].x, a, xa[i]);
        xb[i] = hfma2(md[i].x, c, xb[i]);
        mma1688(sx, xa[i], xb[i], wb[i]);
        mma1688(qa, xa[i], xb[i], xa[i]);
        mma1688(qb, xa[i], xb[i], xb[i]);
      };
      mbar_wait(sBar + B_TB, 0);
#pragma unroll
      for (int i = 0; i < 9; i++) {
        md[i] = lds128(sb + SM_MD + (i * 32 + w8 * 4 + t4) * 16);
        const uint32_t w = *reinterpret_cast<const uint32_t*>(smem_raw + SM_MOD + (i * 32 + w8 * 4 + t4) * 8 + (g & 1) * 4);
        wb[i] = g == 0 ? 0x3f803f80u : g < 3 ? w : 0u;
      }
      mbar_wait(sBar + B_XR, 0);
#pragma unroll
      for (int i = 0; i < 9; i++) { xa[i] = tr[i * 32]; xb[i] = tr[8 * 292 + i * 32]; }
      mbar_wait(sBar + B_EMPTYO, 0);
      STAMP(74);
      {
        uint32_t need = 0x7fu & (~0u << nc);
        int c1 = 5, c2 = 6;
        ra[5] = rb[5] = ra[6] = rb[6] = 0;
#pragma unroll 1
        for (uint32_t n = 0;; n++) {
          uint32_t a1, d1, a2, d2;
          ld_sum(a1, d1, ld);
          ld_sum(a2, d2, ld + 8);
#pragma unroll
          for (int i = 0; i < 7; i++) {
            if (c1 == i) { ra[i] = a1; rb[i] = d1; }
            if (c2 == i) { ra[i] = a2; rb[i] = d2; }
          }
          auto max8 = [](const uint32_t* w) { return __vimax3_u32(__vimax3_u32(w[0], w[1], w[2]), __vimax3_u32(w[3], w[4], w[5]), max(w[6], w[7])); };
          if (!__any_sync(~0u, max8(ld) == ~0u)) need &= ~(1u << c1);
          if (!__any_sync(~0u, max8(ld + 8) == ~0u)) need &= ~(1u << c2);
          if (__builtin_expect(!need || n > (1u << 15), 1)) break;
          c1 = __ffs(need) - 1;
          c2 = 31 - __clz(need);
          if (FX == 2 && (need & (need - 1))) c2 = __ffs(need & (need - 1)) - 1;
#pragma unroll
          for (int i = 0; i < 8; i++) { ld[i] = ldr1(ap + c1 * 2048 + i * 256); ld[8 + i] = ldr1(ap + c2 * 2048 + i * 256); }
        }
      }
      STAMP(69);
      mbar_wait(sBar + B_G2, 0);
      STAMP(48);
#pragma unroll 1
      for (uint32_t n = 0;; n++) {
        const bool bad = ld_late();
        if (!__any_sync(~0u, bad) || n > (1u << 15)) break;
        if (n == 0) {
#pragma unroll
          for (int i = 0; i < 7; i++) stat(i, ra[i], rb[i]);
          if (BGE) ld_bg(0, BGE);
        }
      }
      STAMP(77);
      if (lane == 0) mbar_arrive(sBar + B_G1);
#pragma unroll
      for (int i = 0; i < 8; i++) av[i >> 2][i & 3] = 0.f;
#pragma unroll
      for (int s = 0; s < 4; s++) {
        if (s & 1) mma16816(av[0], pv[s - 1].x, pv[s - 1].y, pv[s].x, pv[s].y, ident, ident);
        mma16816(av[1], pv[4 + s].x, pv[4 + s].y, pv[8 + s].y, pv[8 + s].x, ident, ident);
      }
#pragma unroll
      for (int i = 0; i < 2; i++) stat(7 + i, pack_bf16(av[i][0], av[i][1]), pack_bf16(av[i][2], av[i][3]));
      STAMP(40);
      float* const ps = reinterpret_cast<float*>(smem_raw + SM_PS);
      if (t4 < 2) {
        *reinterpret_cast<float2*>(ps + w8 * 32 + g * 4 + t4 * 2) = make_float2(sx[0], sx[1]);
        *reinterpret_cast<float2*>(ps + 256 + w8 * 32 + g * 4 + t4 * 2) = make_float2(sx[2], sx[3]);
      }
      if (ident) {
        ps[512 + w8 * 32 + g] = (g & 1) ? qa[1] : qa[0];
        ps[512 + w8 * 32 + g + 8] = (g & 1) ? qb[3] : qb[2];
      }
      bar_sync(5, 256);
      STAMP(44);
      float mean = 0.f, dot = 0.f, m2 = 0.f;
#pragma unroll
      for (int i = 0; i < 4; i++) {
        const float4 q = *reinterpret_cast<const float4*>(ps + (lane & 8) * 32 + (lane & 16) * 8 + i * 32 + (lane & 7) * 4);
        mean += q.x; dot += q.y + q.z; m2 += ps[512 + (lane & 16) * 8 + i * 32 + (lane & 15)];
      }
      const float2 sab = *reinterpret_cast<const float2*>(smem_raw + SM_ZERO + 16);
      mean += __shfl_xor_sync(~0u, mean, 16);
      dot += __shfl_xor_sync(~0u, dot, 16);
      m2 += __shfl_xor_sync(~0u, m2, 16);
      mean *= 1.f / DM;
      const float rs = rcp(bfr(sqrt_a(bfr(bfr(fmaxf(fmaf(m2, 1.f / DM, -mean * mean), 0.f)) + 1e-5f))));
      const uint32_t nm = pack_bf16(-mean, -mean);
      uint32_t u = pack_bf16(0.f, fmaf(rs, fmaf(bf_lo(nm), sab.x, dot), sab.y));
      u = ((u & 0x7fff0000u) > 0x7f800000u) ? 0u : (u ^ ((u >> 31) ? 0xffff0000u : 0x80000000u));
      u |= 0xffffu - (row0 + (lane & 15));
      const uint32_t m1 = __reduce_max_sync(~0u, u), m2k = __reduce_max_sync(~0u, u == m1 ? 0u : u);
      if (w8 == 7) asm volatile("st.relaxed.gpu.global.v2.u32 [%0], {%1,%2};" ::"l"(reinterpret_cast<uint2*>(g_ones + F_KEY) + lane * 128 + b), "r"(~m1), "r"(~m2k) : "memory");
      STAMP(41);
      const int r1 = ~m1 & 15, r2 = ~m2k & 15;
      const uint32_t r2t = pack_bf16(rs, rs - bfr(rs));
      const uint32_t rA = __shfl_sync(~0u, r2t, g), rB = __shfl_sync(~0u, r2t, g + 8);
      const uint32_t nmA = __shfl_sync(~0u, nm, g), nmB = __shfl_sync(~0u, nm, g + 8);
      const uint32_t hA = __byte_perm(rA, 0, 0x1010), lA = __byte_perm(rA, 0, 0x3232), hB = __byte_perm(rB, 0, 0x1010), lB = __byte_perm(rB, 0, 0x3232);
      uint32_t* const hx = reinterpret_cast<uint32_t*>(g_ones + F_HX + b * 288) + w8 * 4 + t4;
      const bool topA = g == r1 || g == r2, topB = g + 8 == r1 || g + 8 == r2;
      uint32_t* const pA = hx + (g == r2 ? 576 : 0);
      uint32_t* const pB = hx + (g + 8 == r2 ? 576 : 0);
      uint32_t* const pS = topA ? pA : pB;
#pragma unroll
      for (int i = 0; i < 9; i++) {
        const uint32_t da = hadd2(xa[i], nmA), db = hadd2(xb[i], nmB);
        const uint32_t ha = hfma2(hfma2(da, hA, hmul2(da, lA)), md[i].z, md[i].y), hb = hfma2(hfma2(db, hB, hmul2(db, lB)), md[i].z, md[i].y);
        if (topA || topB) str1(pS + i * 32, topA ? ha : hb);
        tr[i * 32] = hfma2(md[i].w, ha, xa[i]);
        tr[8 * 292 + i * 32] = hfma2(md[i].w, hb, xb[i]);
        md[i].x = hb;
        xs[i] = topA ? xa[i] : xb[i];
      }
      if (__builtin_expect((r1 ^ r2) == 8, 0) && topB) {
#pragma unroll
        for (int i = 0; i < 9; i++) { str1(pB + i * 32, md[i].x); str1(pB + 288 + i * 32, xb[i]); }
      }
      __syncwarp();
      xp = topA || topB ? pS + 288 : nullptr;
      if (HX == 2) st_x();
      if (FW == 4) { if (tid == 128) *reinterpret_cast<uint2*>(tsu + 34) = make_uint2(m1, m2k); }
      else if (tid == 128) tsu[34] = (1u << r1) | (1u << r2);
      bar_arrive(11, 288);
    }
    STAMP(75);
    ld_bg(BGE, 9);
    mbar_wait(sBar + B_FD, 0);
    STAMP(42);
    {
      const uint32_t a = sb + SM_WD + lane * 128 + (((w8 ^ lane) & 7) << 4);
#pragma unroll
      for (int i = 0; i < 9; i++) {
        uint32_t b0[4];
        ldsm4t(b0, a + i * 5120);
        asm volatile("ldmatrix.sync.aligned.m8n8.x1.trans.shared.b16 {%0}, [%1];" : "=r"(bd[i][4]) : "r"(a + i * 5120 + 4096) : "memory");
#pragma unroll
        for (int j = 0; j < 4; j++) bd[i][j] = b0[j];
      }
    }
    if (HX == 3) st_x();
    STAMP(43);
    mbar_wait(sBar + B_G3, 0);
    STAMP(76);
    {
      float c[2][3][4];
#pragma unroll
      for (int i = 0; i < 6; i++) c[i & 1][i >> 1][0] = c[i & 1][i >> 1][1] = c[i & 1][i >> 1][2] = c[i & 1][i >> 1][3] = 0.f;
      uint32_t hb[5][4];
#pragma unroll
      for (int i = 0; i < 5; i++) ldsm4(hb[i], sb + SM_T + T_H + (lane & 1) * 1152 + kq * 288 + (lane >> 3) * 16 + i * 64);
#pragma unroll
      for (int ks = 0; ks < 9; ks++) {
        const uint32_t h0 = hb[ks >> 1][(ks & 1) * 2], h1 = hb[ks >> 1][(ks & 1) * 2 + 1];
        mma16816(c[ks & 1][0], bg[ks][0], bg[ks][2], bg[ks][1], bg[ks][3], h0, h1);
        mma16816(c[ks & 1][1], bg[ks][4], bg[ks][6], bg[ks][5], bg[ks][7], h0, h1);
        mma16816(c[ks & 1][2], bg[ks][8], 0u, bg[ks][9], 0u, h0, h1);
      }
      float* const part = tsf + 64;
      const bool u1 = lane & 1, u2 = lane & 2;
#pragma unroll
      for (int i = 0; i < 3; i++) {
        const float v = (u2 ? (u1 ? c[0][i][3] : c[0][i][2]) : (u1 ? c[0][i][1] : c[0][i][0])) + (u2 ? (u1 ? c[1][i][3] : c[1][i][2]) : (u1 ? c[1][i][1] : c[1][i][0]));
        if (i < 2 || !u2) part[w8 * 80 + (t4 & 1) * 40 + i * 16 + (t4 >> 1) * 8 + g] = v;
      }
      STAMP(45);
      bar_sync(5, 256);
      STAMP(46);
      auto act2 = [&](int f) {
        const float2* pp = reinterpret_cast<const float2*>(part + (g & 1) * 40 + f + (b & 1) * 4);
        const float2 g0 = pp[0], g1 = pp[80], g2 = pp[160], g3 = pp[240], u0 = pp[40], u1 = pp[120], u2 = pp[200], u3 = pp[280];
        return pack_bf16(silu_bf(bfr((g0.x + g1.x) + (g2.x + g3.x))) * bfr((u0.x + u1.x) + (u2.x + u3.x)),
                         silu_bf(bfr((g0.y + g1.y) + (g2.y + g3.y))) * bfr((u0.y + u1.y) + (u2.y + u3.y)));
      };
      const uint32_t v0 = act2((g >> 1) * 8 + t4 * 2), v1 = act2(32 + (t4 & 1) * 2);
      uint32_t a6[5];
#pragma unroll
      for (int i = 0; i < 4; i++) a6[i] = __shfl_sync(~0u, v0, i * 8 + (lane & 7));
      a6[4] = t4 < 2 ? v1 : 0u;
      STAMP(47);
      float* const yp = reinterpret_cast<float*>(g_ones + F_YP) + b * 64 + g * 2;
      float y[5][4];
#pragma unroll
      for (int i = 0; i < 5; i++) {
        y[i][0] = y[i][1] = y[i][2] = y[i][3] = 0.f;
        mma16816(y[i], bd[2 * i][0], i < 4 ? bd[(2 * i + 1) % 9][0] : 0u, bd[2 * i][1], i < 4 ? bd[(2 * i + 1) % 9][1] : 0u, a6[0], a6[1]);
      }
#pragma unroll
      for (int i = 0; i < 5; i++) mma16816(y[i], bd[2 * i][2], i < 4 ? bd[(2 * i + 1) % 9][2] : 0u, bd[2 * i][3], i < 4 ? bd[(2 * i + 1) % 9][3] : 0u, a6[2], a6[3]);
#pragma unroll
      for (int i = 0; i < 5; i++) mma1688(y[i], bd[2 * i][4], i < 4 ? bd[(2 * i + 1) % 9][4] : 0u, a6[4]);
#pragma unroll
      for (int m = 0; m < 2; m++) {
        const float y0 = u2 ? (u1 ? y[2 * m + 1][2] : y[2 * m + 1][0]) : (u1 ? y[2 * m][2] : y[2 * m][0]);
        const float y1 = u2 ? (u1 ? y[2 * m + 1][3] : y[2 * m + 1][1]) : (u1 ? y[2 * m][3] : y[2 * m][1]);
        asm volatile("st.relaxed.gpu.global.v2.f32 [%0], {%1,%2};" ::"l"(yp + (m * 8 + w8) * 8192 + t4 * 16), "f"(y0), "f"(y1) : "memory");
      }
      if (t4 == 0) asm volatile("st.relaxed.gpu.global.v2.f32 [%0], {%1,%2};" ::"l"(yp + (16 + (w8 >> 2)) * 8192 + (w8 & 3) * 16), "f"(y[4][0]), "f"(y[4][1]) : "memory");
    }
    if (HX == 1) st_x();
    STAMP(78);
    if (b < 72) {
      const uint4* pp = g_ones + F_YP + (b >> 2) * 2048 + (w8 * 16 + g) * 16 + (b & 3) * 4 + t4;
      const uint4 none = make_uint4(~0u, ~0u, ~0u, ~0u);
      uint4 r0 = none, r1 = none, q[FK][2];
      PSTAMP(352, 62);
#pragma unroll
      for (int j = 0; j < FK; j++) {
        if (j) delay(FD);
        q[j][0] = ldr4(pp); q[j][1] = ldr4(pp + 128);
      }
      float gb, hv, sg;
      uint16_t xv = 0;
      bf16* op;
      if (w8 == 7) {
        const uint32_t k1 = tsu[32], k2 = tsu[33];
        const int row1 = ~k1 & (SQ - 1), row2 = ~k2 & (SQ - 1);
        const int tok = lane & 1, col = (b < 64 ? ((b >> 5) * 4 + (b & 3)) * 64 + (b & 28) * 2 : b * 8) + ((lane >> 1) & 7);
        const uint32_t key = tok ? k2 : k1;
        const int row = tok ? row2 : row1;
        const int c1 = ((row1 >> 5) & 3) * 32 + (row1 >> 7) * 2 + ((row1 >> 4) & 1), cr = ((row >> 5) & 3) * 32 + (row >> 7) * 2 + ((row >> 4) & 1);
        const uint16_t* xp = reinterpret_cast<const uint16_t*>(g_ones + F_HX + cr * 288 + (tok && c1 == cr ? 144 : 0) + 72) + col;
        gb = __uint_as_float((uint32_t)reinterpret_cast<const uint16_t*>(smem_raw + SM_MD)[(col >> 1) * 8 + 6 + (col & 1)] << 16);
        hv = __uint_as_float((uint32_t)reinterpret_cast<const uint16_t*>(smem_raw + SM_T + T_H)[tok * DM + col] << 16);
        sg = bfr(rcp(1.f + __expf(-__uint_as_float((key & 0xffff0000u) ^ ((key >> 31) ? 0x80000000u : 0xffff0000u)))));
        op = prm.out + (size_t)row * DM + col;
#pragma unroll 1
        for (uint32_t n = 0; n < (1u << 15); n++) {
          asm volatile("ld.relaxed.gpu.global.u16 %0, [%1];" : "=h"(xv) : "l"(xp) : "memory");
          if (xv != 0xffff) break;
        }
        __syncwarp();
      }
#pragma unroll 1
      for (uint32_t n = 0;; n++) {
        bool done = false;
#pragma unroll
        for (int j = 0; j < FK; j++) {
          if (unset(r0)) r0 = q[j][0];
          if (unset(r1)) r1 = q[j][1];
          const bool m0 = unset(r0), m1 = unset(r1);
          if (!__any_sync(~0u, m0 || m1)) { done = true; break; }
          if (m0) q[j][0] = ldr4(pp);
          if (m1) q[j][1] = ldr4(pp + 128);
        }
        if (done) break;
        if (n > (1u << 14)) { SETERR(32); break; }
      }
      PSTAMP(352, 63);
      float s[4] = {__uint_as_float(r0.x) + __uint_as_float(r1.x), __uint_as_float(r0.y) + __uint_as_float(r1.y),
                    __uint_as_float(r0.z) + __uint_as_float(r1.z), __uint_as_float(r0.w) + __uint_as_float(r1.w)};
      const bool u4 = lane & 4, u8 = lane & 8;
#pragma unroll
      for (int i = 0; i < 2; i++) { const float snd = u4 ? s[i] : s[i + 2], kp = u4 ? s[i + 2] : s[i]; s[i] = kp + __shfl_xor_sync(~0u, snd, 4); }
      { const float snd = u8 ? s[0] : s[1], kp = u8 ? s[1] : s[0]; s[0] = kp + __shfl_xor_sync(~0u, snd, 8); }
      s[0] += __shfl_xor_sync(~0u, s[0], 16);
      float* const fs = reinterpret_cast<float*>(smem_raw + SM_PS);
      if (lane < 16) fs[(t4 * 4 + (g & 1) * 2 + (g >> 1)) * 8 + w8] = s[0];
      if (w8 < 7) bar_arrive(5, 256);
      else {
        bar_sync(5, 256);
        const float4 a = *reinterpret_cast<const float4*>(fs + (lane & 15) * 8), c = *reinterpret_cast<const float4*>(fs + (lane & 15) * 8 + 4);
        const float hh = bfr(hv + bfr(bfr(((a.x + a.y) + (a.z + a.w)) + ((c.x + c.y) + (c.z + c.w))) * sg));
        if (lane < 16) *op = __float2bfloat16(__uint_as_float((uint32_t)xv << 16) + bfr(gb * hh));
      }
      PSTAMP(352, 49);
    }
    if (w8 == 5 && lane < 9) g_mod1[b * 9 + lane] = make_uint4(0u, 0u, 0u, 0u);
    if (w8 == 5 && lane == 9) *reinterpret_cast<uint4*>(&g_cnt[(C_Q + b) * 32]) = make_uint4(0u, 0u, 0u, 0u);
    if (w8 == 5 && lane == 10 && b == 0) g_cnt[C_SIDE * 32] = 0;
    STAMP(79); GSTAMP(91);
    }
  }
}

typedef CUresult (*PFN_enc)(CUtensorMap*, CUtensorMapDataType, cuuint32_t, void*, const cuuint64_t*, const cuuint64_t*,
                            const cuuint32_t*, const cuuint32_t*, CUtensorMapInterleave, CUtensorMapSwizzle,
                            CUtensorMapL2promotion, CUtensorMapFloatOOBfill);
static PFN_enc g_enc = nullptr;
static uint4* g_mod1_p = nullptr;
static CUtensorMap mk_map(const void* p, uint64_t cols, uint64_t rows, uint32_t bc, uint32_t br, bool swz = true) {
  CUtensorMap m;
  cuuint64_t dims[2] = {cols, rows};
  cuuint64_t strides[1] = {cols * 2};
  cuuint32_t box[2] = {bc, br}, es[2] = {1, 1};
  g_enc(&m, CU_TENSOR_MAP_DATA_TYPE_BFLOAT16, 2, const_cast<void*>(p), dims, strides, box, es, CU_TENSOR_MAP_INTERLEAVE_NONE,
        swz ? CU_TENSOR_MAP_SWIZZLE_128B : CU_TENSOR_MAP_SWIZZLE_NONE, swz ? CU_TENSOR_MAP_L2_PROMOTION_L2_128B : CU_TENSOR_MAP_L2_PROMOTION_NONE,
        CU_TENSOR_MAP_FLOAT_OOB_FILL_NONE);
  return m;
}

static CUtensorMap mk_map_n(const void* p, int n, const cuuint64_t* dims, const cuuint64_t* strides, const cuuint32_t* box) {
  CUtensorMap m;
  cuuint32_t es[4] = {1, 1, 1, 1};
  g_enc(&m, CU_TENSOR_MAP_DATA_TYPE_BFLOAT16, n, const_cast<void*>(p), dims, strides, box, es, CU_TENSOR_MAP_INTERLEAVE_NONE,
        CU_TENSOR_MAP_SWIZZLE_128B, CU_TENSOR_MAP_L2_PROMOTION_L2_128B, CU_TENSOR_MAP_FLOAT_OOB_FILL_NONE);
  return m;
}

extern "C" void kernel_launch(void* const* d_in, const int* in_sizes, int n_in, void* d_out, int out_size) {
  if (!g_enc) {
    cudaDriverEntryPointQueryResult st;
    cudaGetDriverEntryPoint("cuTensorMapEncodeTiled", (void**)&g_enc, cudaEnableDefault, &st);
    cudaFuncSetAttribute(k_mega, cudaFuncAttributeMaxDynamicSharedMemorySize, SM_TOTAL);
    cudaGetSymbolAddress((void**)&g_mod1_p, g_mod1);
  }
  const cuuint64_t xd[3] = {64, SQ, 9}, xs[2] = {DM * 2, 128};
  const cuuint32_t xb[3] = {64, 32, 9};
  CUtensorMap mX = mk_map_n(d_in[0], 3, xd, xs, xb);
  CUtensorMap mWq = mk_map(d_in[3], HQ * DH, DM, 64, 144);
  CUtensorMap mK = mk_map(d_in[1], DH, HKV * SK, 64, 128);
  CUtensorMap mV = mk_map(d_in[2], DH, HKV * SK, 64, 128);
  const cuuint64_t od[4] = {DM, DH, 2, HKV}, os[3] = {DM * 2, DH * DM * 2, 2 * DH * DM * 2};
  const cuuint32_t ob[4] = {64, DH, 1, 2};
  CUtensorMap mWo = mk_map_n(d_in[4], 4, od, os, ob);
  CUtensorMap mWg = mk_map(d_in[7], FF, DM, 40, 144, false);
  CUtensorMap mWu = mk_map(d_in[8], FF, DM, 40, 144, false);
  const cuuint64_t dd[3] = {64, FF, 9}, ds[2] = {DM * 2, 128};
  const cuuint32_t db[3] = {64, 40, 9};
  CUtensorMap mWd = mk_map_n(d_in[9], 3, dd, ds, db);
  CUtensorMap mM = mk_map(d_in[11], 6 * DM, DM, 16, 192, false);
  Params prm;
  prm.x = (const bf16*)d_in[0]; prm.k = (const bf16*)d_in[1]; prm.v = (const bf16*)d_in[2]; prm.wo = (const bf16*)d_in[4]; prm.wq = (const bf16*)d_in[3];
  prm.w_r = (const bf16*)d_in[6]; prm.c = (const bf16*)d_in[10]; prm.w_mod = (const bf16*)d_in[11];
  prm.wg = (const bf16*)d_in[7]; prm.wu = (const bf16*)d_in[8]; prm.wd = (const bf16*)d_in[9];
  prm.out = (bf16*)d_out;
  prm.mod1 = g_mod1_p;
  cudaLaunchConfig_t cfg = {};
  cfg.gridDim = dim3(132); cfg.blockDim = dim3(384); cfg.dynamicSmemBytes = SM_TOTAL; cfg.stream = cudaStreamPerThread;
  cudaLaunchAttribute at[1];
  at[0].id = cudaLaunchAttributeClusterDimension;
  at[0].val.clusterDim.x = 2; at[0].val.clusterDim.y = 1; at[0].val.clusterDim.z = 1;
  cfg.attrs = at; cfg.numAttrs = 1;
  cudaLaunchKernelEx(&cfg, k_mega, prm, mX, mWq, mK, mV, mWo, mWg, mWu, mWd, mM);
}
```

```cpp
#include <cuda_runtime.h>
#include <cuda_bf16.h>
#include <cuda.h>
#include <stdint.h>

typedef __nv_bfloat16 bf16;

constexpr int SQ = 2048, DM = 576, HQ = 32, HKV = 16, SK = 2048, DH = 128, FF = 4608;

#define KO 3
#define HT 0
#define XL 3
#define EB 13
#define EM 0
#define FS 2
#define PIN 5
#define XPH 0
#define CF 1
#define OP 11
#define TCH (KO ? 16 : 20)
#define TF0 26
#define TW0 16
#define TWN 4
#define FAKEB 0
#define FILLS 30
#define WOMC 0
#define FFNS 0x6420
#define ORD 1
#define FIXS 0
#define HINTH 1
#define HINTW 1
#define PFO 1
#define TN 3
#define FGAP 0
#define FGN 8
#define BGE 5
#define FPRED 1
#define XD 500
#define CV 1
#define WARM 0
#define XT 0
#define CT 0
#define TMP 1
#define XO 0
#define RS0 0
#define CL 0
#define PM 0
#define PN 4
#define MM 31
#define XW 1
#define GP 0
#define FX 1
#define MG 1
#define MGL 0
#define HX 1
#define N2 1
#define HS 0
#define EH 8
#define XD1 1000
#define PW 0
#define QW 0
#define B7 1
#define LN_LIMIT 0.0625f
#define TG 9
#define TL 1
#define KICK 0
#define MT 1
#define MWARM 0
#define PE 0
#define PD 0
#define FK 1
#define FD 300
#define XPF 0
#define WQPF0 0
#define WQPF1 0xff
#define FFNQ 2
#define WQPF2 0
#define QTH 4
#define MPF 1
#define FILLP 31
#define FILL0 25
#define FFN0 20
#define FILLN 8
#define FFNB 6
#define PF0 20
#define FFNR 1
#define FFND 1
#define KV0 16
#define KVS 2
#define QPF 6
#define EF 31
#define WOP 99
#define TLBW 0
#define NOFFN 0
#define FLATE 0
#define RELF 1
#define REL_FENCE() asm volatile("fence.acq_rel.gpu;" ::: "memory")
#define FILLMIN 0
#define FWS 100
#define FW 0
#define GX 0
#define XQ 0
#define XS 0
#define OSP 0
#define XG 4
#define DS 0
#define AO 3072
#define KVP 99
#define NQP 1
#define PFM 7
#define QL 1
#define IS 0
#define ER 0
#define DMY 0
#define EP 0
#define EN 1
#define EPS 0
#define AL 1
#define FILLMAX 45
#define XN 4
#define MODB 0
#define QPV 0
#define LATEG 0
#define RETL 1
#define HINTA 15
#define SIDEF 3
#define FFNE 15
#define TE_POS 8
#define LAZY_LIMIT 1.8446744e19f
#define LAZY_LOW 5.4210109e-20f
__device__ uint4 g_mod1[8 * 144];
__device__ uint4 g_mod2[288];
#define g_q (g_ones + F_PART - AO)
constexpr int PS = AL ? 8192 : 5120;
constexpr int F_HX = 0;
constexpr int F_YP = 128 * 288;
constexpr int F_KEY = 128 * 576;
constexpr int F_PART = 128 * 640 + AO;
constexpr int F_N = 640 + PS;
__device__ uint4 g_ones[128 * F_N];
__device__ __align__(128) unsigned int g_cnt[136 * 32];
__device__ unsigned int g_err;
#define HAS_ERR
enum { C_SIDE = 1, C_M2 = 2, C_Q = 8 };

#define STAMP(i)
#define KSTAMP(i)
#define GSTAMP(i)
#define SETERR(v)
#define ES(t, w, i)
#define ESC(i)
#define PSTAMP(t, i)

__device__ __forceinline__ int get_lane() {
  int l;
  asm volatile("mov.u32 %0, %%laneid;" : "=r"(l));
  __builtin_assume(l >= 0 && l < 32);
  return l;
}
__device__ __forceinline__ uint32_t clk() { uint32_t c; asm volatile("mov.u32 %0, %%clock;" : "=r"(c) :: "memory"); return c; }
__device__ __forceinline__ void delay(uint32_t n) { const uint32_t t0 = clk(); while (clk() - t0 < n) {} }
__device__ __forceinline__ uint32_t smem_u32(const void* p) { return (uint32_t)__cvta_generic_to_shared(p); }
__device__ __forceinline__ void mbar_init(uint32_t a, uint32_t cnt) { asm volatile("mbarrier.init.shared::cta.b64 [%0], %1;" ::"r"(a), "r"(cnt)); }
__device__ __forceinline__ void mbar_expect_tx(uint32_t a, uint32_t bytes) { asm volatile("mbarrier.arrive.expect_tx.shared::cta.b64 _, [%0], %1;" ::"r"(a), "r"(bytes) : "memory"); }
__device__ __forceinline__ void mbar_arrive(uint32_t a) { asm volatile("mbarrier.arrive.shared::cta.b64 _, [%0];" ::"r"(a) : "memory"); }
__device__ __forceinline__ void mbar_arrive_cl(uint32_t a_cluster) { asm volatile("mbarrier.arrive.shared::cluster.b64 _, [%0];" ::"r"(a_cluster) : "memory"); }
__device__ __forceinline__ void mbar_wait(uint32_t a, uint32_t parity) {
  asm volatile(
      "{\n.reg .pred p;\n.reg .u32 n;\nmov.u32 n, 0;\n"
      "WAIT_LOOP:\n"
      "mbarrier.try_wait.parity.shared::cta.b64 p, [%0], %1;\n"
      "@p bra WAIT_DONE;\n"
      "add.u32 n, n, 1;\n"
      "setp.lt.u32 p, n, 65536;\n"
      "@p bra WAIT_LOOP;\n"
      "WAIT_DONE:\n}\n" ::"r"(a), "r"(parity), "l"(&g_err) : "memory");
}
__device__ __forceinline__ void mbar_pace(uint32_t a, uint32_t parity) {
  const uint32_t t0 = clk();
  uint32_t ok;
  do {
    asm volatile("{\n.reg .pred p;\nmbarrier.try_wait.parity.shared::cta.b64 p, [%1], %2, 1000;\nselp.u32 %0, 1, 0, p;\n}\n" : "=r"(ok) : "r"(a), "r"(parity) : "memory");
  } while (!ok && clk() - t0 < 8192);
}
__device__ __forceinline__ void cnt_wait(int idx, unsigned target) {
  for (uint32_t n = 0;; n++) {
    unsigned v;
    asm volatile("ld.relaxed.gpu.global.u32 %0, [%1];" : "=r"(v) : "l"(&g_cnt[idx * 32]) : "memory");
    if (v >= target) break;
    if (n > (1u << 15)) { SETERR(2); break; }
  }
}
__device__ __forceinline__ void cnt_wait1(int word, unsigned target) {
  for (uint32_t n = 0;; n++) {
    unsigned v;
    asm volatile("ld.relaxed.gpu.global.u32 %0, [%1];" : "=r"(v) : "l"(&g_cnt[word]) : "memory");
    if (v >= target) break;
    if (n > (1u << 15)) { SETERR(2); break; }
  }
}
__device__ __forceinline__ void cnt_acq(int word, unsigned target, unsigned ns) {
#pragma unroll 1
  for (uint32_t n = 0;; n++) {
    unsigned v;
    asm volatile("ld.acquire.gpu.global.u32 %0, [%1];" : "=r"(v) : "l"(&g_cnt[word]) : "memory");
    if (v >= target) break;
    if (n > (1u << 15)) { SETERR(2); break; }
    if (ns) __nanosleep(ns);
  }
  asm volatile("fence.proxy.async.global;" ::: "memory");
}
__device__ __forceinline__ void cnt_arrive(int idx) {
  asm volatile("red.relaxed.gpu.global.add.u32 [%0], 1;" ::"l"(&g_cnt[idx * 32]) : "memory");
}
__device__ __forceinline__ uint4 poll4(const uint4* p) {
  uint4 v;
  uint32_t n = 0;
  while (true) {
    asm volatile("ld.relaxed.gpu.global.v4.u32 {%0,%1,%2,%3}, [%4];" : "=r"(v.x), "=r"(v.y), "=r"(v.z), "=r"(v.w) : "l"(p) : "memory");
    if (v.x && v.y && v.z && v.w) break;
    if (++n > (1u << 15)) { SETERR(4); break; }
  }
  return v;
}
__device__ __forceinline__ void poll8(const uint4* p, const uint4* q, uint4& v, uint4& w) {
  uint32_t n = 0;
#pragma unroll 1
  while (true) {
    asm volatile("ld.relaxed.gpu.global.v4.u32 {%0,%1,%2,%3}, [%4];" : "=r"(v.x), "=r"(v.y), "=r"(v.z), "=r"(v.w) : "l"(p) : "memory");
    asm volatile("ld.relaxed.gpu.global.v4.u32 {%0,%1,%2,%3}, [%4];" : "=r"(w.x), "=r"(w.y), "=r"(w.z), "=r"(w.w) : "l"(q) : "memory");
    if (v.x && v.y && v.z && v.w && w.x && w.y && w.z && w.w) break;
    if (++n > (1u << 15)) { SETERR(4); break; }
  }
}
__device__ __forceinline__ uint4 ldr4(const void* p) {
  uint4 v;
  asm volatile("ld.relaxed.gpu.global.v4.u32 {%0,%1,%2,%3}, [%4];" : "=r"(v.x), "=r"(v.y), "=r"(v.z), "=r"(v.w) : "l"(p) : "memory");
  return v;
}
__device__ __forceinline__ uint2 ldr2(const void* p) {
  uint2 v;
  asm volatile("ld.relaxed.gpu.global.v2.u32 {%0,%1}, [%2];" : "=r"(v.x), "=r"(v.y) : "l"(p) : "memory");
  return v;
}
__device__ __forceinline__ uint32_t ldr1(const void* p) {
  uint32_t v;
  asm volatile("ld.relaxed.gpu.global.u32 %0, [%1];" : "=r"(v) : "l"(p) : "memory");
  return v;
}
__device__ __forceinline__ void str1(void* p, uint32_t v) { asm volatile("st.relaxed.gpu.global.u32 [%0], %1;" ::"l"(p), "r"(v) : "memory"); }
__device__ __forceinline__ bool unset(uint4 v) { return v.x == ~0u || v.y == ~0u || v.z == ~0u || v.w == ~0u; }
__device__ __forceinline__ bool nan2(uint32_t v) {
  uint32_t r;
  asm("{\n.reg .pred p, q;\nsetp.nan.bf16x2 p|q, %1, %1;\nor.pred p, p, q;\nselp.u32 %0, 1, 0, p;\n}\n" : "=r"(r) : "r"(v));
  return r != 0;
}
__device__ __forceinline__ uint32_t hmul2(uint32_t a, uint32_t b) { uint32_t r; asm("mul.rn.bf16x2 %0, %1, %2;" : "=r"(r) : "r"(a), "r"(b)); return r; }
__device__ __forceinline__ uint32_t hadd2(uint32_t a, uint32_t b) { uint32_t r; asm("add.rn.bf16x2 %0, %1, %2;" : "=r"(r) : "r"(a), "r"(b)); return r; }
__device__ __forceinline__ uint32_t hfma2(uint32_t a, uint32_t b, uint32_t c) { uint32_t r; asm("fma.rn.bf16x2 %0, %1, %2, %3;" : "=r"(r) : "r"(a), "r"(b), "r"(c)); return r; }
__device__ __forceinline__ void mma16816(float (&c)[4], uint32_t a0, uint32_t a1, uint32_t a2, uint32_t a3, uint32_t b0, uint32_t b1) {
  asm volatile("mma.sync.aligned.m16n8k16.row.col.f32.bf16.bf16.f32 {%0,%1,%2,%3}, {%4,%5,%6,%7}, {%8,%9}, {%0,%1,%2,%3};"
               : "+f"(c[0]), "+f"(c[1]), "+f"(c[2]), "+f"(c[3]) : "r"(a0), "r"(a1), "r"(a2), "r"(a3), "r"(b0), "r"(b1));
}
__device__ __forceinline__ void mma1688(float (&c)[4], uint32_t a0, uint32_t a1, uint32_t b0) {
  asm volatile("mma.sync.aligned.m16n8k8.row.col.f32.bf16.bf16.f32 {%0,%1,%2,%3}, {%4,%5}, {%6}, {%0,%1,%2,%3};"
               : "+f"(c[0]), "+f"(c[1]), "+f"(c[2]), "+f"(c[3]) : "r"(a0), "r"(a1), "r"(b0));
}
__device__ __forceinline__ void ldsm4t(uint32_t (&r)[4], uint32_t a) {
  asm volatile("ldmatrix.sync.aligned.m8n8.x4.trans.shared.b16 {%0,%1,%2,%3}, [%4];" : "=r"(r[0]), "=r"(r[1]), "=r"(r[2]), "=r"(r[3]) : "r"(a) : "memory");
}
__device__ __forceinline__ void ldsm4(uint32_t (&r)[4], uint32_t a) {
  asm volatile("ldmatrix.sync.aligned.m8n8.x4.shared.b16 {%0,%1,%2,%3}, [%4];" : "=r"(r[0]), "=r"(r[1]), "=r"(r[2]), "=r"(r[3]) : "r"(a) : "memory");
}
__device__ __forceinline__ void ldsm2t(uint32_t (&r)[2], uint32_t a) {
  asm volatile("ldmatrix.sync.aligned.m8n8.x2.trans.shared.b16 {%0,%1}, [%2];" : "=r"(r[0]), "=r"(r[1]) : "r"(a) : "memory");
}
__device__ __forceinline__ float warp_sum(float v) {
#pragma unroll
  for (int o = 16; o; o >>= 1) v += __shfl_xor_sync(~0u, v, o);
  return v;
}
__device__ __forceinline__ void tma_load_2d(uint32_t dst, const CUtensorMap* map, uint32_t mbar, int c0, int c1) {
  asm volatile("cp.async.bulk.tensor.2d.shared::cluster.global.mbarrier::complete_tx::bytes [%0], [%1, {%3, %4}], [%2];"
               ::"r"(dst), "l"(map), "r"(mbar), "r"(c0), "r"(c1) : "memory");
}
__device__ __forceinline__ void tma_load_2d_mc(uint32_t dst, const CUtensorMap* map, uint32_t mbar, int c0, int c1) {
  asm volatile("cp.async.bulk.tensor.2d.shared::cluster.global.mbarrier::complete_tx::bytes.multicast::cluster [%0], [%1, {%3, %4}], [%2], %5;"
               ::"r"(dst), "l"(map), "r"(mbar), "r"(c0), "r"(c1), "h"((uint16_t)3) : "memory");
}
__device__ __forceinline__ uint64_t pol_first() {
  uint64_t p;
  asm("createpolicy.fractional.L2::evict_first.b64 %0, 1.0;" : "=l"(p));
  return p;
}
__device__ __forceinline__ void tma_load_2d_h(uint32_t dst, const CUtensorMap* map, uint32_t mbar, int c0, int c1, uint64_t pol) {
  asm volatile("cp.async.bulk.tensor.2d.shared::cluster.global.mbarrier::complete_tx::bytes.L2::cache_hint [%0], [%1, {%3, %4}], [%2], %5;"
               ::"r"(dst), "l"(map), "r"(mbar), "r"(c0), "r"(c1), "l"(pol) : "memory");
}
__device__ __forceinline__ void tma_load_2d_mc_h(uint32_t dst, const CUtensorMap* map, uint32_t mbar, int c0, int c1, uint64_t pol) {
  asm volatile("cp.async.bulk.tensor.2d.shared::cluster.global.mbarrier::complete_tx::bytes.multicast::cluster.L2::cache_hint [%0], [%1, {%3, %4}], [%2], %5, %6;"
               ::"r"(dst), "l"(map), "r"(mbar), "r"(c0), "r"(c1), "h"((uint16_t)3), "l"(pol) : "memory");
}
__device__ __forceinline__ void tma_load_3d(uint32_t dst, const CUtensorMap* map, uint32_t mbar, int c0, int c1, int c2) {
  asm volatile("cp.async.bulk.tensor.3d.shared::cluster.global.mbarrier::complete_tx::bytes [%0], [%1, {%3, %4, %5}], [%2];"
               ::"r"(dst), "l"(map), "r"(mbar), "r"(c0), "r"(c1), "r"(c2) : "memory");
}
__device__ __forceinline__ void tma_load_3d_mc(uint32_t dst, const CUtensorMap* map, uint32_t mbar, int c0, int c1, int c2) {
  asm volatile("cp.async.bulk.tensor.3d.shared::cluster.global.mbarrier::complete_tx::bytes.multicast::cluster [%0], [%1, {%3, %4, %5}], [%2], %6;"
               ::"r"(dst), "l"(map), "r"(mbar), "r"(c0), "r"(c1), "r"(c2), "h"((uint16_t)3) : "memory");
}
__device__ __forceinline__ void tma_load_4d_h(uint32_t dst, const CUtensorMap* map, uint32_t mbar, int c0, int c1, int c2, int c3, uint64_t pol) {
  asm volatile("cp.async.bulk.tensor.4d.shared::cluster.global.mbarrier::complete_tx::bytes.L2::cache_hint [%0], [%1, {%3, %4, %5, %6}], [%2], %7;"
               ::"r"(dst), "l"(map), "r"(mbar), "r"(c0), "r"(c1), "r"(c2), "r"(c3), "l"(pol) : "memory");
}
__device__ __forceinline__ void tma_prefetch_2d(const CUtensorMap* map, int c0, int c1) {
  asm volatile("cp.async.bulk.prefetch.tensor.2d.L2.global.tile [%0, {%1, %2}];" ::"l"(map), "r"(c0), "r"(c1) : "memory");
}
__device__ __forceinline__ void bulk_prefetch(const void* p, uint32_t bytes) {
  asm volatile("cp.async.bulk.prefetch.L2.global [%0], %1;" ::"l"(p), "r"(bytes) : "memory");
}
__device__ __forceinline__ void bulk_prefetch_f(const void* p, uint32_t bytes) {
  asm volatile("cp.async.bulk.prefetch.L2.global.L2::cache_hint [%0], %1, %2;" ::"l"(p), "r"(bytes), "l"(pol_first()) : "memory");
}
__device__ __forceinline__ void bulk_load(uint32_t dst, const void* src, uint32_t bytes, uint32_t mbar) {
  asm volatile("cp.async.bulk.shared::cluster.global.mbarrier::complete_tx::bytes [%0], [%1], %2, [%3];"
               ::"r"(dst), "l"(src), "r"(bytes), "r"(mbar) : "memory");
}
__device__ __forceinline__ void wgmma_fence() { asm volatile("wgmma.fence.sync.aligned;" ::: "memory"); }
__device__ __forceinline__ void wgmma_commit() { asm volatile("wgmma.commit_group.sync.aligned;" ::: "memory"); }
template <int N> __device__ __forceinline__ void wgmma_wait() { asm volatile("wgmma.wait_group.sync.aligned %0;" ::"n"(N) : "memory"); }
__device__ __forceinline__ void fence_async() { asm volatile("fence.proxy.async.shared::cta;" ::: "memory"); }
__device__ __forceinline__ void bar_sync(int id, int n) { asm volatile("bar.sync %0, %1;" ::"r"(id), "r"(n) : "memory"); }
__device__ __forceinline__ void bar_arrive(int id, int n) { asm volatile("bar.arrive %0, %1;" ::"r"(id), "r"(n) : "memory"); }

constexpr uint32_t SM_BASE = 1024;
__host__ __device__ constexpr uint32_t mk_desc(uint32_t addr, uint32_t lbo_bytes) { return ((addr & 0x3FFFF) >> 4) | ((lbo_bytes >> 4) << 16); }

#define R32(d) \
  "+f"(d[0]), "+f"(d[1]), "+f"(d[2]), "+f"(d[3]), "+f"(d[4]), "+f"(d[5]), "+f"(d[6]), "+f"(d[7]), \
  "+f"(d[8]), "+f"(d[9]), "+f"(d[10]), "+f"(d[11]), "+f"(d[12]), "+f"(d[13]), "+f"(d[14]), "+f"(d[15]), \
  "+f"(d[16]), "+f"(d[17]), "+f"(d[18]), "+f"(d[19]), "+f"(d[20]), "+f"(d[21]), "+f"(d[22]), "+f"(d[23]), \
  "+f"(d[24]), "+f"(d[25]), "+f"(d[26]), "+f"(d[27]), "+f"(d[28]), "+f"(d[29]), "+f"(d[30]), "+f"(d[31])
#define R64(d) R32(d), \
  "+f"(d[32]), "+f"(d[33]), "+f"(d[34]), "+f"(d[35]), "+f"(d[36]), "+f"(d[37]), "+f"(d[38]), "+f"(d[39]), \
  "+f"(d[40]), "+f"(d[41]), "+f"(d[42]), "+f"(d[43]), "+f"(d[44]), "+f"(d[45]), "+f"(d[46]), "+f"(d[47]), \
  "+f"(d[48]), "+f"(d[49]), "+f"(d[50]), "+f"(d[51]), "+f"(d[52]), "+f"(d[53]), "+f"(d[54]), "+f"(d[55]), \
  "+f"(d[56]), "+f"(d[57]), "+f"(d[58]), "+f"(d[59]), "+f"(d[60]), "+f"(d[61]), "+f"(d[62]), "+f"(d[63])
#define S32 \
  "{%0,%1,%2,%3,%4,%5,%6,%7,%8,%9,%10,%11,%12,%13,%14,%15,%16,%17,%18,%19,%20,%21,%22,%23,%24,%25,%26,%27,%28,%29,%30,%31}"
#define S64 \
  "{%0,%1,%2,%3,%4,%5,%6,%7,%8,%9,%10,%11,%12,%13,%14,%15,%16,%17,%18,%19,%20,%21,%22,%23,%24,%25,%26,%27,%28,%29,%30,%31," \
  "%32,%33,%34,%35,%36,%37,%38,%39,%40,%41,%42,%43,%44,%45,%46,%47,%48,%49,%50,%51,%52,%53,%54,%55,%56,%57,%58,%59,%60,%61,%62,%63}"

template <int TB>
__device__ __forceinline__ void wgmma128_rs(float (&d)[64], uint32_t a0, uint32_t a1, uint32_t a2, uint32_t a3, uint32_t db, int scale_d) {
  asm volatile("{\n.reg .pred p;\n.reg .b64 q;\nsetp.ne.b32 p, %69, 0;\nmov.b64 q, {%68, 0x40000040};\n"
               "wgmma.mma_async.sync.aligned.m64n128k16.f32.bf16.bf16 " S64 ", {%64,%65,%66,%67}, q, p, 1, 1, %70;\n}\n"
               : R64(d) : "r"(a0), "r"(a1), "r"(a2), "r"(a3), "r"(db), "r"(scale_d), "n"(TB));
}
__device__ __forceinline__ void wgmma64_rs(float (&d)[32], uint32_t a0, uint32_t a1, uint32_t a2, uint32_t a3, uint32_t db, int scale_d) {
  asm volatile("{\n.reg .pred p;\n.reg .b64 q;\nsetp.ne.b32 p, %37, 0;\nmov.b64 q, {%36, 0x40000040};\n"
               "wgmma.mma_async.sync.aligned.m64n64k16.f32.bf16.bf16 " S32 ", {%32,%33,%34,%35}, q, p, 1, 1, 1;\n}\n"
               : R32(d) : "r"(a0), "r"(a1), "r"(a2), "r"(a3), "r"(db), "r"(scale_d));
}
__device__ __forceinline__ uint32_t pack_bf16(float a, float b) {
  uint32_t r;
  asm("cvt.rn.bf16x2.f32 %0, %1, %2;" : "=r"(r) : "f"(b), "f"(a));
  return r;
}
__device__ __forceinline__ float ex2(float x) { float y; asm("ex2.approx.ftz.f32 %0, %1;" : "=f"(y) : "f"(x)); return y; }
__device__ __forceinline__ float bfr(float x) { return __bfloat162float(__float2bfloat16(x)); }
__device__ __forceinline__ float bf_lo(uint32_t u) { return __uint_as_float(u << 16); }
__device__ __forceinline__ float bf_hi(uint32_t u) { return __uint_as_float(u & 0xffff0000u); }
__device__ __forceinline__ uint4 lds128(uint32_t a) {
  uint4 v;
  asm volatile("ld.shared.v4.b32 {%0,%1,%2,%3}, [%4];" : "=r"(v.x), "=r"(v.y), "=r"(v.z), "=r"(v.w) : "r"(a) : "memory");
  return v;
}
__device__ __forceinline__ void sts128(uint32_t a, uint4 v) {
  asm volatile("st.shared.v4.b32 [%0], {%1,%2,%3,%4};" ::"r"(a), "r"(v.x), "r"(v.y), "r"(v.z), "r"(v.w) : "memory");
}
__device__ __forceinline__ void red_add_v4(float4* p, float a, float b, float c, float d) {
  asm volatile("red.global.add.v4.f32 [%0], {%1,%2,%3,%4};" ::"l"(p), "f"(a), "f"(b), "f"(c), "f"(d) : "memory");
}
__device__ __forceinline__ float rcp(float x) { float y; asm("rcp.approx.ftz.f32 %0, %1;" : "=f"(y) : "f"(x)); return y; }
__device__ __forceinline__ float sqrt_a(float x) { float y; asm("sqrt.approx.ftz.f32 %0, %1;" : "=f"(y) : "f"(x)); return y; }
__device__ __forceinline__ float silu_f(float v) { return v * rcp(1.f + __expf(-v)); }
__device__ __forceinline__ float silu_bf(float v) { return bfr(v * rcp(1.f + __expf(-v))); }

constexpr int SM_STASH = 131072;
constexpr int QG = 73728;
constexpr int SM_STG = 3 * QG - 18432;
constexpr int SM_MT = 3 * QG;
constexpr int SM_MB = SM_MT + 4608;
constexpr int SM_XCH = 196608;
constexpr int SM_MISC = 229376;
constexpr int SM_TOTAL = 232448;
constexpr int B_FULLQ = 0, B_TB = 24, B_G2 = 32, B_G3 = 40, B_QH = 48, B_FULLA = 64, B_XR = 96, B_FULLO = 184, B_FFN = 160, B_FD = 168, B_MD = 176, B_X = 2944, B_X1 = 2952, B_MM = 2984,
              B_EMPTYQ = 280, B_G1 = 304, B_EMPTYO = 328, B_ST = 392,
              B_EMPTYA = 400, B_M = 432, B_XF = 144;
constexpr int SM_MOD = SM_MISC + 448;
constexpr int SM_FILL = SM_MISC + 512;
constexpr int SM_M2 = SM_MISC + 2560;
constexpr int SM_RED = SM_MISC + 2752;
constexpr int SM_ZERO = SM_MISC + 3040;
constexpr int SM_WG = 137216;
constexpr int SM_X2 = 65536;
constexpr int SM_WD = 84992;
constexpr int SM_T = 23040;
constexpr int T_H = 2816;
constexpr int SM_PS = SM_T + 5120;
constexpr int SM_OUT = SM_MISC - 16384;
constexpr int SM_MD = SM_STASH + (EB ? 11520 : 0);

template <class F>
__device__ __forceinline__ void ln_rows(uint32_t (&A)[144], uint32_t la, int lane, F done) {
  float mA = 0.f, mB = 0.f, vA, vB;
  bool redo = la >> 31;
#pragma unroll 1
  do {
    if (__builtin_expect(redo, 0)) {
      const uint32_t n2 = __shfl_sync(~0u, pack_bf16(mA, mB), (lane & 7) * 4);
      const uint32_t n = __byte_perm(n2, 0, (lane & 8) ? 0x3232 : 0x1010);
#pragma unroll 1
      for (int k = 0; k < 36; k++) {
        const uint32_t a = (la ^ ((k & 3) << 5)) + (k >> 2) * 4096;
        const uint4 v = lds128(a);
        sts128(a, make_uint4(hadd2(v.x, n), hadd2(v.y, n), hadd2(v.z, n), hadd2(v.w, n)));
      }
      fence_async();
      __syncwarp();
    }
    const uint32_t one = 0x3f803f80u;
    float c[3][4], q[3][4];
#pragma unroll
    for (int i = 0; i < 12; i++) c[i >> 2][i & 3] = q[i >> 2][i & 3] = 0.f;
#pragma unroll
    for (int k = 0; k < 36; k++) {
      uint32_t a[4];
      ldsm4(a, (la ^ ((k & 3) << 5)) + (k >> 2) * 4096);
      A[k * 4] = a[0]; A[k * 4 + 1] = a[1]; A[k * 4 + 2] = a[2]; A[k * 4 + 3] = a[3];
    }
#pragma unroll
    for (int k = 0; k < 36; k++) {
      mma16816(c[k % 3], A[k * 4], A[k * 4 + 1], A[k * 4 + 2], A[k * 4 + 3], one, one);
      mma16816(q[k % 3], hmul2(A[k * 4], A[k * 4]), hmul2(A[k * 4 + 1], A[k * 4 + 1]), hmul2(A[k * 4 + 2], A[k * 4 + 2]), hmul2(A[k * 4 + 3], A[k * 4 + 3]), one, one);
    }
    mA = (c[0][0] + c[1][0] + c[2][0]) * (-1.f / DM); mB = (c[0][2] + c[1][2] + c[2][2]) * (-1.f / DM);
    vA = fmaf(-mA, mA, (q[0][0] + q[1][0] + q[2][0]) * (1.f / DM)); vB = fmaf(-mB, mB, (q[0][2] + q[1][2] + q[2][2]) * (1.f / DM));
    redo = __any_sync(~0u, !(mA * mA <= LN_LIMIT * vA && mB * mB <= LN_LIMIT * vB)) && !redo;
  } while (__builtin_expect(redo, 0));
  done();
  const float rA = rsqrtf(fmaxf(vA, 0.f) + 1e-5f), rB = rsqrtf(fmaxf(vB, 0.f) + 1e-5f);
  const uint32_t hA = pack_bf16(rA, rA), hB = pack_bf16(rB, rB);
  const uint32_t lA = pack_bf16(rA - bf_lo(hA), rA - bf_lo(hA)), lB = pack_bf16(rB - bf_lo(hB), rB - bf_lo(hB));
  const uint32_t oA = pack_bf16(mA * rA, mA * rA), oB = pack_bf16(mB * rB, mB * rB);
#pragma unroll
  for (int i = 0; i < 144; i++) A[i] = hfma2(A[i], (i & 1) ? hB : hA, N2 ? ((i & 1) ? oB : oA) : hfma2(A[i], (i & 1) ? lB : lA, (i & 1) ? oB : oA));
}
__device__ __forceinline__ void modulate(uint32_t (&A)[144], uint32_t mt) {
#pragma unroll
  for (int k = 0; k < 36; k++) {
    const uint4 m = lds128(mt + k * 64);
    A[k * 4] = hfma2(A[k * 4], m.y, m.x); A[k * 4 + 1] = hfma2(A[k * 4 + 1], m.y, m.x);
    A[k * 4 + 2] = hfma2(A[k * 4 + 2], m.w, m.z); A[k * 4 + 3] = hfma2(A[k * 4 + 3], m.w, m.z);
  }
}
__device__ __forceinline__ void q_mma(float (&qa)[32], const uint32_t (&A)[144], uint32_t db) {
#pragma unroll
  for (int k = 0; k < 36; k++) wgmma64_rs(qa, A[k * 4], A[k * 4 + 1], A[k * 4 + 2], A[k * 4 + 3], db + k * 128, k != 0);
  wgmma_commit();
}
constexpr float Q_SCALE = 0.08838834764831845f * 1.4426950408889634f;

struct Params {
  uint4* mod1;
  const bf16 *c, *w_mod, *x, *k, *v, *wq, *w_r, *wo, *wg, *wu, *wd;
  bf16* out;
};

__global__ void __cluster_dims__(2, 1, 1) __launch_bounds__(384, 1)
k_mega(const Params prm, const __grid_constant__ CUtensorMap mX, const __grid_constant__ CUtensorMap mWq,
       const __grid_constant__ CUtensorMap mK, const __grid_constant__ CUtensorMap mV,
       const __grid_constant__ CUtensorMap mWo, const __grid_constant__ CUtensorMap mWg,
       const __grid_constant__ CUtensorMap mWu, const __grid_constant__ CUtensorMap mWd, const __grid_constant__ CUtensorMap mM,
       const __grid_constant__ CUtensorMap mWo0, const __grid_constant__ CUtensorMap mWo1, const __grid_constant__ CUtensorMap mWh,
       const __grid_constant__ CUtensorMap mXh) {
  extern __shared__ __align__(1024) uint8_t smem_raw[];
#define ECLK(x)
  const uint32_t sb = smem_u32(smem_raw);
  if ((sb & 0x3FFFF) != SM_BASE) __trap();
  const uint32_t sBar = sb + SM_MISC;
  const int tid = threadIdx.x;
  const int lane = get_lane();
  const int warp = __shfl_sync(~0u, tid >> 5, 0);
  const int b = blockIdx.x, rank = b & 1, qt = (b >> 1) & 15, kg = b >> 5, hg = kg * 2 + rank;
  const int hcol = (kg * 8 + rank) * DH;
#define CL_ARRIVE() asm volatile("barrier.cluster.arrive.relaxed.aligned;" ::: "memory")
#define CL_WAIT() asm volatile("barrier.cluster.wait.acquire.aligned;" ::: "memory")
  constexpr int HN = KO <= 3 ? 4 : 3, HS_ = KO <= 3 ? 49152 : 65536, H0 = 2, H_FULL = 48, H_GA = 80, H_EMPTY = 304, SM_GA = SM_MT + 2560;
  constexpr int H_DONE = 336, H_XF = 184, H_GO = 208, H_XE = 400, SM_HX = 196608;
  if (__builtin_expect(b >= 128 && warp < 4, 0)) {
    if (tid < 3) {
      mbar_init(sBar + B_X + tid * 8, 1);
      asm volatile("fence.mbarrier_init.release.cluster;" ::: "memory");
    }
    __syncwarp();
    CL_ARRIVE();
    asm volatile("setmaxnreg.dec.sync.aligned.u32 40;");
    CL_WAIT();
    CL_ARRIVE();
    if (warp == 0) bar_sync(9, 288);
    CL_WAIT();
    {
      if (tid == 0) {
        mbar_arrive(sBar + B_FULLQ + 16);
#pragma unroll 1
        for (int n = 0, g = 0, ph = 1, m = 0, row = (b - 128) * 512; n < 40; n++) {
          if (n >= 3) mbar_wait(sBar + B_EMPTYQ + g * 8, ph);
          mbar_expect_tx(sBar + B_X + g * 8, QG);
          if (m < 2) {
            tma_load_3d(sb + g * QG, &mX, sBar + B_X + g * 8, 0, row, 0);
            tma_load_3d(sb + g * QG + QG / 2, &mX, sBar + B_X + g * 8, 0, row + 32, 0);
            row += 64;
          } else {
#pragma unroll 1
            for (int i = 0; i < 4; i++) tma_load_2d(sb + g * QG + i * 18432, &mWq, sBar + B_X + g * 8, (((m - 2) >> 1) * 8 + (m & 1) + 6) * DH + 64, i * 144);
          }
          if (++g == 3) { g = 0; ph ^= 1; }
          if (++m == 10) m = 0;
        }
#pragma unroll 1
        for (int n = 0, s = H0, m = 0, q = (b - 128) * 4; n < 44; n++) {
          if (n == 0) mbar_wait(sBar + B_EMPTYQ + 8, 0);
          if (n == HN - 3) { mbar_wait(sBar + B_EMPTYQ + 16, 0); mbar_arrive(sBar + H_GO); }
          if (n == HN - 2) mbar_wait(sBar + B_EMPTYQ, 1);
          if (n >= HN) mbar_wait(sBar + H_EMPTY + s * 8, ((n - HN) / HN) & 1);
          if (m == 0) cnt_acq((C_Q + q) * 32, 8, 0);
          if ((HT & 8) && m >= 2) mbar_arrive(sBar + H_FULL + s * 8); else
          mbar_expect_tx(sBar + H_FULL + s * 8, KO * 16384);
          if (m < 2) {
#pragma unroll 1
            for (int i = 0; i < 4; i++)
              bulk_load(sb + s * HS_ + i * (KO * 4096), g_q + ((m * 2 + (i >> 1)) * 32 + q * 2 + (i & 1)) * 8192, KO * 4096, sBar + H_FULL + s * 8);
          } else if (!(HT & 8)) {
            asm volatile("cp.async.bulk.tensor.4d.shared::cluster.global.mbarrier::complete_tx::bytes [%0], [%1, {%3, %4, %4, %4}], [%2];"
                         ::"r"(sb + s * HS_), "l"(&mWh), "r"(sBar + H_FULL + s * 8), "r"((m - 2) * 64), "r"(0) : "memory");
          }
          if (++s == HN) s = 0;
          if (++m == 11) { m = 0; q++; }
        }
      } else if (warp > 0) {
        if (tid < 104) {
          uint4 v, w;
          poll8(prm.mod1 + tid - 32, prm.mod1 + tid + 40, v, w);
          uint2* const mt = reinterpret_cast<uint2*>(smem_raw + SM_MT) + ((tid - 32) >> 1) * 8 + (tid & 1);
          mt[0] = make_uint2(~v.x, ~w.x); mt[2] = make_uint2(~v.y, ~w.y); mt[4] = make_uint2(~v.z, ~w.z); mt[6] = make_uint2(~v.w, ~w.w);
        }
        __syncwarp();
        bar_arrive(3, 224);
        bar_arrive(4, 224);
        if (warp == 1) {
#pragma unroll 1
          for (int i = 0; i < 4; i++) bar_arrive(1, 288);
#pragma unroll 1
          for (int n = 0, g = 0, ph = 0, m = 0; n < 40; n++) {
            if (m >= 2) { mbar_wait(sBar + B_X + g * 8, ph); bar_sync(1, 288); }
            if (++g == 3) { g = 0; ph ^= 1; }
            if (++m == 10) m = 0;
          }
#pragma unroll 1
          for (int n = 0, s = H0, m = 0; n < 44; n++) {
            if (m >= 2) { mbar_wait(sBar + H_FULL + s * 8, (n / HN) & 1); bar_sync(1, 288); }
            if (++s == HN) s = 0;
            if (++m == 11) m = 0;
          }
        }
        if (KO && tid == 64) {
          cnt_acq(C_M2 * 32, 72, 1000);
          mbar_expect_tx(sBar + H_GA, 4608);
          bulk_load(sb + SM_GA, g_mod2, 4608, sBar + H_GA);
          mbar_wait(sBar + H_GO, 0);
#pragma unroll 1
          for (int j = 0, g = 0, ph = 1, c = 0, row = (b - 128) * 512; j < 72; j++) {
            if (XPH && j + XPH * 2 < 72) {
              const int c2 = c + XPH * 64;
              tma_prefetch_2d(&mXh, c2 < DM ? c2 : c2 - DM, row + (j & 1) * 64 + (c2 < DM ? 0 : 128));
            }
            if (j >= 3) mbar_wait(sBar + H_XE + g * 8, ph);
            if (HT & 4) mbar_arrive(sBar + H_XF + g * 8); else mbar_expect_tx(sBar + H_XF + g * 8, 8192);
            if (!(HT & 4)) tma_load_2d(sb + SM_HX + g * 8192, &mXh, sBar + H_XF + g * 8, c, row + (j & 1) * 64);
            if (++g == 3) { g = 0; ph ^= 1; }
            if ((j & 1) && (c += 64) == DM) { c = 0; row += 128; }
          }
        }
        if (warp == 3) {
          const int lane = get_lane();
#pragma unroll 1
          for (int i = 0; i < (KO ? 8 : 4); i++) {
            mbar_wait(sBar + H_DONE + i * 8, 0);
            asm volatile("fence.acq_rel.gpu;" ::: "memory");
            if (lane < 8) str1(&g_cnt[(C_Q + (lane >> 1) * 32 + ((b - 128) * 4 + (i & 3)) * 2 + (lane & 1)) * 32 + 2 + (i >> 2)], 8);
          }
        }
      }
    }
    return;
  }
  uint32_t cv[3];
  auto ld_c = [&]() {
#pragma unroll
    for (int i = 0; i < 3; i++) asm volatile("ld.volatile.global.u32 %0, [%1];" : "=r"(cv[i]) : "l"(reinterpret_cast<const uint32_t*>(prm.c) + (warp - 1) * 96 + i * 32 + lane) : "memory");
  };
  if (warp < 4 && warp > 0 && b < 72) {
    if (CL == 0) ld_c();
    if (lane == 0) {
      mbar_init(sBar + B_X1 + warp * 8, 1);
      asm volatile("fence.mbarrier_init.release.cluster;" ::: "memory");
      tma_load_2d(sb + SM_STG + (warp - 1) * 6144, &mM, sBar + B_X1 + warp * 8, b * 16, (warp - 1) * 192);
      mbar_expect_tx(sBar + B_X1 + warp * 8, 6144);
    }
    if (CL == 2) { __syncwarp(); ld_c(); }
  }
  if (tid == 0) {
    if (TMP) asm volatile("prefetch.tensormap [%0];" ::"l"(&mX) : "memory");
    mbar_init(sBar + B_X, 1);
    mbar_init(sBar + B_X1, 1);
#pragma unroll
    for (int i = 0; i < __builtin_popcount(MM); i++) mbar_init(sBar + B_MM + i * 8, 1);
    asm volatile("fence.mbarrier_init.release.cluster;" ::: "memory");
  }
  __syncwarp();
  ECLK(e1);
  CL_ARRIVE();
  ECLK(e2);
  if (warp < 4) asm volatile("setmaxnreg.dec.sync.aligned.u32 40;");
  if (warp == 0) {
    CL_WAIT();
    ECLK(e3);
    CL_ARRIVE();
    bar_sync(9, 288);
    if (lane == 0) {
      if (XD) delay(XD);
      tma_load_3d_mc(sb + rank * (QG / 2), &mX, sBar + B_X, 0, qt * 128 + rank * 32, 0);
      mbar_expect_tx(sBar + B_X, QG);
      if (!XO) {
        if (XD1) delay(XD1);
        tma_load_3d_mc(sb + QG + rank * (QG / 2), &mX, sBar + B_X1, 0, qt * 128 + 64 + rank * 32, 0);
        mbar_expect_tx(sBar + B_X1, QG);
      }
    }
    __syncwarp();
    ECLK(e4);
  } else if (warp < 4) {
    ECLK(e3);
    if (b < 72) {
      if (CL == 1) ld_c();
      const int g = lane >> 2, t4 = lane & 3;
      uint32_t se[3] = {0u, 0u, 0u}, so[3] = {0u, 0u, 0u};
#pragma unroll 1
      for (int live = !MWARM; live < 2; live++) {
        if (live) {
#pragma unroll
          for (int i = 0; i < 3; i++) {
            const uint32_t u = __shfl_sync(~0u, cv[i], lane);
            const uint32_t v = pack_bf16(silu_f(bf_lo(u)), silu_f(bf_hi(u)));
            se[i] = (g & 1) ? 0u : v; so[i] = (g & 1) ? v : 0u;
          }
          ECLK(e4);
          mbar_wait(sBar + B_X1 + warp * 8, 0);
          ES(32, 0, 93);
        }
        float a[4][4];
#pragma unroll
        for (int i = 0; i < 16; i++) a[i >> 2][i & 3] = 0.f;
        const uint32_t la = sb + SM_STG + ((lane >> 3) & 1) * 16 + ((warp - 1) * 192 + (lane & 7) + (lane >> 4) * 8) * 32;
#pragma unroll
        for (int i = 0; i < 12; i++) {
          uint32_t w[4];
          ldsm4t(w, la + i * 512);
          mma16816(a[i & 3], w[0], w[1], w[2], w[3], se[i >> 2], so[i >> 2]);
        }
        float v0 = (t4 & 2) ? ((t4 & 1) ? a[3][0] + a[3][1] : a[2][0] + a[2][1]) : ((t4 & 1) ? a[1][0] + a[1][1] : a[0][0] + a[0][1]);
        float v1 = (t4 & 2) ? ((t4 & 1) ? a[3][2] + a[3][3] : a[2][2] + a[2][3]) : ((t4 & 1) ? a[1][2] + a[1][3] : a[0][2] + a[0][3]);
        float* const red = reinterpret_cast<float*>(smem_raw + SM_MT + 2560 + live * 768);
        red[g * 12 + (warp - 1) * 4 + t4] = v0;
        red[g * 12 + 96 + (warp - 1) * 4 + t4] = v1;
        ES(32, 0, 94);
        bar_sync(6, 96);
        const float4* rp = reinterpret_cast<const float4*>(red + (lane & 7) * 24);
        const float4 x0 = rp[0], x1 = rp[1], x2 = rp[2], y0 = rp[3], y1 = rp[4], y2 = rp[5];
        uint32_t w = pack_bf16((((x0.x + x0.y) + (x0.z + x0.w)) + ((x1.x + x1.y) + (x1.z + x1.w))) + ((x2.x + x2.y) + (x2.z + x2.w)),
                               (((y0.x + y0.y) + (y0.z + y0.w)) + ((y1.x + y1.y) + (y1.z + y1.w))) + ((y2.x + y2.y) + (y2.z + y2.w)));
        if (b >= 36) w = hadd2(w, 0x3f803f80u);
        if (live && tid < 96)
          asm volatile("st.relaxed.gpu.global.u32 [%0], %1;" ::"l"(reinterpret_cast<uint32_t*>(prm.mod1) + ((tid - 32) >> 3) * 576 + b * 8 + (lane & 7)), "r"(~w) : "memory");
      }
    } else if (PD) delay(PD);
    ES(32, 0, 89);
    CL_WAIT();
    CL_ARRIVE();
    CL_WAIT();
    if (lane == 0) mbar_arrive(sBar + B_M);
    if (tid < 104) {
      uint4 v, w;
      if (PW) mbar_wait(sBar + B_X, 0);
      bool ok = false;
#pragma unroll 1
      for (int i = 0; i < __builtin_popcount(MM) && !ok; i++) {
        mbar_wait(sBar + B_MM + i * 8, 0);
        v = lds128(sb + SM_MB + (tid - 32) * 16);
        w = lds128(sb + SM_MB + (tid + 40) * 16);
        ok = v.x && v.y && v.z && v.w && w.x && w.y && w.z && w.w;
      }
      if (!ok) poll8(prm.mod1 + (b & 7) * 144 + tid - 32, prm.mod1 + (b & 7) * 144 + tid + 40, v, w);
      uint2* const mt = reinterpret_cast<uint2*>(smem_raw + SM_MT) + ((tid - 32) >> 1) * 8 + (tid & 1);
      mt[0] = make_uint2(~v.x, ~w.x); mt[2] = make_uint2(~v.y, ~w.y); mt[4] = make_uint2(~v.z, ~w.z); mt[6] = make_uint2(~v.w, ~w.w);
    }
    __syncwarp();
    ES(32, 0, 92);
    bar_arrive(3, 224);
    bar_arrive(4, 224);
    if (lane == 0) mbar_arrive(sBar + B_M + 8);
  } else {
    if (lane == 0) {
      if (MPF && warp < 10 && b < 96) bulk_prefetch(prm.w_mod + (size_t)(b * 6 + warp - 4) * (6 * DM), 2 * DM * 2);
      const int c0 = warp < 9 ? 1 : 8, c1 = warp < 11 ? c0 : 16, c2 = warp < 11 ? c0 : 3;
#pragma unroll
      for (int j = 0; j < 7; j++) mbar_init(sBar + (warp - 4) * 56 + j * 8, j == 0 ? c0 : j < 5 ? c1 : c2);
      *reinterpret_cast<uint4*>(smem_raw + SM_ZERO) = make_uint4(0u, 0u, 0u, 0u);
      asm volatile("fence.mbarrier_init.release.cluster;" ::: "memory");
    }
    __syncwarp();
    CL_WAIT();
    CL_ARRIVE();
    bar_sync(9, 288);
  }
  if (warp < 4) {
    auto ffn_box = [&](int fb) {
      tma_load_2d(sb + (fb == 5 || fb == 6 ? -57600 : EB && fb == 0 ? SM_STASH : SM_WG) + fb * 11520, fb >= 4 ? &mWu : &mWg, sBar + B_FFN, (b * 36) & ~7, (fb & 3) * 144);
    };
    if (__shfl_sync(~0u, tid, 0) == 0) {
     if (lane == 0) {
      const uint64_t pol = pol_first();
      auto kv_load = [&](int t) {
        const int s = t & 3;
        mbar_wait(sBar + B_EMPTYA + s * 8, (t >> 2) & 1);
        mbar_expect_tx(sBar + B_FULLA + s * 8, 32768);
        if (EF & 1) tma_load_2d_mc_h(sb + s * 32768 + rank * 16384, (t & 1) ? &mV : &mK, sBar + B_FULLA + s * 8, rank * 64, kg * 4 * SK + (t >> 1) * 128, pol);
        else tma_load_2d_mc(sb + s * 32768 + rank * 16384, (t & 1) ? &mV : &mK, sBar + B_FULLA + s * 8, rank * 64, kg * 4 * SK + (t >> 1) * 128);
      };
#pragma unroll 1
      for (int i = 0, g = 2; i < 28; i++) {
        const int hh = (i >> 2) + 2 + (i >= 20);
        if (XO && i == XO) {
          tma_load_3d_mc(sb + QG + rank * (QG / 2), &mX, sBar + B_X1, 0, qt * 128 + 64 + rank * 32, 0);
          mbar_expect_tx(sBar + B_X1, QG);
        }
        if (XW && i == XW - 1) mbar_wait(sBar + B_X, 0);
        if (i < 7 && ((MM >> i) & 1)) {
          const uint32_t mb = sBar + B_MM + __popc(MM & ((1 << i) - 1)) * 8;
          bulk_load(sb + SM_MB, prm.mod1 + (b & 7) * 144, 2304, mb);
          mbar_expect_tx(mb, 2304);
        }
        if (i == 3) mbar_wait(sBar + B_M, 0);
        if (i == QTH) mbar_wait(sBar + B_M + 8, 0);
        if (!(i & 3)) {
          if (i) mbar_wait(sBar + B_EMPTYQ + g * 8, i >= 16);
          else if (QW) mbar_wait(sBar + B_X, 0);
          mbar_expect_tx(sBar + B_FULLQ + g * 8, QG);
        }
        if (EF & 2) tma_load_2d_h(sb + g * QG + (i & 3) * 18432, &mWq, sBar + B_FULLQ + g * 8, hcol + (hh & 6) * 128 + (hh & 1) * 64, (i & 3) * 144, pol);
        else tma_load_2d(sb + g * QG + (i & 3) * 18432, &mWq, sBar + B_FULLQ + g * 8, hcol + (hh & 6) * 128 + (hh & 1) * 64, (i & 3) * 144);
        if ((i & 3) == 3 && ++g == 3) g = 0;
      }
#pragma unroll 1
      for (int u = 0; u < 128; u++) kv_load(u < 5 || u == 127 ? u : (u & 1) ? u + 1 : u - 1);
      if (!GX) mbar_wait(sBar + B_X, 1);
      {
        mbar_expect_tx(sBar + B_FFN, 2 * DM * 80);
        mbar_expect_tx(sBar + B_FD, 9 * 5120);
#pragma unroll 1
        for (int i = 0; i < 18; i++) {
          const int g = i & 3;
          mbar_wait(sBar + (i < 4 ? B_EMPTYA : B_EMPTYO) + g * 8, i >= 8 && !(i & 4));
          KSTAMP(270 + i);
          if (KO && !(i & 1)) {
            tma_load_4d_h(sb + g * 32768 + KO * 2048, &mWo0, sBar + B_FULLO + g * 8, (i >> 1) * 64, KO * 16, rank, kg * 4, pol);
            tma_load_4d_h(sb + g * 32768 + 16384, &mWo1, sBar + B_FULLO + g * 8, (i >> 1) * 64, 0, rank, kg * 4 + 1, pol);
            mbar_expect_tx(sBar + B_FULLO + g * 8, 32768 - KO * 2048);
          } else {
            mbar_expect_tx(sBar + B_FULLO + g * 8, 32768);
            tma_load_4d_h(sb + g * 32768, &mWo, sBar + B_FULLO + g * 8, (i >> 1) * 64, 0, rank, kg * 4 + (i & 1) * 2, pol);
          }
        }
        if (!(KO && XL)) mbar_expect_tx(sBar + B_XR, 16 * 1152);
        if (KO && !XL) cnt_acq((C_Q + b) * 32 + 3, 1, 0);
      }
     }
     __syncwarp();
     CL_WAIT();
     {
        const int lane = get_lane();
        if (!(KO && XL)) mbar_wait(sBar + B_EMPTYO + 16, 1);
        if (KO) { if (!XL && lane == 0) bulk_load(sb + SM_X2, g_q + b * 8192, 16 * 1152, sBar + B_XR); }
        else if (lane < 16) bulk_load(sb + SM_X2 + lane * 1168, prm.x + (size_t)(qt * 128 + hg * 16 + lane) * DM, 1152, sBar + B_XR);
        __syncwarp();
        if (lane == 0) {
          mbar_wait(sBar + B_EMPTYO + 24, 1);
          if (LATEG & 4) mbar_wait(sBar + B_G1, 0);
          tma_load_3d(sb + SM_WD, &mWd, sBar + B_FD, 0, b * 36, 0);
          mbar_wait(sBar + B_EMPTYO, 0);
          if (LATEG & 2) mbar_wait(sBar + B_G1, 0);
          ffn_box(5); ffn_box(6);
        }
      }
    } else if (warp == 3) {
#pragma unroll 1
      for (int i = 1, g = 0; i < 7; i++) {
        mbar_wait(sBar + B_FULLQ + g * 8, i >= 3 && i < 6);
        if (++g == 3) g = 0;
        if (i == 0) { ES(96, 0, 9); } else { KSTAMP(170 + i * 2); } bar_sync(1, 288); if (i == 0) { ES(96, 0, 10); } else { KSTAMP(171 + i * 2); }
      }
      long long nxt = 0;
#pragma unroll 1
      for (int u = 0; u < 128; u++) {
        const int t = (u == 0 || u == 127) ? u : (u & 1) ? u + 1 : u - 1;
        mbar_wait(sBar + B_FULLA + (t & 3) * 8, (t >> 2) & 1);
        if (QL ? (t & 31) == 30 && t < 96 : t == 94) mbar_wait(sBar + B_QH, QL ? (t >> 5) & 1 : 0);
        if (!(t & 3)) *reinterpret_cast<volatile uint32_t*>(smem_raw + SM_ZERO + 12) = t >> 2;
        if (!(t & 1) || t == 127) { KSTAMP((t + 1) & ~1);
          bar_sync(1, 288); KSTAMP(((t + 1) & ~1) + 1); }
        else { bar_sync(10, 160); }
      }
      if (lane < 4) mbar_expect_tx(sBar + B_XF - 16 + lane * 8, 4096);
#pragma unroll 1
      for (int i = 0; i < 18; i++) {
        mbar_wait(sBar + B_FULLO + (i & 3) * 8, (i >> 2) & 1);
        const bool rc = (i & 1) && i > 1 && i < 17;
        const uint32_t xf = sBar + B_XF + ((i - 2) & 2) * 4;
        KSTAMP(260 + (i >> 1));
        if (rc) mbar_wait(xf, ((i - 2) >> 2) & 1);
        KSTAMP(130 + i * 2); if (i == 0) bar_sync(10, 160); else bar_sync(1, 288); KSTAMP(131 + i * 2);
        if (rc) mbar_wait(xf - 16, ((i - 2) >> 2) & 1);
        if (i & 1) bar_arrive(2, 288);
        if (rc && lane < 2) mbar_expect_tx(xf - lane * 16, 4096);
        __syncwarp();
      }
#pragma unroll 1
      for (int i = 0; i < (XG == 4 ? 0 : 18); i++) {
        if (XG != 1) mbar_wait(sBar + B_FULLO + (i & 3) * 8, (i >> 2) & 1);
        KSTAMP(190 + i);
        if (XG == 2) { KSTAMP(130 + i * 2); if (MG && i == 0) bar_sync(10, 160); else bar_sync(1, 288); KSTAMP(131 + i * 2); }
        if (GX && i == 3) mbar_wait(sBar + B_X, 1);
        if ((i & 1) && i > 1 && i < 17) {
          const uint32_t xf = sBar + B_XF + ((i - 2) & 2) * 4;
          KSTAMP(260 + (i >> 1));
          mbar_wait(xf, ((i - 2) >> 2) & 1);
          if (XG != 3) {
            __syncwarp();
            if (lane == 0) mbar_expect_tx(xf, 8192);
          }
        }
        if (XG == 1) mbar_wait(sBar + B_FULLO + (i & 3) * 8, (i >> 2) & 1);
        if (XG != 2) { KSTAMP(130 + i * 2); if (MG && i == 0) bar_sync(10, 160); else bar_sync(1, 288); KSTAMP(131 + i * 2); }
        if (XG == 3 && (i & 1) && i > 1 && i < 17 && lane == 0) mbar_expect_tx(sBar + B_XF + ((i - 2) & 2) * 4, 8192);
      }
    } else if (warp > 0) {
      const int st = tid - 32;
      mbar_wait(sBar + B_FULLQ + 16, 0);
      mbar_wait(sBar + B_FULLQ + 16, 1);
      const bf16* const kvp = (rank ? prm.v : prm.k) + ((size_t)kg * 4 * SK + qt * 128) * DH;
      if (st == 0) bulk_prefetch(kvp, 32768);
      mbar_wait(sBar + B_FULLA, 0);
      mbar_wait(sBar + B_FULLA, 1);
      if (warp == 1) {
#pragma unroll 1
        for (int grp = b < 72 ? b : 288; grp < 288; grp += 72) {
          float a[8];
#pragma unroll
          for (int i = 0; i < 8; i++) a[i] = 0.f;
#pragma unroll 2
          for (int r = lane; r < DM; r += 32) {
            uint4 v;
            if (EF & 16) asm("ld.global.nc.L2::cache_hint.v4.u32 {%0,%1,%2,%3}, [%4], %5;" : "=r"(v.x), "=r"(v.y), "=r"(v.z), "=r"(v.w) : "l"(prm.w_mod + (size_t)r * (6 * DM) + 2 * DM + grp * 8), "l"(pol_first()));
            else v = __ldg(reinterpret_cast<const uint4*>(prm.w_mod + (size_t)r * (6 * DM) + 2 * DM + grp * 8));
            float s = silu_bf(__bfloat162float(prm.c[r]));
            a[0] += s * bf_lo(v.x); a[1] += s * bf_hi(v.x); a[2] += s * bf_lo(v.y); a[3] += s * bf_hi(v.y);
            a[4] += s * bf_lo(v.z); a[5] += s * bf_hi(v.z); a[6] += s * bf_lo(v.w); a[7] += s * bf_hi(v.w);
          }
#pragma unroll
          for (int i = 0; i < 8; i++) a[i] = warp_sum(a[i]);
          if (lane == 0) {
            const int kind = grp / 72;
#pragma unroll
            for (int i = 0; i < 4; i++) {
              uint32_t w = pack_bf16(a[2 * i], a[2 * i + 1]);
              if (kind == 2) w = hadd2(w, 0x3f803f80u);
              reinterpret_cast<uint32_t*>(smem_raw + SM_M2)[i * 4 + kind] = w;
            }
            if (kind == 3) {
              fence_async();
              asm volatile("cp.async.bulk.global.shared::cta.bulk_group [%0], [%1], 64;" ::"l"(g_mod2 + b * 4), "r"(sb + SM_M2) : "memory");
              asm volatile("cp.async.bulk.commit_group;\ncp.async.bulk.wait_group 0;" ::: "memory");
              if (SIDEF & 1) asm volatile("fence.acq_rel.gpu;" ::: "memory");
              cnt_arrive(C_SIDE);
              if (KO) cnt_arrive(C_M2);
            }
          }
        }
        __syncwarp();
        if (KO && XL) {
          bar_sync(7, 64);
          if (lane == 0) {
#pragma unroll 1
            for (int i = 0; i < 4; i++) {
              if (i == XL) { cnt_acq((C_Q + b) * 32 + 3, 1, 0); mbar_expect_tx(sBar + B_XR, 16 * 1152); }
              mbar_wait(sBar + B_EMPTYO + 16, i & 1);
            }
            bulk_load(sb + SM_X2, g_q + b * 8192, 16 * 1152, sBar + B_XR);
          }
          __syncwarp();
        }
        bar_sync(8, 160);
        if (lane < 8) asm volatile("red.relaxed.gpu.global.add.u32 [%0], 1;" ::"l"(&g_cnt[(C_Q + qt * 8 + lane) * 32 + 1]) : "memory");
        PSTAMP(32, 56);
        const int lane = get_lane();
        PSTAMP(32, 57);
        cnt_wait1((C_Q + qt * 8 + hg) * 32 + 1, 8);
        PSTAMP(32, 59);
        if (lane == 0) mbar_arrive(sBar + B_G2);
        uint32_t k1 = ~0u, k2 = ~0u;
        uint4 hv[4];
        uint2 hw = make_uint2(0u, 0u);
        auto h_load = [&]() {
          const int r1 = k1 & (SQ - 1), r2 = k2 & (SQ - 1);
          const int r = lane < 16 ? r1 : r2;
          const int c = ((r >> 5) & 3) * 32 + (r >> 7) * 2 + ((r >> 4) & 1);
          const uint4* p = g_ones + F_HX + (c * 288 + (lane >= 16 && (r1 >> 4) == (r2 >> 4) ? 144 : 0) + (lane & 15));
#pragma unroll
          for (int i = 0; i < 4; i++) hv[i] = ldr4(p + i * 16);
          hw = ldr2(reinterpret_cast<const uint2*>(p + 64) - (lane & 15));
        };
#pragma unroll
        for (int i = 0; i < 4; i++) hv[i] = make_uint4(0u, 0u, 0u, 0u);
        const uint4* kp = g_ones + F_KEY + (b & 31) * 64 + lane * 2;
        auto merge = [](uint32_t& m1, uint32_t& m2, uint32_t n1, uint32_t n2) { m2 = min(max(m1, n1), min(m2, n2)); m1 = min(m1, n1); };
#pragma unroll 1
        for (uint32_t n = 0;; n++) {
          uint4 a, c;
          asm volatile("ld.relaxed.gpu.global.v4.u32 {%0,%1,%2,%3}, [%8];\nld.relaxed.gpu.global.v4.u32 {%4,%5,%6,%7}, [%8+16];"
                       : "=r"(a.x), "=r"(a.y), "=r"(a.z), "=r"(a.w), "=r"(c.x), "=r"(c.y), "=r"(c.z), "=r"(c.w) : "l"(kp) : "memory");
          const bool all = !__any_sync(~0u, unset(a) || unset(c));
          merge(a.x, a.y, a.z, a.w);
          merge(a.x, a.y, c.x, c.y);
          merge(a.x, a.y, c.z, c.w);
          const uint32_t m1 = __reduce_min_sync(~0u, a.x);
          const uint32_t m2 = __reduce_min_sync(~0u, a.x == m1 ? a.y : a.x);
          bool bad = m1 != k1 || m2 != k2 || hw.x == ~0u || hw.y == ~0u;
#pragma unroll
          for (int i = 0; i < 4; i++) bad |= unset(hv[i]);
          bad = __any_sync(~0u, bad);
          if (all && !bad) break;
          if (n > (1u << 15)) { SETERR(4); break; }
          if (bad) { k1 = m1; k2 = m2; h_load(); if (FW == 4) asm volatile("st.volatile.shared.b32 [%0], %1;" ::"r"(sb + SM_ZERO), "r"(~k2) : "memory"); }
        }
        PSTAMP(32, 60);
        {
          const uint32_t ha = sb + SM_T + T_H + (lane >> 4) * 1152 + (lane & 15) * 16;
#pragma unroll
          for (int i = 0; i < 4; i++) sts128(ha + i * 256, hv[i]);
          asm volatile("st.shared.v2.b32 [%0], {%1,%2};" ::"r"(ha + 1024 - (lane & 15) * 8), "r"(hw.x), "r"(hw.y) : "memory");
        }
        if (lane == 0) asm volatile("st.shared.v2.b32 [%0], {%1,%2};" ::"r"(sb + SM_T + 128), "r"(~k1), "r"(~k2) : "memory");
        __syncwarp();
        if (lane == 0) mbar_arrive(sBar + B_G3);
        PSTAMP(32, 61);
      } else {
#pragma unroll
        for (int i = 0; i < 4; i++) sts128(sb + SM_FILL + i * 512 + lane * 16, make_uint4(~0u, ~0u, ~0u, ~0u));
        fence_async();
        __syncwarp();
        const int lane = get_lane();
        const uint32_t dump = sb + SM_RED + 64 + lane * 4;
        auto touch128 = [&](const void* q) { asm volatile("cp.async.ca.shared.global.L2::128B [%0], [%1], 4;" ::"r"(dump), "l"(q) : "memory"); };
        auto touch256 = [&](const void* q) { asm volatile("cp.async.ca.shared.global.L2::256B [%0], [%1], 4;" ::"r"(dump), "l"(q) : "memory"); };
#pragma unroll 1
        for (int p = 2; p < FILLP; p++) {
          if (*reinterpret_cast<volatile uint32_t*>(smem_raw + SM_ZERO + 12) < p) mbar_wait(sBar + B_FULLA, p & 1);
          if (lane == 0) {
            if ((p & 7) == KVP && p < 24) {
              if (EF & 64) bulk_prefetch_f(kvp + (size_t)((p >> 3) + 1) * SK * DH, 32768);
              else bulk_prefetch(kvp + (size_t)((p >> 3) + 1) * SK * DH, 32768);
            }
            if (KO && p == OP) {
              fence_async();
              asm volatile("cp.async.bulk.global.shared::cta.bulk_group [%0], [%1], %2;" ::"l"(g_q + b * 8192), "r"(sb + SM_STASH), "n"(KO * 4096) : "memory");
              asm volatile("cp.async.bulk.commit_group;\ncp.async.bulk.wait_group 0;\nfence.acq_rel.gpu;" ::: "memory");
              cnt_arrive(C_Q + qt);
            }
            if (EB && p == EB) ffn_box(0);
            if (p == 16 + QPF) {
              cnt_wait1((C_Q + b) * 32 + 2, 8);
              asm volatile("fence.acq_rel.gpu;" ::: "memory");
              if (!QL) mbar_arrive(sBar + B_QH);
            }
            if (QL && (p & 7) == QPF && p < 24) {
              asm volatile("fence.proxy.async.global;" ::: "memory");
              mbar_expect_tx(sBar + B_QH, 32768);
              bulk_load(sb + SM_STASH + (p >> 3) * 32768, g_q + (b * 4 + (p >> 3) + 1) * 2048, 32768, sBar + B_QH);
            }
            if (!(TCH & 2) && XQ < 3 && !NQP && (p & 7) == QPF && p < 24) bulk_prefetch(g_q + ((size_t)b * 4 + (p >> 3) + 1) * 2048, 32768);
            if (!KO && !(TCH & 4) && p == FILLP - 1) bulk_prefetch(prm.x + (size_t)(qt * 128 + hg * 16) * DM, 16 * DM * 2);
            if (p == WOP) bulk_prefetch(prm.wo + ((size_t)kg * 1024 + (b & 31) * 32) * DM, 32 * DM * 2);
            if (p >= PF0 && p < PF0 + 9) {
              const int i = p - PF0, m = PFO ? 2 - i / 3 : i / 3;
              if (((PFM >> m) & 1) && !((PFM & 8) && m == 1 && b >= 32 && b < 96) && !(EB && m == 0 && b < 32))
              bulk_prefetch((m == 0 ? prm.wg : m == 1 ? prm.wu : prm.wd) + (size_t)(b * 3 + i % 3) * (DM * 12), DM * 24);
            }
          }
          __syncwarp();
          if ((TCH & 2) && (p & 7) == QPF && p < 24) {
#pragma unroll
            for (int i = 0; i < 4; i++) touch256(g_q + ((size_t)b * 4 + (p >> 3) + 1) * 2048 + (i * 32 + lane) * 16);
          }
          if ((TCH & 1) && p >= TF0 && p < TF0 + 9) {
            const int i = p - TF0, c0 = (b * 36) & ~7;
#pragma unroll
            for (int j = 0; j < (FAKEB ? 0 : 4); j++) {
              const int r = i * 64 + (j & 1) * 32 + lane;
              const bf16* q = ((j & 2) ? prm.wu : prm.wg) + (size_t)r * FF + c0;
              touch128(q);
              if ((c0 & 63) > 24) touch128(q + 38);
            }
            if (lane < 20) touch256(prm.wd + min(b * 162 + i * 20 + lane, 128 * 162 - 1) * 128);
          }
          if ((TCH & 16) && p >= TF0 && p < TF0 + 9 / TN) {
            const int i = (p - TF0) * TN, c0 = (b * 36) & ~7;
#pragma unroll
            for (int j = 0; j < TN; j++) {
              const bf16* q = prm.wu + (size_t)(144 + (i + j) * 32 + lane) * FF + c0;
              touch128(q);
              if ((c0 & 63) > 24) touch128(q + 38);
              if (lane < 20) touch256(prm.wd + min(b * 162 + (i + j) * 20 + lane, 128 * 162 - 1) * 128);
            }
          }
          if ((TCH & 4) && p >= FILLP - 3 && lane < 24) touch256(prm.x + (size_t)(qt * 128 + hg * 16) * DM + ((p - FILLP + 3) * 24 + lane) * 128);
          if ((TCH & 8) && p >= TW0 && p < TW0 + TWN) {
            const int i = (qt * TWN + p - TW0) * 144 % 2304;
#pragma unroll
            for (int j = 0; j < 5; j++)
              if (j < 4 || lane < 16) touch256(prm.wo + (size_t)(hcol + i / 576 * 256) * DM + (i % 576 + j * 32 + lane) * 128);
          }
          if (p >= FILL0)
#pragma unroll 1
          for (int z = 0; z < (FGAP ? FGN : 1); z++) {
            if (FGAP && z) __nanosleep(FGAP);
            const int i = lane >= 16 ? lane - 16 : (p - FILL0) * FILLN + lane + 5;
            if ((lane >= 16 ? p == FILLS && i < 5 : lane < FILLN && i < FILLMAX && i >= FILLMIN) && (!FGAP || (lane & (FGN - 1)) == z)) {
              uint4* const fp = g_ones + (i < 5 ? b * 640 : F_PART - 640 + b * PS) + i * 128;
              if (EF & 32) asm volatile("cp.async.bulk.global.shared::cta.bulk_group.L2::cache_hint [%0], [%1], 2048, %2;" ::"l"(fp), "r"(sb + SM_FILL), "l"(pol_first()) : "memory");
              else asm volatile("cp.async.bulk.global.shared::cta.bulk_group [%0], [%1], 2048;" ::"l"(fp), "r"(sb + SM_FILL) : "memory");
            }
          }
        }
        asm volatile("cp.async.bulk.commit_group;\ncp.async.bulk.wait_group 0;" ::: "memory");
        if (SIDEF & 2) asm volatile("fence.acq_rel.gpu;" ::: "memory");
        __syncwarp();
        PSTAMP(64, 51);
        if (lane == 0) {
          cnt_arrive(C_SIDE);
          PSTAMP(64, 52);
          cnt_wait(C_SIDE, 128 + 72);
          PSTAMP(64, 53);
          asm volatile("mbarrier.arrive.shared::cta.b64 _, [%0];" ::"r"(sBar + B_X) : "memory");
        }
        __syncwarp();
        if (KO && XL) bar_arrive(7, 64);
        if (lane == 0) {
          asm volatile("prefetch.tensormap [%0];\nprefetch.tensormap [%1];\nprefetch.tensormap [%2];\nprefetch.tensormap [%3];" ::"l"(&mWo), "l"(&mWg), "l"(&mWu), "l"(&mWd) : "memory");
          if (KO) asm volatile("prefetch.tensormap [%0];\nprefetch.tensormap [%1];" ::"l"(&mWo0), "l"(&mWo1) : "memory");
          if (!EM) mbar_wait(sBar + B_ST, 0);
          mbar_expect_tx(sBar + B_MD, 5760);
          bulk_load(sb + SM_MD, g_mod2, 4608, sBar + B_MD);
          bulk_load(sb + SM_MD + 4608, prm.w_r, 1152, sBar + B_MD);
        }
        __syncwarp();
        {
          mbar_wait(sBar + B_MD, 0);
          float sA = 0.f, sB = 0.f;
#pragma unroll 1
          for (int i = lane; i < 288; i += 32) {
            const uint4 m = lds128(sb + SM_MD + i * 16);
            const uint32_t w = *reinterpret_cast<const uint32_t*>(smem_raw + SM_MD + 4608 + i * 4);
            const float a0 = bf_lo(m.z) * bf_lo(w), a1 = bf_hi(m.z) * bf_hi(w);
            const uint32_t hi = pack_bf16(a0, a1);
            *reinterpret_cast<uint2*>(smem_raw + SM_MOD + i * 8) = make_uint2(pack_bf16(a0 - bf_lo(hi), a1 - bf_hi(hi)), hi);
            sA += a0 + a1;
            sB = fmaf(bf_lo(m.y), bf_lo(w), fmaf(bf_hi(m.y), bf_hi(w), sB));
          }
          sA = warp_sum(sA); sB = warp_sum(sB);
          *reinterpret_cast<float2*>(smem_raw + SM_ZERO + 16) = make_float2(sA, sB);
          __syncwarp();
          if (lane == 0) mbar_arrive(sBar + B_TB);
        }
        if (lane == 0) {
          if (EM) mbar_wait(sBar + B_ST, 0);
#pragma unroll 1
          for (int r = FS - 1, fb = EB ? 1 : 0; FS && fb < 6; r++, fb++) {
            mbar_pace(sBar + B_EMPTYO + (r & 1) * 16, (r >> 1) & 1);
            ffn_box(fb == 5 ? 7 : fb);
          }
#pragma unroll 1
          for (int r = 0, fb = EB ? 1 : 0; !FS && r < 4; r++) {
#pragma unroll 1
            for (const int fe = (FFNS >> (r * 4)) & 15; fb < fe; fb++) ffn_box(fb == 5 ? 7 : fb);
            if (r < 3) mbar_wait(sBar + B_EMPTYO + 16, r & 1);
          }
        }
        __syncwarp();
        const uint32_t* const tsu = reinterpret_cast<const uint32_t*>(smem_raw + SM_T);
        const int row = qt * 128 + hg * 16 + lane;
        auto out_row = [&]() {
          asm volatile("cp.async.bulk.global.shared::cta.bulk_group [%0], [%1], 1152;" ::"l"(prm.out + (size_t)row * DM), "r"(sb + SM_X2 + lane * 1168) : "memory");
        };
        bar_sync(11, 288);
        fence_async();
        const bool top = (*(volatile const uint32_t*)(tsu + 34) >> lane) & 1;
        if (lane < 16 && (FW == 2 || !top)) out_row();
        mbar_wait(sBar + B_G3, 0);
        if (FW != 2 && FW != 3 && top && row != (int)(~*(volatile const uint32_t*)(tsu + 32) & (SQ - 1)) && row != (int)(~*(volatile const uint32_t*)(tsu + 33) & (SQ - 1))) out_row();
        asm volatile("cp.async.bulk.commit_group;\ncp.async.bulk.wait_group.read 0;" ::: "memory");
      }
    }
  } else {
    const int cw = (warp >> 2) - 1;
    const int w8 = warp - 4;
    const int ct = tid - 128;
    const int lane = get_lane(), g = lane >> 2, t4 = lane & 3;
    uint32_t relBar;
    auto release = [&](int off) {
      if (lane < 2) mbar_arrive_cl(relBar + off);
    };
    auto release1 = [&](int off) {
      if (lane == 0) mbar_arrive_cl(relBar + off);
    };
    auto turn_begin = [&]() {
      asm volatile("{\n.reg .pred p;\nsetp.eq.b32 p, %0, 0;\n@p bar.sync 1, 288;\n@!p bar.sync 2, 256;\n}\n" ::"r"(cw) : "memory");
      wgmma_fence();
    };
    auto turn_end = [&]() { asm volatile("{\n.reg .pred p;\nsetp.eq.b32 p, %0, 0;\n@p bar.arrive 2, 256;\n@!p bar.arrive 1, 288;\n}\n" ::"r"(cw) : "memory"); };
    asm volatile("{\n.reg .pred p;\nsetp.eq.u64 p, %0, 0;\n@p trap;\n}\n" :: "l"(g_q) : "memory");
    ESC(7);
    asm volatile("setmaxnreg.inc.sync.aligned.u32 232;");
    float S[64], O[64];
    uint32_t P[32], Qf[32];
    constexpr uint32_t dB_k = mk_desc(SM_BASE, 16);
    constexpr uint32_t dB_n16 = mk_desc(SM_BASE, 16384);
    uint4* qpark;
    {
      uint32_t A[144];
      float qa[32];
      const bool hlp = b >= 128;
      uint32_t sel = 0x3210 + (~b & (b >> 7)) * 0x4444;
#pragma unroll 1
      for (int n = 0, xg = cw, gr = 2;;) {
        const uint32_t la = sb + xg * QG + (w8 & 2) * (QG / 4) + ((w8 & 1) * 16 + ((lane & 15) ^ (rank * 8))) * 128 + (((lane >> 4) ^ (lane & 7)) << 4);
        ESC(19);
        mbar_wait(sBar + B_X + xg * 8, ((n * 10 + cw) / 3) & 1);
        ESC(1);
        ln_rows(A, la, lane, [&]() { if (lane < 2) mbar_arrive(sBar + B_EMPTYQ + xg * 8); });
        ESC(2);
        asm volatile("pmevent 1;" ::: "memory");
        asm volatile("{\n.reg .pred p;\nsetp.eq.b32 p, %1, 0;\n@p bar.sync %0, 224;\n}\n" ::"r"(3 + cw), "r"(n) : "memory");
        ESC(3);
        modulate(A, sb + SM_MT + t4 * 16);
        ESC(4);
      asm volatile("mapa.shared::cluster.u32 %0, %1, %2;" : "=r"(relBar) : "r"(sBar), "r"(rank ^ (get_lane() & 1)));
      qpark = g_q + ((hlp ? (b - 128) * (8 * 8192) + 28 * 256 : b * 8192) + n * 16384 + w8 * 32 + get_lane());
      if (cw == 0) { mbar_wait(sBar + B_FULLQ + 16, 0); ESC(9); }
#pragma unroll 1
      for (int hh = 2 - (b >> 7) * 10;; hh++) {
        asm volatile("{\n.reg .pred p, q;\nsetp.eq.b32 p, %0, 0;\nsetp.ne.and.s32 q, %1, 2, p;\n@q bar.sync 1, 288;\n@!p bar.sync 2, 256;\n}\n" ::"r"(cw), "r"(hh) : "memory");
        wgmma_fence();
        q_mma(qa, A, dB_k + gr * (QG >> 4));
        turn_end();
        wgmma_wait<0>();
        if (hh < 6) release1(B_EMPTYQ + gr * 8);
        else if (hh < 9) { release(B_EMPTYA + gr * 16); release(B_EMPTYA + gr * 16 + 8); }
        if (++gr == 3) gr = 0;
        sel ^= (b >> 7) * 0x4444;
#pragma unroll
        for (int j = 0; j < 32; j++) qa[j] *= Q_SCALE;
#pragma unroll
        for (int j = 0; j < 4; j++) {
          const uint4 v = make_uint4(pack_bf16(qa[8 * j], qa[8 * j + 1]), pack_bf16(qa[8 * j + 2], qa[8 * j + 3]),
                                     pack_bf16(qa[8 * j + 4], qa[8 * j + 5]), pack_bf16(qa[8 * j + 6], qa[8 * j + 7]));
          qpark[((hh & 6) << (10 + (b >> 7) * 7)) + ((hh & 1) << (10 + (b >> 7) * 3)) + j * 256] =
              make_uint4(__byte_perm(v.x, v.y, sel), __byte_perm(v.y, v.x, sel), __byte_perm(v.z, v.w, sel), __byte_perm(v.w, v.z, sel));
        }
        if (hh == 9 - (b >> 7) * 10) break;
        if (hh == 6) hh++;
      }
      __syncwarp();
      if (__builtin_expect(n == (b >> 7) * 3, 1)) break;
      if (lane == 0) mbar_arrive(sBar + H_DONE + n * 8);
      n++;
      xg = gr + cw - (gr + cw == 3 ? 3 : 0);
      gr = gr ? gr - 1 : 2;
      }
      int b_;
      asm volatile("mov.u32 %0, %%ctaid.x;" : "=r"(b_));
      if (__builtin_expect(b_ >= 128, 0)) {
        if (lane == 0) mbar_arrive(sBar + H_DONE + 24);
        CL_WAIT();
      mbar_wait(sBar + H_GA, 0);
#pragma unroll 1
      for (int it = 0, n = 0, s = H0, j = cw; it < 4; it++) {
        uint32_t A[KO * 32];
        const int q = (b - 128) * 4 + it, lane = get_lane();
#pragma unroll
        for (int m = 0; m < 2; m++, n++) {
          mbar_wait(sBar + H_FULL + s * 8, (n / HN) & 1);
#pragma unroll
          for (int i = 0; i < 4 * KO; i++) {
            const uint4 v = lds128(sb + s * HS_ + i * 4096 + w8 * 512 + lane * 16);
            uint32_t* const a = A + (m * 4 * KO + i) * 4;
            if ((i / KO) & 1) { a[0] = v.y; a[1] = v.x; a[2] = v.w; a[3] = v.z; }
            else { a[0] = v.x; a[1] = v.y; a[2] = v.z; a[3] = v.w; }
          }
          if (__any_sync(~0u, A[(m + 1) * 16 * KO - 1] != 0x12345678u || A[m * 16 * KO] != 0x9abcdef0u || lane == 0) && lane == 0) mbar_arrive(sBar + H_EMPTY + s * 8);
          if (++s == HN) s = 0;
        }
        const int bb = (w8 >> 1) * 32 + q * 2 + (w8 & 1);
        uint4* op = g_q + bb * 8192 + lane;
#pragma unroll 1
        for (int c = 0; c < 9; c++, n++, j += 2) {
          float acc[32];
          uint32_t xr[4][4], ga[8];
          const int xg = j % 3;
          mbar_wait(sBar + H_XF + xg * 8, (j / 3) & 1);
#pragma unroll
          for (int i = 0; i < 4; i++) ldsm4(xr[i], sb + SM_HX + xg * 8192 + ((w8 & 3) * 16 + (lane & 15)) * 128 + (((i * 2 + (lane >> 4)) ^ (lane & 7)) << 4));
#pragma unroll
          for (int i = 0; i < 8; i++) asm volatile("ld.shared.b32 %0, [%1];" : "=r"(ga[i]) : "r"(sb + SM_GA + (c * 32 + i * 4 + (lane & 3)) * 16) : "memory");
          if (__any_sync(~0u, xr[0][0] != 0x12345678u || xr[3][3] != 0x9abcdef0u || lane == 0) && lane < 4) mbar_arrive(sBar + H_XE + xg * 8);
          turn_begin();
          const uint32_t db = mk_desc(SM_BASE, 16) + s * (HS_ >> 4);
#pragma unroll
          for (int k = 0; k < 8 * KO; k++) wgmma64_rs(acc, A[k * 4], A[k * 4 + 1], A[k * 4 + 2], A[k * 4 + 3], db + k * 128, k != 0);
          wgmma_commit();
          if (n + cw < 44) turn_end();
          wgmma_wait<0>();
          if (lane == 0) mbar_arrive(sBar + H_EMPTY + s * 8);
          if (++s == HN) s = 0;
#pragma unroll
          for (int i = 0; i < 4; i++) {
            uint32_t u[4];
#pragma unroll
            for (int k = 0; k < 4; k++)
              u[k] = pack_bf16(fmaf(bf_lo(ga[i * 2 + (k >> 1)]), acc[i * 8 + k * 2], bf_lo(xr[i][k])), fmaf(bf_hi(ga[i * 2 + (k >> 1)]), acc[i * 8 + k * 2 + 1], bf_hi(xr[i][k])));
            op[i * 32] = make_uint4(u[0], u[1], u[2], u[3]);
          }
          op += 128;
        }
        __syncwarp();
        if (lane == 0) mbar_arrive(sBar + H_DONE + 32 + it * 8);
      }
        return;
      }
#pragma unroll
      for (int j = 0; j < 4; j++) {
        const uint4 v = __ldcg(qpark + j * 256);
        Qf[4 * j] = v.x; Qf[4 * j + 1] = v.y; Qf[4 * j + 2] = v.z; Qf[4 * j + 3] = v.w;
      }
#pragma unroll
      for (int j = 0; j < 16; j++) Qf[16 + j] = pack_bf16(qa[2 * j], qa[2 * j + 1]);
    }
    STAMP(5); GSTAMP(65); STAMP(0); GSTAMP(90);
    float mb0 = 0.f, mb1 = 0.f, l0 = 0.f, l1 = 0.f;
    int nz = 0;
    float i0 = 0.f, i1 = 0.f;
    auto o_scale = [&]() {
      float a0 = l0, a1 = l1;
      a0 += __shfl_xor_sync(~0u, a0, 1); a0 += __shfl_xor_sync(~0u, a0, 2);
      a1 += __shfl_xor_sync(~0u, a1, 1); a1 += __shfl_xor_sync(~0u, a1, 2);
      i0 = rcp(a0); i1 = rcp(a1);
    };
    auto o_frag = [&](int i) {
      return make_uint4(pack_bf16(O[i * 8] * i0, O[i * 8 + 1] * i0), pack_bf16(O[i * 8 + 2] * i1, O[i * 8 + 3] * i1),
                        pack_bf16(O[i * 8 + 4] * i0, O[i * 8 + 5] * i0), pack_bf16(O[i * 8 + 6] * i1, O[i * 8 + 7] * i1));
    };
    auto row_max = [&](float& x0, float& x1) {
      float y0 = fmaxf(S[0], S[1]), y1 = fmaxf(S[2], S[3]), z0 = fmaxf(S[4], S[5]), z1 = fmaxf(S[6], S[7]);
#pragma unroll
      for (int j = 2; j < 16; j += 2) {
        y0 = fmaxf(y0, fmaxf(S[j * 4], S[j * 4 + 1])); y1 = fmaxf(y1, fmaxf(S[j * 4 + 2], S[j * 4 + 3]));
        z0 = fmaxf(z0, fmaxf(S[j * 4 + 4], S[j * 4 + 5])); z1 = fmaxf(z1, fmaxf(S[j * 4 + 6], S[j * 4 + 7]));
      }
      x0 = fmaxf(y0, z0); x1 = fmaxf(y1, z1);
      x0 = fmaxf(x0, __shfl_xor_sync(~0u, x0, 1)); x1 = fmaxf(x1, __shfl_xor_sync(~0u, x1, 1));
      x0 = fmaxf(x0, __shfl_xor_sync(~0u, x0, 2)); x1 = fmaxf(x1, __shfl_xor_sync(~0u, x1, 2));
    };
    float s0, s1;
    auto shift = [&]() {
#pragma unroll
      for (int i = 0; i < 64; i++) S[i] -= (i & 2) ? mb1 : mb0;
    };
    auto exps = [&](int j0, int j1) {
#pragma unroll
      for (int j = j0; j < j1; j++) {
        S[j * 4] = ex2(S[j * 4]); S[j * 4 + 1] = ex2(S[j * 4 + 1]);
        S[j * 4 + 2] = ex2(S[j * 4 + 2]); S[j * 4 + 3] = ex2(S[j * 4 + 3]);
        if (HS == 0 || (HS == 2 && j < 8)) { s0 += S[j * 4] + S[j * 4 + 1]; s1 += S[j * 4 + 2] + S[j * 4 + 3]; }
      }
    };
    auto cvtP = [&]() {
#pragma unroll
      for (int i = 0; i < 32; i++) {
        if (HS & 1) asm volatile("cvt.rn.bf16x2.f32 %0, %1, %2;" : "=r"(P[i]) : "f"(S[2 * i + 1]), "f"(S[2 * i]));
        else P[i] = pack_bf16(S[2 * i], S[2 * i + 1]);
      }
      if (HS) {
        uint32_t t[16];
#pragma unroll
        for (int i = 0; i < 16; i++) t[i] = hadd2(P[(i >> 1) * 4 + (i & 1)], P[(i >> 1) * 4 + (i & 1) + 2]);
#pragma unroll
        for (int i = 0; i < 8; i++) t[i] = hadd2(t[(i >> 1) * 4 + (i & 1)], t[(i >> 1) * 4 + (i & 1) + 2]);
#pragma unroll
        for (int i = 0; i < 4; i++) t[i] = hadd2(t[(i >> 1) * 4 + (i & 1)], t[(i >> 1) * 4 + (i & 1) + 2]);
        if (HS == 1) {
          t[0] = hadd2(t[0], t[2]); t[1] = hadd2(t[1], t[3]);
          s0 = bf_lo(t[0]) + bf_hi(t[0]); s1 = bf_lo(t[1]) + bf_hi(t[1]);
        } else if (HS == 2) {
          s0 += bf_lo(t[2]) + bf_hi(t[2]); s1 += bf_lo(t[3]) + bf_hi(t[3]);
        } else {
          s0 = (bf_lo(t[0]) + bf_hi(t[0])) + (bf_lo(t[2]) + bf_hi(t[2])); s1 = (bf_lo(t[1]) + bf_hi(t[1])) + (bf_lo(t[3]) + bf_hi(t[3]));
        }
      }
    };
    auto issue_qk = [&](uint32_t db) {
#pragma unroll
      for (int kk = 0; kk < 8; kk++)
        wgmma128_rs<0>(S, Qf[kk * 4], Qf[kk * 4 + 1], Qf[kk * 4 + 2], Qf[kk * 4 + 3], db + (kk >> 2) * 1024 + (kk & 3) * 2, kk != 0);
    };
    auto issue_pv = [&](uint32_t db, int first) {
#pragma unroll
      for (int kk = 0; kk < 8; kk++) {
        if (kk == TE_POS) turn_end();
        wgmma128_rs<1>(O, P[kk * 4], P[kk * 4 + 1], P[kk * 4 + 2], P[kk * 4 + 3], db + kk * 128, kk ? 1 : !first);
      }
      wgmma_commit();
      if (TE_POS == 8) turn_end();
    };
    auto sched_fence = [&]() {
      if (HS & 1) asm volatile("st.shared.v2.f32 [%0], {%1,%2};" ::"r"(sb + SM_RED), "f"(S[EH * 4 - 2]), "f"(S[EH * 4 - 1]) : "memory");
      else asm volatile("st.shared.v2.f32 [%0], {%1,%2};" ::"r"(sb + SM_RED), "f"(s0), "f"(s1) : "memory");
    };
    {
      STAMP(6);
      turn_begin();
      issue_qk(dB_k);
      wgmma_commit();
      turn_end();
      CL_WAIT();
      wgmma_wait<0>();
      release(B_EMPTYA);
      bool redo = sb >> 31;
#pragma unroll 1
      do {
        if (__builtin_expect(redo, 0)) {
          row_max(mb0, mb1);
          shift();
          nz = 1;
        }
        l0 = 0.f; l1 = 0.f;
#pragma unroll
        for (int i = 0; i < 32; i++) {
          const float e0 = ex2(S[2 * i]), e1 = ex2(S[2 * i + 1]);
          P[i] = pack_bf16(e0, e1);
          if (i & 1) l1 += e0 + e1; else l0 += e0 + e1;
        }
        redo = __any_sync(~0u, !(l0 <= LAZY_LIMIT && l1 <= LAZY_LIMIT && l0 >= LAZY_LOW && l1 >= LAZY_LOW)) && !redo;
      } while (__builtin_expect(redo, 0));
    }
    const uint4* qn = qpark + 8 * 256;
    if (!QL) asm volatile("" : "+l"(qn));
    uint32_t kd = dB_k + 4096;
#pragma unroll 1
    for (int t = 1; t < 64; t++, kd ^= 4096) {
      const int j = t & 15, h = t >> 4;
      const int ks = (t & 1) * 2, vs = 3 - ks;
      turn_begin();
      issue_qk(kd);
      wgmma_commit();
      if (__builtin_expect(j == 1 && h > XS, 0)) {
#pragma unroll
        for (int i = RS0; i < 8; i++) sts128(sb + SM_STASH + (h - 1) * 32768 + i * 4096 + ct * 16, o_frag(i));
        wgmma_fence();
      }
      if (cw == 0) bar_sync(10, 160);
      issue_pv(kd ^ (dB_k ^ (dB_n16 + 6144)), j == 1);
      wgmma_wait<1>();
      release(B_EMPTYA + ks * 8);
      if (j == 15 && h < 3 - XQ) {
#pragma unroll
        for (int i = 0; i < 8; i++) {
          uint4 v;
          if (QL) v = lds128(sb + SM_STASH + h * 32768 + i * 4096 + ct * 16);
          else if (EF & 4) asm volatile("ld.global.cg.L2::cache_hint.v4.u32 {%0,%1,%2,%3}, [%4], %5;" : "=r"(v.x), "=r"(v.y), "=r"(v.z), "=r"(v.w) : "l"(qn + i * 256), "l"(pol_first()));
          else v = __ldcg(qn + i * 256);
          Qf[4 * i] = v.x; Qf[4 * i + 1] = v.y; Qf[4 * i + 2] = v.z; Qf[4 * i + 3] = v.w;
        }
        qn += 8 * 256;
      }
      auto dummy = [&]() {
        if (__builtin_expect(t == 4 || t == 8, 0)) {
#pragma unroll
          for (int i = 0; i < 8; i++) sts128(sb + SM_STASH + 65536 + i * 4096 + ct * 16, make_uint4(Qf[4 * i], Qf[4 * i + 1], Qf[4 * i + 2], Qf[4 * i + 3]));
        }
      };
      if (DMY == 1) dummy();
      if (__builtin_expect(nz, 0)) shift();
      s0 = 0.f; s1 = 0.f;
      exps(0, EH);
      sched_fence();
      wgmma_wait<0>();
      release(B_EMPTYA + vs * 8);
      if (DMY == 2) dummy();
      float lo = 0.f;
      if (__builtin_expect(j == 0, 0)) {
        o_scale();
        l0 = 0.f; l1 = 0.f;
        lo = LAZY_LOW;
      }
#if !(HS & 1)
      bool bad = __any_sync(~0u, !(s0 <= LAZY_LIMIT && s1 <= LAZY_LIMIT));
#endif
      if (__builtin_expect(!bad, 1)) {
        exps(EH, 16);
        cvtP();
        bad = __any_sync(~0u, !(s0 <= LAZY_LIMIT && s1 <= LAZY_LIMIT && s0 >= lo && s1 >= lo));
      }
      if (__builtin_expect(bad, 0)) {
        const uint32_t* kp = reinterpret_cast<const uint32_t*>(prm.k + ((size_t)kg * 4 * SK + t * 128 + g) * DH) + t4;
        const uint4* qp = qpark + h * (8 * 256);
        float4 tmp[16];
        uint4 qf[8];
#pragma unroll
        for (int kk = 0; kk < 8; kk++) qf[kk] = h < 3 ? __ldcg(qp + kk * 256) : make_uint4(Qf[4 * kk], Qf[4 * kk + 1], Qf[4 * kk + 2], Qf[4 * kk + 3]);
        float x0 = __uint_as_float(0xff800000u), x1 = x0;
#pragma unroll 1
        for (int jn = 0; jn < 16; jn++) {
          float c[4] = {0.f, 0.f, 0.f, 0.f};
#pragma unroll
          for (int kk = 0; kk < 8; kk++) mma16816(c, qf[kk].x, qf[kk].y, qf[kk].z, qf[kk].w, __ldg(kp + jn * 512 + kk * 8), __ldg(kp + jn * 512 + kk * 8 + 4));
          tmp[jn] = make_float4(c[0], c[1], c[2], c[3]);
          x0 = fmaxf(x0, fmaxf(c[0], c[1])); x1 = fmaxf(x1, fmaxf(c[2], c[3]));
        }
        x0 = fmaxf(x0, __shfl_xor_sync(~0u, x0, 1)); x1 = fmaxf(x1, __shfl_xor_sync(~0u, x1, 1));
        x0 = fmaxf(x0, __shfl_xor_sync(~0u, x0, 2)); x1 = fmaxf(x1, __shfl_xor_sync(~0u, x1, 2));
        const float n0 = j ? fmaxf(mb0, x0) : x0, n1 = j ? fmaxf(mb1, x1) : x1;
        const float f0 = j ? ex2(mb0 - n0) : 1.f, f1 = j ? ex2(mb1 - n1) : 1.f;
        mb0 = n0; mb1 = n1;
        l0 *= f0; l1 *= f1;
#pragma unroll
        for (int i = 0; i < 16; i++) { O[i * 4] *= f0; O[i * 4 + 1] *= f0; O[i * 4 + 2] *= f1; O[i * 4 + 3] *= f1; }
        s0 = 0.f; s1 = 0.f;
        nz = 1;
#pragma unroll 1
        for (int jn = 0; jn < 16; jn++) {
          const float4 c = tmp[jn];
          const float e0 = ex2(c.x - n0), e1 = ex2(c.y - n0), e2 = ex2(c.z - n1), e3 = ex2(c.w - n1);
          s0 += e0 + e1; s1 += e2 + e3;
          reinterpret_cast<float2*>(tmp)[jn] = make_float2(__uint_as_float(pack_bf16(e0, e1)), __uint_as_float(pack_bf16(e2, e3)));
        }
#pragma unroll
        for (int i = 0; i < 8; i++) {
          const float4 c = tmp[i];
          P[i * 4] = __float_as_uint(c.x); P[i * 4 + 1] = __float_as_uint(c.y); P[i * 4 + 2] = __float_as_uint(c.z); P[i * 4 + 3] = __float_as_uint(c.w);
        }
      }
      if (RS0 && __builtin_expect(j == 0, 0)) {
#pragma unroll
        for (int i = 0; i < RS0; i++) sts128(sb + SM_STASH + (h - 1) * 32768 + i * 4096 + ct * 16, o_frag(i));
      }
      if (DMY == 3) dummy();
      l0 += s0; l1 += s1;
    }
    STAMP(70); GSTAMP(66);
    int nc = 0;
    uint32_t ra[7], rb[7], ld[16];
    const uint32_t* const ap = reinterpret_cast<const uint32_t*>(g_ones + F_PART) + (qt * 8 + hg) * (PS * 4) + w8 * 32 + get_lane();
    auto ld_sum = [&](uint32_t& a, uint32_t& c, const uint32_t* w) {
      a = pack_bf16((bf_lo(w[0]) + bf_lo(w[2])) + (bf_lo(w[4]) + bf_lo(w[6])), (bf_hi(w[0]) + bf_hi(w[2])) + (bf_hi(w[4]) + bf_hi(w[6])));
      c = pack_bf16((bf_lo(w[1]) + bf_lo(w[3])) + (bf_lo(w[5]) + bf_lo(w[7])), (bf_hi(w[1]) + bf_hi(w[3])) + (bf_hi(w[5]) + bf_hi(w[7])));
    };
    {
      const int lane = get_lane();
      uint32_t A[128];
      float c0[32], kp[16];
      auto ld_a = [&](int i0, int i1) {
#pragma unroll
        for (int i = i0 < KO ? KO : i0; i < i1; i++) {
          const uint4 v = lds128(sb + SM_STASH + i * 4096 + ct * 16);
          A[i * 4] = v.x; A[i * 4 + 1] = v.y; A[i * 4 + 2] = v.z; A[i * 4 + 3] = v.w;
        }
      };
      ld_a(MG == 2 ? 8 : 0, MGL);
      if (OSP == 1) { o_scale(); asm volatile("st.shared.v2.f32 [%0], {%1,%2};" ::"r"(sb + SM_RED), "f"(i0), "f"(i1) : "memory"); }
      turn_begin();
#pragma unroll
      for (int kk = 0; kk < 8; kk++) wgmma128_rs<1>(O, P[kk * 4], P[kk * 4 + 1], P[kk * 4 + 2], P[kk * 4 + 3], dB_n16 + 6144 + kk * 128, 1);
      wgmma_commit();
      ld_a(MG == 2 && MGL < 8 ? 8 : MGL, 16);
      if (cw == 0) bar_sync(10, 160);
      wgmma_fence();
#pragma unroll
      for (int kk = KO; kk < 16; kk++) {
        wgmma64_rs(c0, A[kk * 4], A[kk * 4 + 1], A[kk * 4 + 2], A[kk * 4 + 3], dB_k + kk * 128, kk != KO);
        if (ER > 1 && kk == ER) { wgmma_commit(); wgmma_wait<1>(); release(B_EMPTYA + 24); }
      }
      wgmma_commit();
      turn_end();
      if (OSP == 2) {
        float z;
        asm volatile("ld.shared.f32 %0, [%1];" : "=f"(z) : "r"(sb + SM_ZERO) : "memory");
        l0 += z; l1 += z;
      }
      if (OSP != 1) o_scale();
      if (ER < 2) wgmma_wait<1>();
      if (ER == 1) release(B_EMPTYA + 24);
#pragma unroll
      for (int i = 16; i < 24; i++) {
        const uint4 v = lds128(sb + SM_STASH + i * 4096 + ct * 16);
        A[i * 4] = v.x; A[i * 4 + 1] = v.y; A[i * 4 + 2] = v.z; A[i * 4 + 3] = v.w;
      }
#pragma unroll
      for (int i = 0; i < 8; i++) {
        const uint4 v = o_frag(i);
        A[96 + i * 4] = v.x; A[96 + i * 4 + 1] = v.y; A[96 + i * 4 + 2] = v.z; A[96 + i * 4 + 3] = v.w;
      }
      if (__any_sync(~0u, A[95] != 0x12345678u || A[64] != 0x9abcdef0u || lane == 0)) {
        release(B_EMPTYA + (ER ? 0 : 24));
        release1(B_ST);
      }
      STAMP(71);
      uint32_t xb = w8 * 1024 + lane * 16;
      const uint32_t peer = __shfl_sync(~0u, relBar, 1) - sBar;
      int gr = MG ? 2 : 0;
      wgmma_wait<0>();
      release1(B_EMPTYO);
#pragma unroll
      for (int i = 0; i < 8; i++) ld[i] = ~0u;
#pragma unroll
      for (int i = 0; i < 5; i++) ra[i] = rb[i] = 0;
      auto ld_take = [&]() {
        uint32_t a, d;
        ld_sum(a, d, ld);
#pragma unroll
        for (int i = 0; i < 5; i++)
          if (nc == i) { ra[i] = a; rb[i] = d; }
        nc += !__any_sync(~0u, nan2(hadd2(a, d)));
      };
      uint32_t* dp = reinterpret_cast<uint32_t*>(g_ones + F_PART) + (qt * 8 + w8) * (PS * 4) + kg * 512 + rank * 256 + lane;
      auto recv = [&]() {
        uint4 u[2];
#pragma unroll
        for (int j = 0; j < 2; j++) u[j] = lds128(sb + SM_XCH + xb + j * 512);
#pragma unroll
        for (int j = 0; j < 2; j++) {
          str1(dp + j * 128, pack_bf16(kp[j * 8] + bf_lo(u[j].x), kp[j * 8 + 1] + bf_hi(u[j].x)));
          str1(dp + j * 128 + 32, pack_bf16(kp[j * 8 + 2] + bf_lo(u[j].y), kp[j * 8 + 3] + bf_hi(u[j].y)));
          str1(dp + j * 128 + 64, pack_bf16(kp[j * 8 + 4] + bf_lo(u[j].z), kp[j * 8 + 5] + bf_hi(u[j].z)));
          str1(dp + j * 128 + 96, pack_bf16(kp[j * 8 + 6] + bf_lo(u[j].w), kp[j * 8 + 7] + bf_hi(u[j].w)));
        }
        dp += 2048;
        xb ^= 8192;
      };
#pragma unroll 1
      for (int c = 0;; c++) {
#pragma unroll
        for (int hd = 1; hd < 4; hd += 2) {
          if (MG && hd < 2 && c == 0) continue;
          if (XG == 4 && hd == 3) {
            asm volatile("{\n.reg .pred p;\nsetp.eq.b32 p, %0, 0;\n@p bar.sync 1, 288;\n@!p bar.sync 2, 288;\n}\n" ::"r"(cw) : "memory");
            wgmma_fence();
          } else turn_begin();
          const uint32_t db = dB_k + gr * 1024;
#pragma unroll
          for (int kk = hd == 3 ? 0 : KO; kk < 16; kk++) {
            const uint32_t* const a = A + (hd - 1) * 32 + kk * 4;
            wgmma64_rs(c0, a[0], a[1], a[2], a[3], db + kk * 128, hd == 3 || kk != KO);
          }
          if (hd & 1) {
            wgmma_commit();
            if (XG == 4 && hd == 3) { if (c < 8 || cw == 0) asm volatile("{\n.reg .pred p;\nsetp.eq.b32 p, %0, 0;\n@p bar.arrive 2, 288;\n@!p bar.arrive 1, 288;\n}\n" ::"r"(cw) : "memory"); }
            else if (hd == 1 || c < 8 || cw == 0) turn_end();
            if (hd == 1 ? c == 8 : (c & 7) != 0) {
              if (hd == 1) mbar_wait(sBar + B_XF + 8 - (XG == 4) * cw * 16, 1);
              else if (XG == 2) mbar_wait(sBar + B_XF + (~c & 1) * 8, ((c - 1) >> 1) & 1);
              recv();
            }
            if (hd == 1 && c >= 3 && c < 8) {
              ld_take();
#pragma unroll
              for (int i = 0; i < 8; i++) ld[i] = ldr1(ap + nc * 2048 + i * 256);
            }
            if (hd == HINTH && c == 8 && cw == HINTW) bar_arrive(8, 160);
            if (hd == 3 && c == 8) {
              ld_take();
#pragma unroll
              for (int i = 0; i < 16; i++) ld[i] = ldr1(ap + 5 * 2048 + i * 256);
            }
            wgmma_wait<0>();
            release1(B_EMPTYO + gr * 4);
            gr = (gr + 2) & 7;
          }
        }
        if (c == 8) break;
        if (c == 0) mbar_wait(sBar + B_EMPTYA + (ER ? 0 : 24), ER != 0);
#pragma unroll
        for (int j = 0; j < 2; j++)
          asm volatile("st.async.shared::cluster.mbarrier::complete_tx::bytes.v4.b32 [%0], {%1,%2,%3,%4}, [%5];" ::"r"(sb + SM_XCH + xb + peer + j * 512),
                       "r"(pack_bf16(c0[j * 16 + 2], c0[j * 16 + 3])), "r"(pack_bf16(c0[j * 16 + 6], c0[j * 16 + 7])), "r"(pack_bf16(c0[j * 16 + 10], c0[j * 16 + 11])),
                       "r"(pack_bf16(c0[j * 16 + 14], c0[j * 16 + 15])), "r"(sBar + B_XF + (c & 1) * 8 + peer - (XG == 4) * cw * 16) : "memory");
#pragma unroll
        for (int j = 0; j < 16; j++) kp[j] = c0[(j >> 1) * 4 + (j & 1)];
      }
      STAMP(72); GSTAMP(67);
      uint2* const dst = reinterpret_cast<uint2*>(g_ones + F_PART) + ((qt * 8 + w8) * (PS / 128) + 32 + rank * 4 + kg) * 256 + lane;
#pragma unroll
      for (int jb = 0; jb < 8; jb++)
        asm volatile("st.relaxed.gpu.global.v2.u32 [%0], {%1,%2};" ::"l"(dst + jb * 32), "r"(pack_bf16(c0[jb * 4], c0[jb * 4 + 1])), "r"(pack_bf16(c0[jb * 4 + 2], c0[jb * 4 + 3])) : "memory");
    }
    STAMP(73);
    {
    const int lane = get_lane(), g = lane >> 2, t4 = lane & 3;
    uint32_t* const tsu = reinterpret_cast<uint32_t*>(smem_raw + SM_T);
    float* const tsf = reinterpret_cast<float*>(smem_raw + SM_T);
    const int row0 = qt * 128 + hg * 16;
    const int kq = w8 >> 1;
    uint32_t bg[9][10], bd[9][5];
    auto ld_bg = [&](int k0, int k1) {
      if (k0 == 0) mbar_wait(sBar + B_FFN, 0);
      const uint32_t wa = sb + (w8 == 3 || w8 == 5 ? -11520 : (w8 & 1) ? SM_WG + 46080 : EB && w8 == 0 ? SM_STASH : SM_WG) + (kq * 144 + (lane & 15)) * 80 + (lane >> 4) * 16;
#pragma unroll
      for (int ks = k0; ks < k1; ks++) {
        uint32_t b0[4], b1[4], b2[2];
        ldsm4t(b0, wa + ks * 1280); ldsm4t(b1, wa + ks * 1280 + 32); ldsm2t(b2, wa + ks * 1280 + 64 - (lane >> 4) * 16);
#pragma unroll
        for (int i = 0; i < 4; i++) { bg[ks][i] = b0[i]; bg[ks][4 + i] = b1[i]; }
        bg[ks][8] = b2[0]; bg[ks][9] = b2[1];
      }
    };
    uint32_t xs[9], *xp;
    auto st_x = [&]() {
#pragma unroll
      for (int i = 0; i < 9; i++)
        if (xp) str1(xp + i * 32, xs[i]);
    };
    {
      uint32_t xa[9], xb[9], wb[9];
      uint4 md[9];
      float av[2][4];
      uint2 pv[12];
      const uint32_t ident = (g >> 1) == t4 ? 0x3f80u << ((g & 1) * 16) : 0u;
      auto ld_late = [&]() {
        bool bad = false;
#pragma unroll
        for (int s = 0; s < 12; s++)
          if (pv[s].x == ~0u || pv[s].y == ~0u) {
            bad = true;
            if (s < 4) { pv[s].x = ldr1(ap + (28 + s) * 512); pv[s].y = ldr1(ap + (28 + s) * 512 + 256); }
            else pv[s] = ldr2(ap + (28 + s) * 512 + w8 * 32 + lane);
          }
        return bad;
      };
#pragma unroll
      for (int s = 0; s < 12; s++) pv[s] = make_uint2(~0u, ~0u);
      uint32_t* const tr = reinterpret_cast<uint32_t*>(smem_raw + SM_X2) + g * 292 + w8 * 4 + t4;
      float sx[4] = {0.f, 0.f, 0.f, 0.f}, qa[4] = {0.f, 0.f, 0.f, 0.f}, qb[4] = {0.f, 0.f, 0.f, 0.f};
      auto stat = [&](int i, uint32_t a, uint32_t c) {
        xa[i] = hfma2(md[i].x, a, xa[i]);
        xb[i] = hfma2(md[i].x, c, xb[i]);
        mma1688(sx, xa[i], xb[i], wb[i]);
        mma1688(qa, xa[i], xb[i], xa[i]);
        mma1688(qb, xa[i], xb[i], xb[i]);
      };
      mbar_wait(sBar + B_TB, 0);
#pragma unroll
      for (int i = 0; i < 9; i++) {
        md[i] = lds128(sb + SM_MD + (i * 32 + w8 * 4 + t4) * 16);
        const uint32_t w = *reinterpret_cast<const uint32_t*>(smem_raw + SM_MOD + (i * 32 + w8 * 4 + t4) * 8 + (g & 1) * 4);
        wb[i] = g == 0 ? 0x3f803f80u : g < 3 ? w : 0u;
      }
      mbar_wait(sBar + B_XR, 0);
#pragma unroll
      for (int i = 0; i < 9; i++) {
        if (KO) asm volatile("ld.shared.v2.b32 {%0,%1}, [%2];" : "=r"(xa[i]), "=r"(xb[i]) : "r"(sb + SM_X2 + (i * 4 + (w8 >> 1)) * 512 + lane * 16 + (w8 & 1) * 8) : "memory");
        else { xa[i] = tr[i * 32]; xb[i] = tr[8 * 292 + i * 32]; }
      }
      mbar_wait(sBar + B_EMPTYO, 0);
      STAMP(74);
      {
        uint32_t need = 0x7fu & (~0u << nc);
        int c1 = 5, c2 = 6;
        ra[5] = rb[5] = ra[6] = rb[6] = 0;
#pragma unroll 1
        for (uint32_t n = 0;; n++) {
          uint32_t a1, d1, a2, d2;
          ld_sum(a1, d1, ld);
          ld_sum(a2, d2, ld + 8);
#pragma unroll
          for (int i = 0; i < 7; i++) {
            if (c1 == i) { ra[i] = a1; rb[i] = d1; }
            if (c2 == i) { ra[i] = a2; rb[i] = d2; }
          }
          auto max8 = [](const uint32_t* w) { return __vimax3_u32(__vimax3_u32(w[0], w[1], w[2]), __vimax3_u32(w[3], w[4], w[5]), max(w[6], w[7])); };
          if (!__any_sync(~0u, max8(ld) == ~0u)) need &= ~(1u << c1);
          if (!__any_sync(~0u, max8(ld + 8) == ~0u)) need &= ~(1u << c2);
          if (__builtin_expect(!need || n > (1u << 15), 1)) break;
          c1 = __ffs(need) - 1;
          c2 = 31 - __clz(need);
          if (FX == 2 && (need & (need - 1))) c2 = __ffs(need & (need - 1)) - 1;
#pragma unroll
          for (int i = 0; i < 8; i++) { ld[i] = ldr1(ap + c1 * 2048 + i * 256); ld[8 + i] = ldr1(ap + c2 * 2048 + i * 256); }
        }
      }
      STAMP(69);
      mbar_wait(sBar + B_G2, 0);
      STAMP(48);
#pragma unroll 1
      for (uint32_t n = 0;; n++) {
        const bool bad = ld_late();
        if (!__any_sync(~0u, bad) || n > (1u << 15)) break;
        if (n == 0) {
#pragma unroll
          for (int i = 0; i < 7; i++) stat(i, ra[i], rb[i]);
          if (BGE) ld_bg(0, BGE);
        }
      }
      STAMP(77);
      if (lane == 0) mbar_arrive(sBar + B_G1);
#pragma unroll
      for (int i = 0; i < 8; i++) av[i >> 2][i & 3] = 0.f;
#pragma unroll
      for (int s = 0; s < 4; s++) {
        if (s & 1) mma16816(av[0], pv[s - 1].x, pv[s - 1].y, pv[s].x, pv[s].y, ident, ident);
        mma16816(av[1], pv[4 + s].x, pv[4 + s].y, pv[8 + s].y, pv[8 + s].x, ident, ident);
      }
#pragma unroll
      for (int i = 0; i < 2; i++) stat(7 + i, pack_bf16(av[i][0], av[i][1]), pack_bf16(av[i][2], av[i][3]));
      STAMP(40);
      float* const ps = reinterpret_cast<float*>(smem_raw + SM_PS);
      if (t4 < 2) {
        *reinterpret_cast<float2*>(ps + w8 * 32 + g * 4 + t4 * 2) = make_float2(sx[0], sx[1]);
        *reinterpret_cast<float2*>(ps + 256 + w8 * 32 + g * 4 + t4 * 2) = make_float2(sx[2], sx[3]);
      }
      if (ident) {
        ps[512 + w8 * 32 + g] = (g & 1) ? qa[1] : qa[0];
        ps[512 + w8 * 32 + g + 8] = (g & 1) ? qb[3] : qb[2];
      }
      bar_sync(5, 256);
      STAMP(44);
      float mean = 0.f, dot = 0.f, m2 = 0.f;
#pragma unroll
      for (int i = 0; i < 4; i++) {
        const float4 q = *reinterpret_cast<const float4*>(ps + (lane & 8) * 32 + (lane & 16) * 8 + i * 32 + (lane & 7) * 4);
        mean += q.x; dot += q.y + q.z; m2 += ps[512 + (lane & 16) * 8 + i * 32 + (lane & 15)];
      }
      const float2 sab = *reinterpret_cast<const float2*>(smem_raw + SM_ZERO + 16);
      mean += __shfl_xor_sync(~0u, mean, 16);
      dot += __shfl_xor_sync(~0u, dot, 16);
      m2 += __shfl_xor_sync(~0u, m2, 16);
      mean *= 1.f / DM;
      const float rs = rcp(bfr(sqrt_a(bfr(bfr(fmaxf(fmaf(m2, 1.f / DM, -mean * mean), 0.f)) + 1e-5f))));
      const uint32_t nm = pack_bf16(-mean, -mean);
      uint32_t u = pack_bf16(0.f, fmaf(rs, fmaf(bf_lo(nm), sab.x, dot), sab.y));
      u = ((u & 0x7fff0000u) > 0x7f800000u) ? 0u : (u ^ ((u >> 31) ? 0xffff0000u : 0x80000000u));
      u |= 0xffffu - (row0 + (lane & 15));
      const uint32_t m1 = __reduce_max_sync(~0u, u), m2k = __reduce_max_sync(~0u, u == m1 ? 0u : u);
      if (w8 == 7) asm volatile("st.relaxed.gpu.global.v2.u32 [%0], {%1,%2};" ::"l"(reinterpret_cast<uint2*>(g_ones + F_KEY) + lane * 128 + b), "r"(~m1), "r"(~m2k) : "memory");
      STAMP(41);
      const int r1 = ~m1 & 15, r2 = ~m2k & 15;
      const uint32_t r2t = pack_bf16(rs, rs - bfr(rs));
      const uint32_t rA = __shfl_sync(~0u, r2t, g), rB = __shfl_sync(~0u, r2t, g + 8);
      const uint32_t nmA = __shfl_sync(~0u, nm, g), nmB = __shfl_sync(~0u, nm, g + 8);
      const uint32_t hA = __byte_perm(rA, 0, 0x1010), lA = __byte_perm(rA, 0, 0x3232), hB = __byte_perm(rB, 0, 0x1010), lB = __byte_perm(rB, 0, 0x3232);
      uint32_t* const hx = reinterpret_cast<uint32_t*>(g_ones + F_HX + b * 288) + w8 * 4 + t4;
      const bool topA = g == r1 || g == r2, topB = g + 8 == r1 || g + 8 == r2;
      uint32_t* const pA = hx + (g == r2 ? 576 : 0);
      uint32_t* const pB = hx + (g + 8 == r2 ? 576 : 0);
      uint32_t* const pS = topA ? pA : pB;
#pragma unroll
      for (int i = 0; i < 9; i++) {
        const uint32_t da = hadd2(xa[i], nmA), db = hadd2(xb[i], nmB);
        const uint32_t ha = hfma2(hfma2(da, hA, hmul2(da, lA)), md[i].z, md[i].y), hb = hfma2(hfma2(db, hB, hmul2(db, lB)), md[i].z, md[i].y);
        if (topA || topB) str1(pS + i * 32, topA ? ha : hb);
        tr[i * 32] = hfma2(md[i].w, ha, xa[i]);
        tr[8 * 292 + i * 32] = hfma2(md[i].w, hb, xb[i]);
        md[i].x = hb;
        xs[i] = topA ? xa[i] : xb[i];
      }
      if (__builtin_expect((r1 ^ r2) == 8, 0) && topB) {
#pragma unroll
        for (int i = 0; i < 9; i++) { str1(pB + i * 32, md[i].x); str1(pB + 288 + i * 32, xb[i]); }
      }
      __syncwarp();
      xp = topA || topB ? pS + 288 : nullptr;
      if (HX == 2) st_x();
      if (FW == 4) { if (tid == 128) *reinterpret_cast<uint2*>(tsu + 34) = make_uint2(m1, m2k); }
      else if (tid == 128) tsu[34] = (1u << r1) | (1u << r2);
      bar_arrive(11, 288);
    }
    STAMP(75);
    ld_bg(BGE, 9);
    mbar_wait(sBar + B_FD, 0);
    STAMP(42);
    {
      const uint32_t a = sb + SM_WD + lane * 128 + (((w8 ^ lane) & 7) << 4);
#pragma unroll
      for (int i = 0; i < 9; i++) {
        uint32_t b0[4];
        ldsm4t(b0, a + i * 5120);
        asm volatile("ldmatrix.sync.aligned.m8n8.x1.trans.shared.b16 {%0}, [%1];" : "=r"(bd[i][4]) : "r"(a + i * 5120 + 4096) : "memory");
#pragma unroll
        for (int j = 0; j < 4; j++) bd[i][j] = b0[j];
      }
    }
    if (HX == 3) st_x();
    STAMP(43);
    mbar_wait(sBar + B_G3, 0);
    STAMP(76);
    {
      float c[2][3][4];
#pragma unroll
      for (int i = 0; i < 6; i++) c[i & 1][i >> 1][0] = c[i & 1][i >> 1][1] = c[i & 1][i >> 1][2] = c[i & 1][i >> 1][3] = 0.f;
      uint32_t hb[5][4];
#pragma unroll
      for (int i = 0; i < 5; i++) ldsm4(hb[i], sb + SM_T + T_H + (lane & 1) * 1152 + kq * 288 + (lane >> 3) * 16 + i * 64);
#pragma unroll
      for (int ks = 0; ks < 9; ks++) {
        const uint32_t h0 = hb[ks >> 1][(ks & 1) * 2], h1 = hb[ks >> 1][(ks & 1) * 2 + 1];
        mma16816(c[ks & 1][0], bg[ks][0], bg[ks][2], bg[ks][1], bg[ks][3], h0, h1);
        mma16816(c[ks & 1][1], bg[ks][4], bg[ks][6], bg[ks][5], bg[ks][7], h0, h1);
        mma16816(c[ks & 1][2], bg[ks][8], 0u, bg[ks][9], 0u, h0, h1);
      }
      float* const part = tsf + 64;
      const bool u1 = lane & 1, u2 = lane & 2;
#pragma unroll
      for (int i = 0; i < 3; i++) {
        const float v = (u2 ? (u1 ? c[0][i][3] : c[0][i][2]) : (u1 ? c[0][i][1] : c[0][i][0])) + (u2 ? (u1 ? c[1][i][3] : c[1][i][2]) : (u1 ? c[1][i][1] : c[1][i][0]));
        if (i < 2 || !u2) part[w8 * 80 + (t4 & 1) * 40 + i * 16 + (t4 >> 1) * 8 + g] = v;
      }
      STAMP(45);
      bar_sync(5, 256);
      STAMP(46);
      auto act2 = [&](int f) {
        const float2* pp = reinterpret_cast<const float2*>(part + (g & 1) * 40 + f + (b & 1) * 4);
        const float2 g0 = pp[0], g1 = pp[80], g2 = pp[160], g3 = pp[240], u0 = pp[40], u1 = pp[120], u2 = pp[200], u3 = pp[280];
        return pack_bf16(silu_bf(bfr((g0.x + g1.x) + (g2.x + g3.x))) * bfr((u0.x + u1.x) + (u2.x + u3.x)),
                         silu_bf(bfr((g0.y + g1.y) + (g2.y + g3.y))) * bfr((u0.y + u1.y) + (u2.y + u3.y)));
      };
      const uint32_t v0 = act2((g >> 1) * 8 + t4 * 2), v1 = act2(32 + (t4 & 1) * 2);
      uint32_t a6[5];
#pragma unroll
      for (int i = 0; i < 4; i++) a6[i] = __shfl_sync(~0u, v0, i * 8 + (lane & 7));
      a6[4] = t4 < 2 ? v1 : 0u;
      STAMP(47);
      float* const yp = reinterpret_cast<float*>(g_ones + F_YP) + b * 64 + g * 2;
      float y[5][4];
#pragma unroll
      for (int i = 0; i < 5; i++) {
        y[i][0] = y[i][1] = y[i][2] = y[i][3] = 0.f;
        mma16816(y[i], bd[2 * i][0], i < 4 ? bd[(2 * i + 1) % 9][0] : 0u, bd[2 * i][1], i < 4 ? bd[(2 * i + 1) % 9][1] : 0u, a6[0], a6[1]);
      }
#pragma unroll
      for (int i = 0; i < 5; i++) mma16816(y[i], bd[2 * i][2], i < 4 ? bd[(2 * i + 1) % 9][2] : 0u, bd[2 * i][3], i < 4 ? bd[(2 * i + 1) % 9][3] : 0u, a6[2], a6[3]);
#pragma unroll
      for (int i = 0; i < 5; i++) mma1688(y[i], bd[2 * i][4], i < 4 ? bd[(2 * i + 1) % 9][4] : 0u, a6[4]);
#pragma unroll
      for (int m = 0; m < 2; m++) {
        const float y0 = u2 ? (u1 ? y[2 * m + 1][2] : y[2 * m + 1][0]) : (u1 ? y[2 * m][2] : y[2 * m][0]);
        const float y1 = u2 ? (u1 ? y[2 * m + 1][3] : y[2 * m + 1][1]) : (u1 ? y[2 * m][3] : y[2 * m][1]);
        asm volatile("st.relaxed.gpu.global.v2.f32 [%0], {%1,%2};" ::"l"(yp + (m * 8 + w8) * 8192 + t4 * 16), "f"(y0), "f"(y1) : "memory");
      }
      if (t4 == 0) asm volatile("st.relaxed.gpu.global.v2.f32 [%0], {%1,%2};" ::"l"(yp + (16 + (w8 >> 2)) * 8192 + (w8 & 3) * 16), "f"(y[4][0]), "f"(y[4][1]) : "memory");
    }
    if (HX == 1) st_x();
    STAMP(78);
    if (b < 72) {
      const uint4* pp = g_ones + F_YP + (b >> 2) * 2048 + (w8 * 16 + g) * 16 + (b & 3) * 4 + t4;
      const uint4 none = make_uint4(~0u, ~0u, ~0u, ~0u);
      uint4 r0 = none, r1 = none, q[FK][2];
      PSTAMP(352, 62);
#pragma unroll
      for (int j = 0; j < FK; j++) {
        if (j) delay(FD);
        q[j][0] = ldr4(pp); q[j][1] = ldr4(pp + 128);
      }
      float gb, hv, sg;
      uint16_t xv = 0;
      bf16* op;
      if (w8 == 7) {
        const uint32_t k1 = tsu[32], k2 = tsu[33];
        const int row1 = ~k1 & (SQ - 1), row2 = ~k2 & (SQ - 1);
        const int tok = lane & 1, col = (b < 64 ? ((b >> 5) * 4 + (b & 3)) * 64 + (b & 28) * 2 : b * 8) + ((lane >> 1) & 7);
        const uint32_t key = tok ? k2 : k1;
        const int row = tok ? row2 : row1;
        const int c1 = ((row1 >> 5) & 3) * 32 + (row1 >> 7) * 2 + ((row1 >> 4) & 1), cr = ((row >> 5) & 3) * 32 + (row >> 7) * 2 + ((row >> 4) & 1);
        const uint16_t* xp = reinterpret_cast<const uint16_t*>(g_ones + F_HX + cr * 288 + (tok && c1 == cr ? 144 : 0) + 72) + col;
        gb = __uint_as_float((uint32_t)reinterpret_cast<const uint16_t*>(smem_raw + SM_MD)[(col >> 1) * 8 + 6 + (col & 1)] << 16);
        hv = __uint_as_float((uint32_t)reinterpret_cast<const uint16_t*>(smem_raw + SM_T + T_H)[tok * DM + col] << 16);
        sg = bfr(rcp(1.f + __expf(-__uint_as_float((key & 0xffff0000u) ^ ((key >> 31) ? 0x80000000u : 0xffff0000u)))));
        op = prm.out + (size_t)row * DM + col;
#pragma unroll 1
        for (uint32_t n = 0; n < (1u << 15); n++) {
          asm volatile("ld.relaxed.gpu.global.u16 %0, [%1];" : "=h"(xv) : "l"(xp) : "memory");
          if (xv != 0xffff) break;
        }
        __syncwarp();
      }
#pragma unroll 1
      for (uint32_t n = 0;; n++) {
        bool done = false;
#pragma unroll
        for (int j = 0; j < FK; j++) {
          if (unset(r0)) r0 = q[j][0];
          if (unset(r1)) r1 = q[j][1];
          const bool m0 = unset(r0), m1 = unset(r1);
          if (!__any_sync(~0u, m0 || m1)) { done = true; break; }
          if (m0) q[j][0] = ldr4(pp);
          if (m1) q[j][1] = ldr4(pp + 128);
        }
        if (done) break;
        if (n > (1u << 14)) { SETERR(32); break; }
      }
      PSTAMP(352, 63);
      float s[4] = {__uint_as_float(r0.x) + __uint_as_float(r1.x), __uint_as_float(r0.y) + __uint_as_float(r1.y),
                    __uint_as_float(r0.z) + __uint_as_float(r1.z), __uint_as_float(r0.w) + __uint_as_float(r1.w)};
      const bool u4 = lane & 4, u8 = lane & 8;
#pragma unroll
      for (int i = 0; i < 2; i++) { const float snd = u4 ? s[i] : s[i + 2], kp = u4 ? s[i + 2] : s[i]; s[i] = kp + __shfl_xor_sync(~0u, snd, 4); }
      { const float snd = u8 ? s[0] : s[1], kp = u8 ? s[1] : s[0]; s[0] = kp + __shfl_xor_sync(~0u, snd, 8); }
      s[0] += __shfl_xor_sync(~0u, s[0], 16);
      float* const fs = reinterpret_cast<float*>(smem_raw + SM_PS);
      if (lane < 16) fs[(t4 * 4 + (g & 1) * 2 + (g >> 1)) * 8 + w8] = s[0];
      if (w8 < 7) bar_arrive(5, 256);
      else {
        bar_sync(5, 256);
        const float4 a = *reinterpret_cast<const float4*>(fs + (lane & 15) * 8), c = *reinterpret_cast<const float4*>(fs + (lane & 15) * 8 + 4);
        const float hh = bfr(hv + bfr(bfr(((a.x + a.y) + (a.z + a.w)) + ((c.x + c.y) + (c.z + c.w))) * sg));
        if (lane < 16) *op = __float2bfloat16(__uint_as_float((uint32_t)xv << 16) + bfr(gb * hh));
      }
      PSTAMP(352, 49);
    }
    if (w8 == 5 && lane < 9) g_mod1[b * 9 + lane] = make_uint4(0u, 0u, 0u, 0u);
    if (w8 == 5 && lane == 9) *reinterpret_cast<uint4*>(&g_cnt[(C_Q + b) * 32]) = make_uint4(0u, 0u, 0u, 0u);
    if (w8 == 5 && lane == 10 && b < 2) g_cnt[(C_SIDE + b) * 32] = 0;
    STAMP(79); GSTAMP(91);
    }
  }
}

typedef CUresult (*PFN_enc)(CUtensorMap*, CUtensorMapDataType, cuuint32_t, void*, const cuuint64_t*, const cuuint64_t*,
                            const cuuint32_t*, const cuuint32_t*, CUtensorMapInterleave, CUtensorMapSwizzle,
                            CUtensorMapL2promotion, CUtensorMapFloatOOBfill);
static PFN_enc g_enc = nullptr;
static uint4* g_mod1_p = nullptr;
static CUtensorMap mk_map(const void* p, uint64_t cols, uint64_t rows, uint32_t bc, uint32_t br, bool swz = true) {
  CUtensorMap m;
  cuuint64_t dims[2] = {cols, rows};
  cuuint64_t strides[1] = {cols * 2};
  cuuint32_t box[2] = {bc, br}, es[2] = {1, 1};
  g_enc(&m, CU_TENSOR_MAP_DATA_TYPE_BFLOAT16, 2, const_cast<void*>(p), dims, strides, box, es, CU_TENSOR_MAP_INTERLEAVE_NONE,
        swz ? CU_TENSOR_MAP_SWIZZLE_128B : CU_TENSOR_MAP_SWIZZLE_NONE, swz ? CU_TENSOR_MAP_L2_PROMOTION_L2_128B : CU_TENSOR_MAP_L2_PROMOTION_NONE,
        CU_TENSOR_MAP_FLOAT_OOB_FILL_NONE);
  return m;
}

static CUtensorMap mk_map_n(const void* p, int n, const cuuint64_t* dims, const cuuint64_t* strides, const cuuint32_t* box) {
  CUtensorMap m;
  cuuint32_t es[4] = {1, 1, 1, 1};
  g_enc(&m, CU_TENSOR_MAP_DATA_TYPE_BFLOAT16, n, const_cast<void*>(p), dims, strides, box, es, CU_TENSOR_MAP_INTERLEAVE_NONE,
        CU_TENSOR_MAP_SWIZZLE_128B, CU_TENSOR_MAP_L2_PROMOTION_L2_128B, CU_TENSOR_MAP_FLOAT_OOB_FILL_NONE);
  return m;
}

extern "C" void kernel_launch(void* const* d_in, const int* in_sizes, int n_in, void* d_out, int out_size) {
  if (!g_enc) {
    cudaDriverEntryPointQueryResult st;
    cudaGetDriverEntryPoint("cuTensorMapEncodeTiled", (void**)&g_enc, cudaEnableDefault, &st);
    cudaFuncSetAttribute(k_mega, cudaFuncAttributeMaxDynamicSharedMemorySize, SM_TOTAL);
    cudaGetSymbolAddress((void**)&g_mod1_p, g_mod1);
  }
  const cuuint64_t xd[3] = {64, SQ, 9}, xs[2] = {DM * 2, 128};
  const cuuint32_t xb[3] = {64, 32, 9};
  CUtensorMap mX = mk_map_n(d_in[0], 3, xd, xs, xb);
  CUtensorMap mWq = mk_map(d_in[3], HQ * DH, DM, 64, 144);
  CUtensorMap mK = mk_map(d_in[1], DH, HKV * SK, 64, 128);
  CUtensorMap mV = mk_map(d_in[2], DH, HKV * SK, 64, 128);
  const cuuint64_t od[4] = {DM, DH, 2, HKV}, os[3] = {DM * 2, DH * DM * 2, 2 * DH * DM * 2};
  const cuuint32_t ob[4] = {64, DH, 1, 2};
  CUtensorMap mWo = mk_map_n(d_in[4], 4, od, os, ob);
  const cuuint32_t ob0[4] = {64, DH - KO * 16, 1, 1}, ob1[4] = {64, DH, 1, 1}, obh[4] = {64, KO ? KO * 16 : 16, 2, 4};
  const cuuint64_t hd[4] = {DM, DH, 2, 4}, hs[3] = {DM * 2, DH * DM * 2, 8 * DH * DM * 2};
  CUtensorMap mWo0 = mk_map_n(d_in[4], 4, od, os, ob0), mWo1 = mk_map_n(d_in[4], 4, od, os, ob1), mWh = mk_map_n(d_in[4], 4, hd, hs, obh);
  CUtensorMap mXh = mk_map(d_in[0], DM, SQ, 64, 64);
  CUtensorMap mWg = mk_map(d_in[7], FF, DM, 40, 144, false);
  CUtensorMap mWu = mk_map(d_in[8], FF, DM, 40, 144, false);
  const cuuint64_t dd[3] = {64, FF, 9}, ds[2] = {DM * 2, 128};
  const cuuint32_t db[3] = {64, 40, 9};
  CUtensorMap mWd = mk_map_n(d_in[9], 3, dd, ds, db);
  CUtensorMap mM = mk_map(d_in[11], 6 * DM, DM, 16, 192, false);
  Params prm;
  prm.x = (const bf16*)d_in[0]; prm.k = (const bf16*)d_in[1]; prm.v = (const bf16*)d_in[2]; prm.wo = (const bf16*)d_in[4]; prm.wq = (const bf16*)d_in[3];
  prm.w_r = (const bf16*)d_in[6]; prm.c = (const bf16*)d_in[10]; prm.w_mod = (const bf16*)d_in[11];
  prm.wg = (const bf16*)d_in[7]; prm.wu = (const bf16*)d_in[8]; prm.wd = (const bf16*)d_in[9];
  prm.out = (bf16*)d_out;
  prm.mod1 = g_mod1_p;
  cudaLaunchConfig_t cfg = {};
  cfg.gridDim = dim3(132); cfg.blockDim = dim3(384); cfg.dynamicSmemBytes = SM_TOTAL; cfg.stream = cudaStreamPerThread;
  cudaLaunchAttribute at[1];
  at[0].id = cudaLaunchAttributeClusterDimension;
  at[0].val.clusterDim.x = 2; at[0].val.clusterDim.y = 1; at[0].val.clusterDim.z = 1;
  cfg.attrs = at; cfg.numAttrs = 1;
  cudaLaunchKernelEx(&cfg, k_mega, prm, mX, mWq, mK, mV, mWo, mWg, mWu, mWd, mM, mWo0, mWo1, mWh, mXh);
}
```
